```python
import torch

def _softmax(x, axis=-1):
    return torch.softmax(x, dim=axis)
def _gelu(x):
    return torch.nn.functional.gelu(x, approximate="tanh")
def _silu(x):
    return torch.nn.functional.silu(x)
def _sigmoid(x):
    return torch.sigmoid(x)
def _layernorm(x, axis=-1, eps=1e-5):
    m = x.mean(dim=axis, keepdim=True)
    v = x.var(dim=axis, keepdim=True, unbiased=False)
    return (x - m) / torch.sqrt(v + eps)
def _scatter_add(tgt, idx, src, axis=0):
    return tgt.clone().index_add_(axis, idx, src)
def _segment_sum(src, seg, n):
    out = torch.zeros((n,) + src.shape[1:], dtype=src.dtype)
    return out.index_add_(0, seg, src)
def _pad(x, pw):
    flat = tuple(v for pair in reversed(pw) for v in pair)
    return torch.nn.functional.pad(x, flat)

kernel_name = 'gated_mix__ssm_conv_s5__moe_arch_mod__prompt'

def setup_inputs():

    _w = (lambda a: (lambda t: t.to(torch.bfloat16) if t.is_floating_point() else t)(torch.as_tensor(a)))
    def _A_setup():
        B, S, D = 1, 2048, 1024
        P = D
        Lambda_re = -0.5 * (lambda _x: torch.exp(torch.as_tensor(_x)))((lambda *s: torch.randn(*s, dtype=torch.bfloat16) * 0.8)(P))
        Lambda_im = (lambda *s: torch.randn(*s, dtype=torch.bfloat16) * 0.8)(P) * 1.0
        B_re = (lambda *s: torch.randn(*s, dtype=torch.bfloat16) * 0.8)(P, D) * (D ** -0.5)
        B_im = (lambda *s: torch.randn(*s, dtype=torch.bfloat16) * 0.8)(P, D) * (D ** -0.5)
        C_re = (lambda *s: torch.randn(*s, dtype=torch.bfloat16) * 0.8)(D, P) * (P ** -0.5)
        C_im = (lambda *s: torch.randn(*s, dtype=torch.bfloat16) * 0.8)(D, P) * (P ** -0.5)
        log_dt = (lambda *s: torch.randn(*s, dtype=torch.bfloat16) * 0.8)(P) * 0.3 - 2.0
        Dskip = (lambda *s: torch.randn(*s, dtype=torch.bfloat16) * 0.8)(D)
        return {
            "x": _w((lambda *s: torch.randn(*s, dtype=torch.bfloat16) * 0.05)(B, S, D)),
            "Lambda_re": _w(Lambda_re),
            "Lambda_im": _w(Lambda_im),
            "B_re": _w(B_re),
            "B_im": _w(B_im),
            "C_re": _w(C_re),
            "C_im": _w(C_im),
            "log_dt": _w(log_dt),
            "Dskip": _w(Dskip),
        }
    _A_in = _A_setup()

    def _B_setup():
        B, S, D, F, C = 1, 2048, 1024, 3584, 8
        return {
            "x": _w((lambda *s: torch.randn(*s, dtype=torch.bfloat16) * 0.05)(B, S, D)),
            "w_r": _w((lambda *s: torch.randn(*s, dtype=torch.bfloat16) * 1.6)(D)),
            "w_gate": _w((lambda *s: torch.randn(*s, dtype=torch.bfloat16) * 0.1)(D, F)),
            "w_up": _w((lambda *s: torch.randn(*s, dtype=torch.bfloat16) * 0.1)(D, F)),
            "w_down": _w((lambda *s: torch.randn(*s, dtype=torch.bfloat16) * 0.1)(F, D)),
        }
    _B_in = _B_setup()

    return {
        "A_x": _A_in["x"],
        "A_Lambda_re": _A_in["Lambda_re"],
        "A_Lambda_im": _A_in["Lambda_im"],
        "A_B_re": _A_in["B_re"],
        "A_B_im": _A_in["B_im"],
        "A_C_re": _A_in["C_re"],
        "A_C_im": _A_in["C_im"],
        "A_log_dt": _A_in["log_dt"],
        "A_Dskip": _A_in["Dskip"],
        "B_x": _B_in["x"],
        "B_w_r": _B_in["w_r"],
        "B_w_gate": _B_in["w_gate"],
        "B_w_up": _B_in["w_up"],
        "B_w_down": _B_in["w_down"],
        "gate_w": _w((lambda *s: torch.randn(*s, dtype=torch.bfloat16) * 0.05)(1024) * 16.0),
    }

def reference(A_x, A_Lambda_re, A_Lambda_im, A_B_re, A_B_im, A_C_re, A_C_im, A_log_dt, A_Dskip, B_x, B_w_r, B_w_gate, B_w_up, B_w_down, gate_w):
    def _A_ref(x, Lambda_re, Lambda_im, B_re, B_im, C_re, C_im, log_dt, Dskip):
        Bsz, L, H = x.shape
        Lam = Lambda_re + 1j * Lambda_im
        Bmat = B_re + 1j * B_im
        Cmat = C_re + 1j * C_im
        dt = torch.exp(log_dt)
        Lam_bar = torch.exp(dt * Lam)
        B_bar = ((Lam_bar - 1.0) / Lam)[:, None] * Bmat
        Bu = torch.einsum("bld,pd->blp", x + 0j, B_bar)
        h = torch.zeros_like(Bu[:, 0, :])
        hs = []
        for t in range(L):
            h = Lam_bar[None, :] * h + Bu[:, t, :]
            hs.append(h)
        hseq = torch.stack(hs, 1)
        y = 2.0 * torch.einsum("blp,dp->bld", hseq, Cmat).real + x * Dskip[None, None, :]
        return y

    def _B_ref(x, w_r, w_gate, w_up, w_down):
        B, S, D = x.shape
        C = 8
        r = x @ w_r
        idx = torch.argsort(-r, axis=-1)[:, :C]
        idx_e = (lambda x, n, axis: torch.repeat_interleave(x, n, dim=axis))(idx.reshape(B, C, 1), D, axis=2)
        x_sel = (lambda x, i, axis: torch.take_along_dim(x, i, dim=axis))(x, idx_e, axis=1)
        g = _silu(x_sel @ w_gate)
        u = x_sel @ w_up
        y = (g * u) @ w_down
        r_sel = _sigmoid((lambda x, i, axis: torch.take_along_dim(x, i, dim=axis))(r, idx, axis=1))
        y = y * r_sel.reshape(B, C, 1)
        b_off = (torch.arange(B) * S).reshape(B, 1)
        flat_idx = (idx + b_off).reshape(B * C)
        zero = (x * 0.0).reshape(B * S, D)
        upd = _scatter_add(zero, flat_idx, y.reshape(B * C, D), axis=0)
        return x + upd.reshape(B, S, D)

    x = A_x
    g = _sigmoid((x * gate_w).sum(-1, keepdims=True))
    a = _A_ref(x, A_Lambda_re, A_Lambda_im, A_B_re, A_B_im, A_C_re, A_C_im, A_log_dt, A_Dskip)
    b = _B_ref(x, B_w_r, B_w_gate, B_w_up, B_w_down)
    return g * a + (1 - g) * b
```

```cpp
#include <cuda_runtime.h>
#include <cuda_bf16.h>
#include <cuda.h>
#include <stdint.h>

namespace {

constexpr int S_ = 2048, D_ = 1024, F_ = 3584;
constexpr int NCTA = 128, NGRID = 132;
constexpr int NENT = 72;
constexpr int NST = 5;
constexpr int RE0 = 4;
constexpr int GU0 = 20;
constexpr uint32_t SLOT = 32768, SMALL = 24576, ABYTES = 8192, WBYTES = 4096;
constexpr uint32_t OFF_XS = NST * SLOT;
constexpr uint32_t OFF_LIST = OFF_XS + 8192;
constexpr uint32_t OFF_W = OFF_XS + 16384;
constexpr uint32_t OFF_STG = OFF_W + 32768;
constexpr uint32_t OFF_DN = OFF_XS + 8192;
constexpr uint32_t OFF_CONST = OFF_STG;
constexpr uint32_t OFF_RED = OFF_STG + 4096;
constexpr uint32_t OFF_FULL = OFF_STG + 16384;
constexpr uint32_t OFF_EMPTY = OFF_FULL + 80 * 8;
constexpr uint32_t OFF_G = OFF_EMPTY + 96 * 8;
constexpr uint32_t OFF_DK = OFF_G + 320;
constexpr uint32_t OFF_KEYS = OFF_DK + 256;
constexpr uint32_t OFF_SEL = OFF_KEYS + 32;
constexpr uint32_t OFF_FAC = OFF_SEL + 32;
constexpr uint32_t OFF_EPOCH = OFF_FAC + 32;
constexpr uint32_t OFF_PROF = OFF_EPOCH + 16;
constexpr uint32_t SMEM_BYTES = OFF_PROF + 896;
static_assert(SMEM_BYTES <= 232448, "smem");

constexpr uint32_t SPIN_LIMIT = 1u << 18;

__device__ uint4 g_h[8 * 4 * 256 * 64];
__device__ unsigned long long g_rpack[S_ / 2];
__device__ unsigned long long g_gpack[S_ / 2];
__device__ float2 g_carry[16 * 1024];
__device__ unsigned int g_cnt[80 * 32];
__device__ unsigned int g_base[64 * 8];
__device__ __nv_bfloat16 g_hid[2 * 8 * F_];
#define STAMPW(cond, w) do {} while (0)
#define LATE(i, tt) do {} while (0)
#define STAMPIF(cond, i) STAMPW(cond, 80 + (i))
#define STAMP(i) STAMPW(1, 80 + (i))
#define KSTAMP(i) STAMPW((threadIdx.x & 127) == 0, i)

struct Params {
    const __nv_bfloat16 *x, *lam_re, *lam_im, *b_re, *b_im, *c_re, *c_im, *log_dt, *dskip, *w_r, *gate_w;
    float* out;
    int swapped;
};

__device__ __forceinline__ uint32_t smem_u32(const void* p) { return (uint32_t)__cvta_generic_to_shared(p); }
__device__ __forceinline__ void mbar_init(uint32_t bar, uint32_t cnt) { asm volatile("mbarrier.init.shared::cta.b64 [%0], %1;" ::"r"(bar), "r"(cnt) : "memory"); }
__device__ __forceinline__ void mbar_expect_tx(uint32_t bar, uint32_t bytes) { asm volatile("mbarrier.arrive.expect_tx.shared::cta.b64 _, [%0], %1;" ::"r"(bar), "r"(bytes) : "memory"); }
__device__ __forceinline__ void mbar_arrive(uint32_t bar) { asm volatile("mbarrier.arrive.shared::cta.b64 _, [%0];" ::"r"(bar) : "memory"); }
__device__ __forceinline__ bool mbar_try(uint32_t bar) {
    uint32_t ok;
    asm volatile("{ .reg .pred p; mbarrier.try_wait.parity.shared::cta.b64 p, [%1], 0; selp.u32 %0, 1, 0, p; }" : "=r"(ok) : "r"(bar) : "memory");
    return ok;
}
__device__ __forceinline__ void mbar_wait(uint32_t bar) {
    if (mbar_try(bar)) return;
#pragma unroll 1
    for (uint32_t it = 0; it < SPIN_LIMIT; ++it)
        if (mbar_try(bar)) return;
    __trap();
}
__device__ __forceinline__ bool elect_one() {
    uint32_t pred;
    asm volatile("{ .reg .pred P; elect.sync _|P, 0xffffffff; selp.b32 %0, 1, 0, P; }" : "=r"(pred));
    return pred;
}
__device__ __forceinline__ void named_bar(int id, int n) { asm volatile("bar.sync %0, %1;" ::"r"(id), "r"(n) : "memory"); }

__device__ __forceinline__ void bulk_load(uint32_t dst, const void* src, uint32_t bytes, uint32_t bar) {
    asm volatile("cp.async.bulk.shared::cluster.global.mbarrier::complete_tx::bytes [%0], [%1], %2, [%3];" ::"r"(dst), "l"(src), "r"(bytes), "r"(bar) : "memory");
}
__device__ __forceinline__ void sts128(uint32_t a, uint32_t x, uint32_t y, uint32_t z, uint32_t w) {
    asm volatile("st.shared.v4.u32 [%0], {%1,%2,%3,%4};" ::"r"(a), "r"(x), "r"(y), "r"(z), "r"(w) : "memory");
}
__device__ __forceinline__ uint2 lds64(uint32_t a) {
    uint2 v;
    asm volatile("ld.shared.v2.u32 {%0,%1}, [%2];" : "=r"(v.x), "=r"(v.y) : "r"(a) : "memory");
    return v;
}
__device__ __forceinline__ uint32_t clk32() { uint32_t c; asm volatile("mov.u32 %0, %%clock;" : "=r"(c)); return c; }
__device__ __forceinline__ void pace_until(uint32_t t) { while ((int)(clk32() - t) < 0) {} }
#define SLEEP_MARGIN 200
__device__ __forceinline__ void sleep_until(uint32_t t) {
    while ((int)(clk32() + SLEEP_MARGIN - t) < 0) __nanosleep(40);
    pace_until(t);
}
__device__ __forceinline__ void tma2(uint32_t dst, const CUtensorMap* m, int c0, int c1, uint32_t bar) {
    asm volatile("cp.async.bulk.tensor.2d.shared::cluster.global.mbarrier::complete_tx::bytes [%0], [%1, {%3, %4}], [%2];"
                 ::"r"(dst), "l"(m), "r"(bar), "r"(c0), "r"(c1) : "memory");
}
__device__ __forceinline__ void tma3(uint32_t dst, const CUtensorMap* m, int c0, int c1, uint32_t bar) {
    asm volatile("cp.async.bulk.tensor.3d.shared::cluster.global.mbarrier::complete_tx::bytes [%0], [%1, {%3, %4, %5}], [%2];"
                 ::"r"(dst), "l"(m), "r"(bar), "r"(c0), "r"(c1), "r"(0) : "memory");
}
__device__ __forceinline__ void tma4(uint32_t dst, const CUtensorMap* m, int c0, int c3, uint32_t bar) {
    asm volatile("cp.async.bulk.tensor.4d.shared::cluster.global.mbarrier::complete_tx::bytes [%0], [%1, {%3, %5, %5, %4}], [%2];"
                 ::"r"(dst), "l"(m), "r"(bar), "r"(c0), "r"(c3), "r"(0) : "memory");
}
__device__ __forceinline__ void tma5(uint32_t dst, const CUtensorMap* m, int c0, int c4, uint32_t bar) {
    asm volatile("cp.async.bulk.tensor.5d.shared::cluster.global.mbarrier::complete_tx::bytes [%0], [%1, {%3, %5, %5, %5, %4}], [%2];"
                 ::"r"(dst), "l"(m), "r"(bar), "r"(c0), "r"(c4), "r"(0) : "memory");
}
__device__ __forceinline__ void tma5b(uint32_t dst, const CUtensorMap* m, int c0, int c3, uint32_t bar) {
    asm volatile("cp.async.bulk.tensor.5d.shared::cluster.global.mbarrier::complete_tx::bytes [%0], [%1, {%3, %5, %5, %4, %5}], [%2];"
                 ::"r"(dst), "l"(m), "r"(bar), "r"(c0), "r"(c3), "r"(0) : "memory");
}
__device__ __forceinline__ void prefetch_l2(const void* p) {
    asm volatile("prefetch.global.L2 [%0];" ::"l"(p));
}

__device__ __forceinline__ uint32_t lds32(uint32_t a) {
    uint32_t v;
    asm volatile("ld.volatile.shared.u32 %0, [%1];" : "=r"(v) : "r"(a) : "memory");
    return v;
}
__device__ __forceinline__ uint32_t uni(uint32_t v) { return __shfl_sync(0xffffffffu, v, 0); }   __device__ __forceinline__ uint32_t ld_acquire(const unsigned int* p) {
    uint32_t v;
    asm volatile("ld.acquire.gpu.global.u32 %0, [%1];" : "=r"(v) : "l"(p) : "memory");
    return v;
}
__device__ __forceinline__ void red_release(unsigned int* p) { asm volatile("red.release.gpu.global.add.u32 [%0], 1;" ::"l"(p) : "memory"); }
__device__ __forceinline__ void wait_count(const unsigned int* p, uint32_t target) {
#pragma unroll 1
    for (uint32_t it = 0; it < SPIN_LIMIT; ++it)
        if ((int)(ld_acquire(p) - target) >= 0) return;
    __trap();
}
__device__ __forceinline__ void wait_count_slow(const unsigned int* p, uint32_t target) {
#pragma unroll 1
    for (uint32_t it = 0; it < SPIN_LIMIT; ++it) {
        if ((int)(ld_acquire(p) - target) >= 0) return;
        __nanosleep(200);
    }
    __trap();
}
__device__ __forceinline__ unsigned long long ld_relaxed1(const void* p) {
    unsigned long long v;
    asm volatile("ld.relaxed.gpu.global.b64 %0, [%1];" : "=l"(v) : "l"(p) : "memory");
    return v;
}
__device__ __forceinline__ ulonglong2 ld_relaxed2(const void* p) {
    ulonglong2 v;
    asm volatile("ld.relaxed.gpu.global.v2.b64 {%0, %1}, [%2];" : "=l"(v.x), "=l"(v.y) : "l"(p) : "memory");
    return v;
}
__device__ __forceinline__ uint4 ldg_cg128(const void* p) {
    uint4 v;
    asm volatile("ld.global.cg.v4.u32 {%0,%1,%2,%3}, [%4];" : "=r"(v.x), "=r"(v.y), "=r"(v.z), "=r"(v.w) : "l"(p) : "memory");
    return v;
}

__device__ __forceinline__ uint64_t make_desc(uint32_t addr, uint32_t sbo = 1024) {
    return (uint64_t)((addr & 0x3FFFF) >> 4) | ((uint64_t)1 << 16) | ((uint64_t)(sbo >> 4) << 32) | ((uint64_t)1 << 62);
}
__device__ __forceinline__ void wgmma_fence() { asm volatile("wgmma.fence.sync.aligned;" ::: "memory"); }
__device__ __forceinline__ void wgmma_commit() { asm volatile("wgmma.commit_group.sync.aligned;" ::: "memory"); }
template <int N> __device__ __forceinline__ void wgmma_wait() { asm volatile("wgmma.wait_group.sync.aligned %0;" ::"n"(N) : "memory"); }

#define R8(d, i) "+f"(d[i]), "+f"(d[i + 1]), "+f"(d[i + 2]), "+f"(d[i + 3]), "+f"(d[i + 4]), "+f"(d[i + 5]), "+f"(d[i + 6]), "+f"(d[i + 7])
#define R64(d) R8(d, 0), R8(d, 8), R8(d, 16), R8(d, 24), R8(d, 32), R8(d, 40), R8(d, 48), R8(d, 56)
template <int TA>
__device__ __forceinline__ void wgmma_n128(float (&d)[64], uint64_t da, uint64_t db, int scale_d = 1) {
    asm volatile("{ .reg .pred p; setp.ne.b32 p, %66, 0;\n"
                 "wgmma.mma_async.sync.aligned.m64n128k16.f32.bf16.bf16 "
                 "{%0,%1,%2,%3,%4,%5,%6,%7,%8,%9,%10,%11,%12,%13,%14,%15,%16,%17,%18,%19,%20,%21,%22,%23,%24,%25,%26,%27,%28,%29,%30,%31,"
                 "%32,%33,%34,%35,%36,%37,%38,%39,%40,%41,%42,%43,%44,%45,%46,%47,%48,%49,%50,%51,%52,%53,%54,%55,%56,%57,%58,%59,%60,%61,%62,%63}, "
                 "%64, %65, p, 1, 1, %67, 0; }"
                 : R64(d)
                 : "l"(da), "l"(db), "r"(scale_d), "n"(TA));
}
__device__ __forceinline__ void pin4(float (&d)[4]) { asm volatile("" : "+f"(d[0]), "+f"(d[1]), "+f"(d[2]), "+f"(d[3])::"memory"); }
__device__ __forceinline__ void pin64(float (&d)[64]) { asm volatile("" : R64(d)::"memory"); }

template <int TA>
__device__ __forceinline__ void wgmma_n8(float (&d)[4], uint64_t da, uint64_t db, int scale_d = 1) {
    asm volatile("{ .reg .pred p; setp.ne.b32 p, %7, 0;\n"
                 "wgmma.mma_async.sync.aligned.m64n8k16.f32.bf16.bf16 {%0,%1,%2,%3}, %4, %5, p, 1, 1, %6, 0; }"
                 : "+f"(d[0]), "+f"(d[1]), "+f"(d[2]), "+f"(d[3])
                 : "l"(da), "l"(db), "n"(TA), "r"(scale_d));
}

__device__ __forceinline__ float bf_lo(uint32_t u) { return __uint_as_float(u << 16); }
__device__ __forceinline__ float bf_hi(uint32_t u) { return __uint_as_float(u & 0xFFFF0000u); }
__device__ __forceinline__ float rbf(float v) { return __bfloat162float(__float2bfloat16_rn(v)); }
__device__ __forceinline__ uint32_t pack_bf(float lo, float hi) {
    uint32_t r;
    asm("cvt.rn.bf16x2.f32 %0, %1, %2;" : "=r"(r) : "f"(hi), "f"(lo));
    return r;
}
__device__ __forceinline__ uint32_t mul_bf2(uint32_t a, uint32_t b) {
    __nv_bfloat162 r = __hmul2(*reinterpret_cast<__nv_bfloat162*>(&a), *reinterpret_cast<__nv_bfloat162*>(&b));
    return *reinterpret_cast<uint32_t*>(&r);
}
__device__ __forceinline__ float2 cmul(float2 a, float2 b) { return make_float2(a.x * b.x - a.y * b.y, a.x * b.y + a.y * b.x); }
__device__ __forceinline__ float2 cfma(float2 a, float2 b, float2 c) {
    return make_float2(fmaf(a.x, b.x, fmaf(-a.y, b.y, c.x)), fmaf(a.x, b.y, fmaf(a.y, b.x, c.y)));
}
__device__ __forceinline__ float sigmoidf_(float v) { return __fdividef(1.0f, 1.0f + expf(-v)); }

__device__ __forceinline__ void bulk_store(void* dst, uint32_t src, uint32_t bytes) {
    asm volatile("cp.async.bulk.global.shared::cta.bulk_group [%0], [%1], %2;" ::"l"(dst), "r"(src), "r"(bytes) : "memory");
}
__device__ __forceinline__ float4 lds128f(uint32_t a) {
    float4 v;
    asm volatile("ld.shared.v4.f32 {%0,%1,%2,%3}, [%4];" : "=f"(v.x), "=f"(v.y), "=f"(v.z), "=f"(v.w) : "r"(a) : "memory");
    return v;
}
__device__ __forceinline__ uint2 ldg64(const void* p) {
    uint2 v;
    asm volatile("ld.global.nc.v2.u32 {%0,%1}, [%2];" : "=r"(v.x), "=r"(v.y) : "l"(p));
    return v;
}
__device__ __forceinline__ void put4(float* p, float a, float b, float c, float d, uint32_t routed) {
    asm volatile("{ .reg .pred p; setp.ne.u32 p, %5, 0;\n"
                 "@p red.global.add.v4.f32 [%0], {%1,%2,%3,%4};\n"
                 "@!p st.global.v4.f32 [%0], {%1,%2,%3,%4}; }" ::"l"(p), "f"(a), "f"(b), "f"(c), "f"(d), "r"(routed) : "memory");
}

#define TT0 3300
#define P1 516
#define P2 520
#define P3 520
#define P4 260
#define PF0 500
#define PF_PACE 350
#define PF2_PACE 450
#define G0 900
#define R0 3000
#define R_PACE 400
#define W_SHIFT 310
#define PROMO CU_TENSOR_MAP_L2_PROMOTION_L2_256B
#define H_SHIFT 150
#define PSCAN 100
#define ST_PACE 450
#define DN_PACE 600
constexpr bool is_small(int i) { return i >= 64 || (i >= 52 && (i - 52) % 3 != 2); }
constexpr uint32_t duration(int i) {
    return (is_small(i) ? P4 : i < 16 ? P1 : i < 32 ? P2 : P3) + (i >= RE0 && i < RE0 + 4 ? 72 : 0) + (i >= GU0 && i < GU0 + 32 ? 36 : 0) +
           (i == 16 || i == 32 ? PSCAN : 0);
}
constexpr uint32_t issue_time(int i) { return i <= NST ? TT0 : issue_time(i - 1) + duration(i - NST); }
constexpr uint32_t PMIN = 240;
constexpr uint64_t pack_periods(int i0) {
    uint64_t r = 0;
    for (int k = 0; k < 8; k++) r |= (uint64_t)((issue_time(i0 + k + 1) / 8 - issue_time(i0 + k) / 8 - PMIN / 8) & 255) << (8 * k);
    return r;
}
template <int I> struct Sched { static constexpr uint32_t t = issue_time(I) / 8 * 8; static constexpr uint64_t p = pack_periods(I); };
template <int LO, int HI, class F>
__device__ __forceinline__ void for_entries(uint32_t base, F body) {
    uint32_t tt = base + Sched<LO>::t;
    uint64_t pk = Sched<LO>::p;
#pragma unroll 1
    for (int i = LO; i < HI; i++) {
        body(i, tt);
        tt += PMIN + 8 * ((uint32_t)pk & 255u);
        pk >>= 8;
        if (LO + 8 < HI && i == LO + 7) pk = Sched<LO + 8>::p;
        if (LO + 16 < HI && i == LO + 15) pk = Sched<LO + 16>::p;
        static_assert(HI - LO <= 24, "segment too long");
    }
}

struct Ring { uint32_t sb, prev; int slot; };
struct NoHook { __device__ void operator()() const {} };
template <int TA, int SM, class H = NoHook>
__device__ __forceinline__ void run_entries(Ring& r, int lo, int hi, float (&accA)[64], float (&accB)[64], float (&small)[4],
                                            bool fresh = false, bool sfresh = false, H released = H()) {
    const uint32_t sb = r.sb;
    const uint64_t d0 = make_desc(sb);
    const bool leader = (threadIdx.x & 31) == 0;
#pragma unroll 1
    for (int i = lo; i < hi; i++) {
        const uint32_t bar = sb + OFF_FULL + 8 * i;
        const uint64_t da = d0 + (uint64_t)(r.slot * (SLOT >> 4));
        const int n = i - (SM == 1 ? RE0 : GU0);
        const uint64_t dw = d0 + (uint64_t)((OFF_W >> 4) + (SM == 1 ? n * 512 : (n & 7) * 256));
        const uint64_t dt8 = d0 + (uint64_t)((OFF_XS >> 4) + (SM == 1 ? n * 64 : (n >> 1) * 64 + (n & 1) * 4));
        r.slot = r.slot == NST - 1 ? 0 : r.slot + 1;
        mbar_wait(bar);
        KSTAMP(i);
        wgmma_fence();
#pragma unroll
        for (int kk = 0; kk < 4; kk++) {
            wgmma_n128<TA>(accA, da + kk * (TA ? 128 : 2), da + 1024 + kk * 2, kk > 0 || !fresh);
            if (SM == 1) wgmma_n8<0>(small, dw + kk * 2, dt8 + kk * 2, kk > 0 || !sfresh);
            if (SM == 2 && (kk & 1)) wgmma_n8<1>(small, dw + (kk >> 1) * 128, dt8 + (kk >> 1) * 2, kk > 1 || !sfresh);
            wgmma_n128<TA>(accB, da + 512 + kk * (TA ? 128 : 2), da + 1024 + kk * 2, kk > 0 || !fresh);
            if (kk == 1) {
                wgmma_commit();
                wgmma_wait<1>();
                if (leader) mbar_arrive(r.prev);
                released();
            }
        }
        wgmma_commit();
        r.prev = bar + (OFF_EMPTY - OFF_FULL);
        fresh = sfresh = false;
    }
}
template <int HALF>
__device__ __forceinline__ void run_small(Ring& r, int i, float (&acc)[64]) {
    const uint32_t sb = r.sb, bar = sb + OFF_FULL + 8 * i;
    const uint64_t da = make_desc(sb) + (uint64_t)(r.slot * (SLOT >> 4));
    r.slot = r.slot == NST - 1 ? 0 : r.slot + 1;
    mbar_wait(bar);
    KSTAMP(i);
    wgmma_fence();
#pragma unroll
    for (int kk = 0; kk < 4; kk++) wgmma_n128<1>(acc, da + HALF * 512 + kk * 128, da + 1024 + kk * 2);
    wgmma_commit();
    wgmma_wait<1>();
    if ((threadIdx.x & 31) == 0) mbar_arrive(r.prev);
    r.prev = bar + (OFF_EMPTY - OFF_FULL);
}

__global__ void __launch_bounds__(384, 1)
fused_kernel(const __grid_constant__ CUtensorMap mX, const __grid_constant__ CUtensorMap mB, const __grid_constant__ CUtensorMap mCre,
             const __grid_constant__ CUtensorMap mCim, const __grid_constant__ CUtensorMap mWg, const __grid_constant__ CUtensorMap mWu,
             const __grid_constant__ CUtensorMap mWd, const __grid_constant__ CUtensorMap mXr, const __grid_constant__ Params prm) {
    extern __shared__ __align__(1024) uint8_t smem[];
    uint32_t sb;
    asm volatile("mov.u32 %0, %1;" : "=r"(sb) : "r"(smem_u32(smem)));
    const int tid = threadIdx.x, warp = __shfl_sync(0xffffffffu, tid >> 5, 0), lane = tid & 31;
    const uint32_t cstart = clk32();
    uint32_t smid, nsmid;
    asm volatile("mov.u32 %0, %%smid;" : "=r"(smid));
    asm volatile("mov.u32 %0, %%nsmid;" : "=r"(nsmid));
    const uint32_t su = (smid - 64) >> 1, sq = (su * 37) >> 8;
    int cta = smid < 64 ? (smid & 14) * 8 + (smid >> 4) * 2 + (smid & 1) : smid < 120 ? (su - 7 * sq) * 16 + 24 + sq * 2 + (smid & 1) : smid < 124 ? smid + 8 : smid - 116;
    if (nsmid != NGRID) cta = blockIdx.x;
    if (cta >= NCTA) {
        if (tid == 0) wait_count_slow(&g_cnt[0], (atomicAdd(&g_cnt[0], 1u) / NGRID + 1) * NGRID);
        return;
    }
    const int chunk = (cta >> 5) * 4 + ((cta >> 2) & 3);
    const int dt = ((cta >> 4) & 1) * 4 + (cta & 3);
    const bool has_gu = cta >= 16;
    const uint32_t full = sb + OFF_FULL, empty = sb + OFF_EMPTY;
    const uint32_t bar_epoch = full + 8 * 72, bar_vec = full + 8 * 73, bar_xs = full + 8 * 74, bar_dn = full + 8 * 75, bar_free = full + 8 * 76;
    const uint32_t bar_order2 = empty + 8 * 72, bar_order3 = empty + 8 * 73, bar_fp = empty + 8 * 74, bar_hs = empty + 8 * 75,
        bar_accb = empty + 8 * 76, bar_st = empty + 8 * 80, bar_init2 = empty + 8 * 88, bar_order0 = empty + 8 * 89,
        bar_order1 = empty + 8 * 90, bar_rdone = empty + 8 * 91, bar_cand = empty + 8 * 92, bar_dummy = empty + 8 * 95;

    STAMPIF(tid == 0, 0);
    if (warp == 5) {
        if (elect_one()) {
#pragma unroll
            for (int i = 0; i < NST; i++) mbar_init(full + 8 * i, 1);
            asm volatile("fence.proxy.async.shared::cta;" ::: "memory");
        }
        __syncwarp();
        asm volatile("bar.arrive 0, 288;" ::: "memory");
        if (elect_one()) {
#pragma unroll
            for (int i = 0; i < NST; i++) {
                mbar_expect_tx(full + 8 * i, i >= RE0 ? SLOT + ABYTES : SLOT);
                tma5b(sb + i * SLOT, &mB, i * 64, dt * 4, full + 8 * i);
                tma4(sb + i * SLOT + 2 * ABYTES, &mX, i * 64, chunk * 64, full + 8 * i);
                STAMPIF(i == 0, 1);
            }
            STAMP(2);
        }
    } else if (warp == 4) {
        if (!(cta & 1) && lane < 8) asm volatile("st.relaxed.gpu.global.u32 [%0], %1;" ::"l"(&g_base[cta * 4 + lane]), "r"(cstart) : "memory");
        const int r = cta * 8 + ((lane & 15) >> 1);
        prefetch_l2((const char*)prm.x + (cta * 16 + (lane >> 1)) * 2048 + (lane & 1) * 128);
        prefetch_l2((const char*)((r & 512) ? prm.b_im : prm.b_re) + (r & 511) * 2048 + (lane & 1) * 128);
    } else if (warp < 4) {
        if (elect_one()) {
            const uint32_t base = warp == 0 ? empty : warp == 1 ? empty + 640 : warp == 2 ? full + 512 : full + 8 * NST;
            const uint32_t cnt = warp < 2 ? 4 : 1;
#pragma unroll
            for (int i = 0; i < 16; i++) mbar_init(base + 8 * i, cnt);
            *reinterpret_cast<uint32_t*>(smem + OFF_KEYS + 16) = 0;
            *reinterpret_cast<uint32_t*>(smem + OFF_EPOCH + 4) = cstart;
            *reinterpret_cast<uint32_t*>(smem + OFF_EPOCH + 8) = 0;
            if (sb & 1023) __trap();
            asm volatile("fence.proxy.async.shared::cta;" ::: "memory");
        }
    }
    __syncwarp();

    if (warp >= 8) {
        asm volatile("setmaxnreg.dec.sync.aligned.u32 72;");
        named_bar(0, 288);
        const uint32_t c0 = uni(lds32(sb + OFF_EPOCH + 4));
        if (warp == 8) {
            uint32_t dst = sb;
            const uint32_t wb = has_gu ? SLOT + WBYTES : SLOT;
            auto gemm1 = [&](int i, uint32_t tt) {
                if (lane == 0) mbar_expect_tx(full + 8 * i, i < RE0 + 4 ? SLOT + ABYTES : i >= GU0 ? wb : SLOT);
                mbar_wait(empty + 8 * (i - NST));
                LATE(i, tt);
                pace_until(tt);
                if (elect_one()) {
                    tma5b(dst, &mB, (i & 15) * 64, (i >> 4) * 64 + dt * 4, full + 8 * i);
                    tma4(dst + 2 * ABYTES, &mX, (i & 15) * 64, chunk * 64, full + 8 * i);
                }
                dst = dst == sb + (NST - 1) * SLOT ? sb : dst + SLOT;
            };
            for_entries<NST, 9>(c0, gemm1);
            mbar_wait(bar_init2);
            const uint32_t cb = uni(lds32(sb + OFF_EPOCH + 4));
            for_entries<9, 32>(cb, gemm1);
            STAMP(3);
            auto ctile = [&](int i, int kb, uint32_t bytes, uint32_t tt) {
                if (lane == 0) mbar_expect_tx(full + 8 * i, bytes);
                mbar_wait(empty + 8 * (i - NST));
                LATE(i, tt);
                pace_until(tt);
                if (elect_one()) tma5(dst + 2 * ABYTES, (kb & 4) ? &mCim : &mCre, ((kb & 3) + ((kb >> 1) & 12)) * 64, dt * 8, full + 8 * i);
                dst = dst == sb + (NST - 1) * SLOT ? sb : dst + SLOT;
            };
            for_entries<32, 52>(cb, [&](int i, uint32_t tt) { ctile(i, i, wb, tt); });
            for_entries<52, 64>(cb, [&](int i, uint32_t tt) { ctile(i, i, (0x924u >> (i - 52)) & 1 ? SLOT : SMALL, tt); });
            for_entries<64, NENT>(cb, [&](int i, uint32_t tt) { ctile(i, i + (i >> 1) - 76, SMALL, tt); });
            STAMP(4);
        } else if (warp == 9) {
#pragma unroll
            for (int u = 0; u < 8; u++) {
                const int row = (u >> 2) * 4 + (lane >> 3);
                asm volatile("cp.async.cg.shared.global [%0], [%1], 16;" ::"r"(sb + OFF_XS + (u & 3) * 1024 + row * 128 + (((lane & 7) ^ row) << 4)),
                             "l"((const char*)(u < 4 ? prm.w_r : prm.gate_w) + (u & 3) * 512 + lane * 16) : "memory");
            }
            if (elect_one()) {
                *reinterpret_cast<volatile uint32_t*>(smem + OFF_EPOCH) = atomicAdd(&g_cnt[0], 1u) / NGRID;
                mbar_arrive(bar_epoch);
            }
            __syncwarp();
            asm volatile("cp.async.wait_all;" ::: "memory");
            asm volatile("fence.proxy.async.shared::cta;" ::: "memory");
            __syncwarp();
            if (lane == 0) mbar_arrive(bar_vec);
#pragma unroll 1
            for (int it = 0; it < 3; it++) {
                uint32_t b0, b1;
                asm volatile("ld.relaxed.gpu.global.u32 %0, [%1];" : "=r"(b0) : "l"(&g_base[(cta & ~15) * 4]) : "memory");
                asm volatile("ld.relaxed.gpu.global.u32 %0, [%1];" : "=r"(b1) : "l"(&g_base[(cta & ~1) * 4]) : "memory");
                const bool ok0 = b0 - c0 + 400u < 800u, ok1 = b1 - c0 + 400u < 800u;
                if (ok0 || ok1) *reinterpret_cast<volatile uint32_t*>(smem + OFF_EPOCH + 4) = ok0 ? b0 : b1;
                if (__all_sync(0xffffffffu, ok0)) break;
            }
            STAMP(5);
            mbar_wait(bar_cand);
            {
                const uint32_t* list = reinterpret_cast<const uint32_t*>(smem + OFF_LIST);
                const int n = (int)lds32(sb + OFF_KEYS + 16);
#pragma unroll 1
                for (int i0 = 0; i0 < n; i0 += 32) {
                    const uint32_t k = list[i0 + lane];
                    int rank = 0;
#pragma unroll 2
                    for (int o = 0; o < n; o += 4) {
                        const uint4 l4 = *reinterpret_cast<const uint4*>(list + o);
                        rank += (l4.x > k) + (l4.y > k) + (l4.z > k) + (l4.w > k);
                    }
                    if (rank < 8) reinterpret_cast<uint32_t*>(smem + OFF_SEL)[rank] = k;
                }
                __syncwarp();
                STAMP(6);
                const uint32_t key = lds32(sb + OFF_SEL + 4 * (lane & 7)), tok = ~key & 2047u, tag = lds32(sb + OFF_EPOCH) + 1;
#pragma unroll 1
                for (int s = 0; s < 8; s++) {
                    const uint32_t t = __shfl_sync(0xffffffffu, tok, s);
                    const uint32_t d = sb + OFF_XS + (lane >> 3) * 1024 + s * 128 + (((lane & 7) ^ s) << 4);
                    const char* src = (const char*)prm.x + t * 2048 + lane * 16;
#pragma unroll
                    for (int u = 0; u < 4; u++) asm volatile("cp.async.cg.shared.global [%0], [%1], 16;" ::"r"(d + u * 4096), "l"(src + u * 512) : "memory");
                    if ((t >> 7) == (uint32_t)chunk) *reinterpret_cast<float4*>(prm.out + t * D_ + dt * 128 + lane * 4) = make_float4(0.f, 0.f, 0.f, 0.f);
                }
                uint32_t it = 0;
                unsigned long long u;
                do {
                    u = ld_relaxed1(&g_gpack[tok >> 1]);
                    if (++it > SPIN_LIMIT) __trap();
                } while (!__all_sync(0xffffffffu, (uint32_t)(u >> 32) == tag));
                const uint32_t kb = key >> 16;
                const float r = bf_lo((kb & 0x8000u) ? (kb & 0x7FFFu) : (~kb & 0xFFFFu)), gv = (tok & 1) ? bf_hi((uint32_t)u) : bf_lo((uint32_t)u);
                reinterpret_cast<float*>(smem + OFF_FAC)[lane & 7] = rbf(1.0f - gv) * rbf(sigmoidf_(r));
                asm volatile("cp.async.wait_all;" ::: "memory");
                asm volatile("fence.proxy.async.shared::cta;" ::: "memory");
                __syncwarp();
                if (lane == 0) mbar_arrive(bar_xs);
                STAMP(7);
            }
            if (elect_one()) {
                char* hd = reinterpret_cast<char*>(g_h) + (size_t)chunk * 524288 + dt * 4096;
#pragma unroll 1
                for (int u = 0; u < 4; u++) {
                    uint32_t tt = 0;
#pragma unroll
                    for (int q = 0; q < 4; q++) {
                        if (!(q & 1)) mbar_wait(bar_st + 16 * u + 4 * q);
                        if ((u & 1) && q) sleep_until(tt);
                        bulk_store(hd + q * 131072, sb + OFF_STG + q * 4096, 4096);
                        tt = clk32() + ST_PACE;
                    }
                    asm volatile("cp.async.bulk.commit_group;" ::: "memory");
                    asm volatile("cp.async.bulk.wait_group 0;" ::: "memory");
                    mbar_arrive(bar_free + 8 * u);
                    STAMP(8 + u);
                    red_release(&g_cnt[(16 + chunk * 4 + u) * 32]);
                    STAMP(12 + u);
                    hd += 32768;
                }
            }
        } else if (warp == 10) {
            const char* pb = (const char*)((cta & 64) ? prm.b_im : prm.b_re) + ((cta & 63) * 8 + ((lane & 15) >> 1)) * 2048 + (lane & 1) * 128;
            const uint32_t crow = (cta * 8 + ((lane & 15) >> 1)) * 2048 + (lane & 1) * 128;
#pragma unroll 1
            for (int k = 1; k < 16; k++) {
                sleep_until(c0 + (k < 6 ? PF0 + k * PF2_PACE : TT0 - 5500 + k * 1050));
                prefetch_l2(pb + (k >> 3) * 1048576 + (k & 7) * 256);
            }
            asm volatile("prefetch.tensormap [%0];" ::"l"(&mCre));
            asm volatile("prefetch.tensormap [%0];" ::"l"(&mCim));
#pragma unroll 1
            for (int k = 0; k < 4; k++) {
                sleep_until(c0 + Sched<22>::t + k * 1000);
                prefetch_l2((const char*)(k & 2 ? prm.c_im : prm.c_re) + crow + (k & 1) * 256);
            }
            mbar_wait(bar_epoch);
            mbar_wait(bar_init2);
            uint32_t dst = sb + (32 % NST) * SLOT;
            const uint32_t target = (lds32(sb + OFF_EPOCH) + 1) * 8, cb = uni(lds32(sb + OFF_EPOCH + 4)) + H_SHIFT;
            const char* hsrc = reinterpret_cast<const char*>(g_h) + (size_t)chunk * 524288;
            const unsigned int* cnt = &g_cnt[(16 + chunk * 4) * 32];
            uint32_t early = target - 1;
            auto next_quarter = [&]() {
                uint32_t it = 0;
                while (!__all_sync(0xffffffffu, (int)(early - target) >= 0)) {
                    asm volatile("ld.relaxed.gpu.global.u32 %0, [%1];" : "=r"(early) : "l"(cnt) : "memory");
                    if (++it > SPIN_LIMIT) __trap();
                }
                asm volatile("fence.acquire.gpu;" ::: "memory");
                asm volatile("fence.proxy.async.global;" ::: "memory");
                cnt += 32;
            };
            const char *pcr = (const char*)prm.c_re + crow + 512, *pci = (const char*)prm.c_im + crow + 512;
            auto htile = [&](int i, int kb, bool lo, bool hi, uint32_t tt) {
                const char* src = hsrc + (kb & 4) * 32768 + ((kb & 3) + ((kb >> 1) & 12)) * 8192;
                mbar_wait(empty + 8 * (i - NST));
                pace_until(tt);
                if (elect_one()) {
                    if (lo) bulk_load(dst, src, ABYTES, full + 8 * i);
                    if (hi) bulk_load(dst + ABYTES, src + 262144, ABYTES, full + 8 * i);
                }
                dst = dst == sb + (NST - 1) * SLOT ? sb : dst + SLOT;
            };
            auto hfirst = [&](int i, uint32_t tt) {
                if ((i & 7) == 6) asm volatile("ld.relaxed.gpu.global.u32 %0, [%1];" : "=r"(early) : "l"(cnt) : "memory");
                htile(i, i, true, (0x924FFFFFu >> (i - 32)) & 1, tt);
                if (!(i & 1)) prefetch_l2(((i & 4) ? pci : pcr) + (i & 2) * 128 + (i & 24) * 64);
            };
            mbar_wait(bar_free);
            next_quarter();
            STAMP(16);
            for_entries<32, 40>(cb, hfirst);
            next_quarter();
            STAMP(17);
            for_entries<40, 48>(cb, hfirst);
            next_quarter();
            STAMP(18);
            for_entries<48, 56>(cb, hfirst);
            next_quarter();
            STAMP(19);
            for_entries<56, 64>(cb, [&](int i, uint32_t tt) { htile(i, i, true, (0x92u >> (i - 56)) & 1, tt); });
            for_entries<64, NENT>(cb, [&](int i, uint32_t tt) { htile(i, i + (i >> 1) - 76, false, true, tt); });
        } else {
            const CUtensorMap* mw = (cta & 1) ? &mWu : &mWg;
            asm volatile("prefetch.tensormap [%0];" ::"l"(&mXr));
            const char* pp = (const char*)prm.x + (cta * 16 + (lane >> 1)) * 2048 + (lane & 1) * 128;
#pragma unroll 1
            for (int k = 1; k < 8; k++) {
                sleep_until(c0 + PF0 + k * PF_PACE);
                prefetch_l2(pp + k * 256);
            }
#pragma unroll 1
            for (int u = 0; u < 4; u++) {
                sleep_until(c0 + R0 + u * R_PACE);
                if (elect_one()) tma3(sb + OFF_W + u * ABYTES, &mXr, u * 256, cta * 16, full + 8 * (RE0 + u));
            }
            asm volatile("prefetch.tensormap [%0];" ::"l"(mw));
            mbar_wait(bar_init2);
            mbar_wait(empty + 8 * 10);
            const uint32_t cb = uni(lds32(sb + OFF_EPOCH + 4)) + W_SHIFT;
            auto gutile = [&](int i, uint32_t tt) {
                const int n = i + 3 - GU0;
                mbar_wait(empty + 8 * (i - NST));
                pace_until(tt);
                if (has_gu && elect_one()) tma2(sb + OFF_W + (n & 7) * WBYTES, mw, (cta >> 1) * 64 - 512, n * 32, full + 8 * (i + 3));
            };
            for_entries<GU0 - 3, GU0 + 13>(cb, gutile);
            for_entries<GU0 + 13, GU0 + 29>(cb, gutile);
            asm volatile("prefetch.tensormap [%0];" ::"l"(&mWd));
            if (lane == 0) mbar_expect_tx(bar_dn, 7 * ABYTES);
            mbar_wait(empty + 8 * (GU0 + 31));
            mbar_wait(bar_free + 24);
            uint32_t tt = clk32();
#pragma unroll 1
            for (int u = 0; u < 7; u++) {
                sleep_until(tt);
                if (elect_one()) tma2(sb + OFF_DN + u * ABYTES, &mWd, (cta & 15) * 64, (cta >> 4) * 448 + u * 64, bar_dn);
                tt += DN_PACE;
            }
            STAMP(20);
        }
    } else {
        asm volatile("setmaxnreg.inc.sync.aligned.u32 216;");
        const int wg = warp >> 2, w = warp & 3, g = lane >> 2, c = lane & 3, at = tid & 127;
        float facc[4];
        float2 a[2], m0[2], a32[2], a128[2];
        auto load_const = [&]() {
            const float2* cp = reinterpret_cast<const float2*>(smem + OFF_CONST) + wg * 64 + w * 8 + g;
#pragma unroll
            for (int h = 0; h < 2; h++) { a[h] = cp[32 * h]; m0[h] = cp[128 + 32 * h]; a32[h] = cp[256 + 32 * h]; a128[h] = cp[384 + 32 * h]; }
        };
        if (wg == 0) {
            named_bar(0, 288);
            asm volatile("bar.arrive 1, 192;" ::: "memory");
            STAMPIF(tid == 0, 21);
        } else {
            const int pc = (at >> 5) * 256 + dt * 32 + (at & 31);
            const float lr = __bfloat162float(prm.lam_re[pc]), li = __bfloat162float(prm.lam_im[pc]), ld = __bfloat162float(prm.log_dt[pc]);
            const uint32_t dk = __ldg(reinterpret_cast<const uint32_t*>(prm.dskip + dt * 128) + (at & 63));
            if (w >= 2) {
                if (elect_one()) {
#pragma unroll 1
                    for (int r = 0; r < 4; r++) {
                        const uint32_t base = w == 2 ? empty + 8 * (16 + 16 * r) : full + 8 * min(NST + 16 + 16 * r, 48), cnt = w == 2 ? 4 : 1;
#pragma unroll
                        for (int i = 0; i < 16; i++) mbar_init(base + 8 * i, cnt);
                    }
                }
                asm volatile("fence.proxy.async.shared::cta;" ::: "memory");
                named_bar(1, 192);
                if (lane < 2) mbar_arrive(bar_init2);
            }
#pragma unroll
            for (int i = 0; i < 4; i++) sts128(sb + OFF_LIST + i * 2048 + at * 16, 0u, 0u, 0u, 0u);
            STAMPIF(at == 0, 22);
            {
                reinterpret_cast<uint32_t*>(smem + OFF_DK)[at & 63] = dk;
                const float dtv = rbf(expf(ld));
                const float er = expf(dtv * lr);
                float sn, cs;
                sincosf(dtv * li, &sn, &cs);
                const float ar = er * cs, ai = er * sn;
                const float nr = ar - 1.0f, ni = ai;
                const bool big = fabsf(lr) >= fabsf(li);
                const float t = (big ? li : lr) / (big ? lr : li), dn = big ? lr + li * t : lr * t + li;
                const float cr = (big ? nr + ni * t : nr * t + ni) / dn, ci = (big ? ni - nr * t : ni * t - nr) / dn;
                float2* cp = reinterpret_cast<float2*>(smem + OFF_CONST) + at;
                float2 pw = make_float2(ar, -ai);
                cp[0] = pw;
                cp[128] = prm.swapped ? make_float2(-2.f * ci, 2.f * cr) : make_float2(2.f * cr, -2.f * ci);
#pragma unroll
                for (int i = 1; i <= 7; i++) {
                    pw = cmul(pw, pw);
                    if (i == 5) cp[256] = pw;
                    if (i == 7) cp[384] = pw;
                }
                __syncwarp();
            }
            named_bar(2, 128);
            load_const();
            mbar_wait(bar_epoch);
            const uint32_t tag = *reinterpret_cast<volatile uint32_t*>(smem + OFF_EPOCH) + 1;
            mbar_wait(bar_rdone);
            STAMPIF(at == 0, 23);
            const uint32_t tpub = clk32();
            if (w < 2) {
                const float2* red = reinterpret_cast<const float2*>(smem + OFF_RED) + w * 8 + (lane & 7);
                const float2 r0 = red[0], r1 = red[16], r2 = red[32], r3 = red[48];
                const float v0 = (r0.x + r1.x) + (r2.x + r3.x), v1 = (r0.y + r1.y) + (r2.y + r3.y);
                uint32_t pk2;
                if (w == 0) {
                    pk2 = pack_bf(v0, v1);
                    pk2 ^= (((pk2 >> 15) & 0x00010001u) * 0x7FFFu) ^ 0x80008000u;
                } else pk2 = pack_bf(sigmoidf_(rbf(v0)), sigmoidf_(rbf(v1)));
                if (lane < 8) asm volatile("st.relaxed.gpu.global.b64 [%0], %1;" ::"l"((w ? g_gpack : g_rpack) + cta * 8 + lane), "l"(((unsigned long long)tag << 32) | pk2) : "memory");
                __syncwarp();
            }
            STAMPIF(at == 0, 24);
            uint32_t it = 0, pr[8], g1;
            sleep_until(tpub + G0);
            while (true) {
                bool ok = true;
#pragma unroll
                for (int k = 0; k < 4; k++) {
                    const ulonglong2 u = ld_relaxed2(&g_rpack[k * 256 + 2 * at]);
                    ok = ok && (uint32_t)(u.x >> 32) == tag && (uint32_t)(u.y >> 32) == tag;
                    pr[2 * k] = (uint32_t)u.x; pr[2 * k + 1] = (uint32_t)u.y;
                }
                const unsigned long long u1 = ld_relaxed1(&g_gpack[chunk * 64 + (at & 63)]);
                ok = ok && (uint32_t)(u1 >> 32) == tag;
                g1 = (uint32_t)u1;
                if (__all_sync(0xffffffffu, ok)) break;
                if (++it > SPIN_LIMIT) __trap();
            }
            STAMPIF(at == 0, 25);
            uint32_t m = __vmaxu2(__vimax3_u16x2(__vimax3_u16x2(pr[0], pr[1], pr[2]), pr[3], pr[4]), __vimax3_u16x2(pr[5], pr[6], pr[7]));
            m = (max(m, m << 16) & 0xFFFF0000u) | (uint32_t)lane;
            const uint32_t m1 = __reduce_max_sync(0xffffffffu, m), m2 = __reduce_max_sync(0xffffffffu, m == m1 ? 0u : m);
            uint32_t* keys = reinterpret_cast<uint32_t*>(smem + OFF_KEYS);
            if (lane == 0) keys[w] = m2;
            sts128(sb + OFF_XS + 4096 + at * 16, pr[0], pr[1], pr[2], pr[3]);
            sts128(sb + OFF_XS + 6144 + at * 16, pr[4], pr[5], pr[6], pr[7]);
            *reinterpret_cast<uint32_t*>(smem + OFF_G + 4 * (at & 63) + (at & 48)) = g1;
            named_bar(2, 128);
            const uint4 th4 = *reinterpret_cast<const uint4*>(keys);
            const uint32_t th = (max(min(min(th4.x, th4.y), min(th4.z, th4.w)) >> 16, 1u) - 1u) * 0x00010001u;
            uint32_t mask = 0;
#pragma unroll
            for (int k = 7; k >= 0; k--) mask = mask * 2 + __vminu2(__vmaxu2(pr[k], th) ^ th, 0x00010001u);
            uint32_t pos = 0;
            asm volatile("{ .reg .pred p; setp.ne.u32 p, %2, 0; @p atom.shared.add.u32 %0, [%1], %2; }" : "+r"(pos) : "r"(sb + OFF_KEYS + 16), "r"(__popc(mask)) : "memory");
            while (mask) {
                const int bit = __ffs(mask) - 1, k = bit & 7, hi = bit >> 4;
                mask &= mask - 1;
                const uint32_t sc = *reinterpret_cast<const uint16_t*>(smem + OFF_XS + 4096 + (k >> 2) * 2048 + at * 16 + (k & 3) * 4 + hi * 2);
                *reinterpret_cast<uint32_t*>(smem + OFF_LIST + 4 * pos++) = (sc << 16) | (0x8000u + 2047u - (uint32_t)((k >> 1) * 512 + 4 * at + 2 * (k & 1) + hi));
            }
            __syncwarp();
            if (lane == 0) mbar_arrive(bar_cand);
            STAMPIF(at == 0, 26);
            mbar_wait(bar_order0);
        }

        float accA[64], accB[64];
        Ring ring = {sb, bar_dummy, wg};
        {
            static_assert(GU0 - 16 == RE0, "segments");
            run_entries<0, 0>(ring, wg * 16, wg * 16 + RE0, accA, accB, facc, true);
            if (wg == 0) {
                float racc[4];
                mbar_wait(bar_vec);
                run_entries<0, 1>(ring, RE0, RE0 + 4, accA, accB, racc, false, true);
                const uint32_t red = sb + OFF_RED + 4 * (w * 32 + (c >> 1) * 16 + g);
                run_entries<0, 0>(ring, RE0 + 4, RE0 + 5, accA, accB, facc, false, false, [&]() {
                    pin4(racc);
                    asm volatile("{ .reg .pred p; setp.ne.u32 p, %3, 0; @p st.shared.f32 [%0], %1; @p st.shared.f32 [%0 + 32], %2; }" ::"r"(red),
                                 "f"((w & 1) ? racc[1] : racc[0]), "f"((w & 1) ? racc[3] : racc[2]), "r"((uint32_t)((c & 1) == (w >> 1))) : "memory");
                    __syncwarp();
                    if (lane == 0) mbar_arrive(bar_rdone);
                });
                run_entries<0, 0>(ring, RE0 + 5, 16, accA, accB, facc);
                if (lane == 0) mbar_arrive(bar_order0);
                mbar_wait(bar_epoch);
                mbar_wait(bar_cand);
                load_const();
                named_bar(3, 128);
            } else {
                mbar_wait(bar_xs);
                run_entries<0, 2>(ring, GU0, 32, accA, accB, facc, false, true);
                if (lane == 0) mbar_arrive(bar_order1);
            }
        }
        const uint32_t tag = *reinterpret_cast<volatile uint32_t*>(smem + OFF_EPOCH) + 1;
        const float sgn = prm.swapped ? -1.f : 1.f;
        float2 m1[2], a64[2];
#pragma unroll
        for (int h = 0; h < 2; h++) {
            m1[h] = make_float2(sgn * m0[h].y, -sgn * m0[h].x);
            a64[h] = cmul(a32[h], a32[h]);
        }
        const uint32_t tstart = clk32();
        wgmma_wait<0>();
        pin64(accA); pin64(accB); pin4(facc);
        if (lane == 0) mbar_arrive(ring.prev);
        STAMPIF(at == 0, 28 + wg);

        {
            const uint32_t t2 = tag & 3u;
            float2* cslot = &g_carry[wg * 512 + dt * 32 + w * 8 + g];
            float2 w0[2];
#pragma unroll
            for (int h = 0; h < 2; h++) {
                float (&acc)[64] = h ? accB : accA;
                const float2 a1 = make_float2(a[h].x, -sgn * a[h].y);
                float2 e = make_float2(acc[0], acc[2]);
#pragma unroll
                for (int s = 1; s < 32; s++) {
                    const int i0 = 4 * (s >> 1) + (s & 1);
                    e = cfma(a1, e, make_float2(acc[i0], acc[i0 + 2]));
                }
                e = make_float2(m0[h].x * e.x + m0[h].y * e.y, m1[h].x * e.x + m1[h].y * e.y);
                float2 y = make_float2(__shfl_up_sync(0xffffffffu, e.x, 1, 4), __shfl_up_sync(0xffffffffu, e.y, 1, 4));
                if (c >= 1) e = cfma(a32[h], y, e);
                y = make_float2(__shfl_up_sync(0xffffffffu, e.x, 2, 4), __shfl_up_sync(0xffffffffu, e.y, 2, 4));
                if (c >= 2) e = cfma(a64[h], y, e);
                if (c == 3 && chunk < 15)
                    asm volatile("st.relaxed.gpu.global.v2.b32 [%0], {%1, %2};" ::"l"(cslot + chunk * 1024 + 256 * h), "r"((__float_as_uint(e.x) & ~3u) | t2),
                                 "r"((__float_as_uint(e.y) & ~3u) | t2) : "memory");
                w0[h] = make_float2(__shfl_up_sync(0xffffffffu, e.x, 1, 4), __shfl_up_sync(0xffffffffu, e.y, 1, 4));
                if (c == 0) w0[h] = make_float2(0.f, 0.f);
                pace_until(tstart);
                STAMPIF(at == 0, 30 + 2 * wg + h);
            }
            const int j1 = chunk - 1 - c;
            uint2 v[4];
            auto poll = [&](int h) {
#pragma unroll
                for (int m = 0; m < 4; m++)
                    asm volatile("ld.relaxed.gpu.global.v2.b32 {%0, %1}, [%2];" : "=r"(v[m].x), "=r"(v[m].y) : "l"(cslot + max(j1 - 4 * m, 0) * 1024 + 256 * h) : "memory");
            };
            const uint32_t zmask = lds32(sb + OFF_EPOCH + 8);
            const uint4* gs = reinterpret_cast<const uint4*>(smem + OFF_G) + c * 5;
            const uint32_t stg = sb + OFF_STG + w * 1024 + g * 128;
#pragma unroll
            for (int h = 0; h < 2; h++) {
                float (&acc)[64] = h ? accB : accA;
                poll(h);
                const float2 one = make_float2(1.f, 0.f), a256 = cmul(a128[h], a128[h]), a512 = cmul(a256, a256);
                const float2 pw128 = cmul((c & 1) ? a128[h] : one, (c & 2) ? a256 : one), pw32 = cmul((c & 1) ? a32[h] : one, (c & 2) ? a64[h] : one);
                float z = 0.f;
#pragma unroll
                for (int s = 0; s < 32; s++) {
                    const int i0 = 4 * (s >> 1) + (s & 1);
                    const float f = acc[i0], k = acc[i0 + 2];
                    acc[i0] = fmaf(m0[h].x, f, fmaf(m0[h].y, k, z)); acc[i0 + 2] = fmaf(m1[h].x, f, fmaf(m1[h].y, k, z));
                    z = __uint_as_float(__float_as_uint(acc[i0]) & zmask);
                }
                pace_until(tstart);
                STAMPIF(at == 0, 34 + 2 * wg + h);
                if (chunk > 0) {
                    uint32_t it = 0;
                    while (true) {
                        uint32_t bad = 0;
#pragma unroll
                        for (int m = 0; m < 4; m++) bad |= (v[m].x ^ t2) | (v[m].y ^ t2);
                        if (__all_sync(0xffffffffu, (bad & 3u) == 0)) break;
                        poll(h);
                        if (++it > SPIN_LIMIT) __trap();
                    }
                    float2 hin = make_float2(0.f, 0.f);
#pragma unroll
                    for (int m = 3; m >= 0; m--)
                        hin = cfma(a512, hin, j1 - 4 * m >= 0 ? make_float2(__uint_as_float(v[m].x), __uint_as_float(v[m].y)) : make_float2(0.f, 0.f));
                    hin = cmul(pw128, hin);
                    hin.x += __shfl_xor_sync(0xffffffffu, hin.x, 1); hin.y += __shfl_xor_sync(0xffffffffu, hin.y, 1);
                    hin.x += __shfl_xor_sync(0xffffffffu, hin.x, 2); hin.y += __shfl_xor_sync(0xffffffffu, hin.y, 2);
                    w0[h] = cfma(pw32, hin, w0[h]);
                }
                if (h || wg) mbar_wait(bar_free + 16 * wg + 8 * h - 8);
                STAMPIF(at == 0, 38 + 2 * wg + h);
#pragma unroll
                for (int j = 0; j < 4; j++) {
                    const uint4 g4 = gs[j];
                    const uint32_t gg[4] = {g4.x, g4.y, g4.z, g4.w};
                    uint32_t ra[4], ia[4];
#pragma unroll
                    for (int u = 0; u < 4; u++) {
                        const int i0 = 16 * j + 4 * u;
                        const float2 y = cfma(a[h], w0[h], make_float2(acc[i0], acc[i0 + 2]));
                        w0[h] = cfma(a[h], y, make_float2(acc[i0 + 1], acc[i0 + 3]));
                        ra[u] = mul_bf2(pack_bf(y.x, w0[h].x), gg[u]);
                        ia[u] = mul_bf2(pack_bf(y.y, w0[h].y), gg[u]);
                    }
                    const uint32_t hd = stg + (((2 * c + (j & 1)) ^ g) << 4) + (j >> 1) * 8192;
                    sts128(hd, ra[0], ra[1], ra[2], ra[3]);
                    sts128(hd + 4096, ia[0], ia[1], ia[2], ia[3]);
                    if (j & 1) {
                        asm volatile("fence.proxy.async.shared::cta;" ::: "memory");
                        __syncwarp();
                        if (lane == 0) mbar_arrive(bar_st + 32 * wg + 16 * h + 4 * (j & 2));
                    }
                }
                STAMPIF(at == 0, 42 + 2 * wg + h);
            }
        }

        const int tl = 32 * w + 16 * wg + g, t0 = chunk * 128 + tl;
        float* op = prm.out + (size_t)t0 * D_ + dt * 128 + 4 * c;
        uint2 xv[2][8];
        auto load_x = [&]() {
            const __nv_bfloat16* xp = prm.x + (size_t)t0 * D_ + dt * 128 + 4 * c;
#pragma unroll
            for (int j = 0; j < 8; j++) { xv[0][j] = ldg64(xp + 16 * j); xv[1][j] = ldg64(xp + 8 * D_ + 16 * j); }
        };
        float gv[2], om[2];
        uint32_t routed[2];
        auto row_setup = [&]() {
            const uint4 sa = *reinterpret_cast<const uint4*>(smem + OFF_SEL), sc = *reinterpret_cast<const uint4*>(smem + OFF_SEL + 16);
#pragma unroll
            for (int r = 0; r < 2; r++) {
                const uint32_t id = 0x8000u + 2047u - (uint32_t)(t0 + 8 * r);
                routed[r] = (uint16_t)sa.x == id || (uint16_t)sa.y == id || (uint16_t)sa.z == id || (uint16_t)sa.w == id ||
                            (uint16_t)sc.x == id || (uint16_t)sc.y == id || (uint16_t)sc.z == id || (uint16_t)sc.w == id;
                gv[r] = __bfloat162float(reinterpret_cast<const __nv_bfloat16*>(smem + OFF_G)[tl + 8 * w + 8 * r]);
                om[r] = rbf(1.0f - gv[r]);
            }
        };
        auto add_skip = [&](float (&acc)[64], int j, bool fresh) {
            const uint2 dk = lds64(sb + OFF_DK + 32 * j + 8 * c);
            const float d[4] = {bf_lo(dk.x), bf_hi(dk.x), bf_lo(dk.y), bf_hi(dk.y)};
#pragma unroll
            for (int r = 0; r < 2; r++) {
                const float xf[4] = {bf_lo(xv[r][j].x), bf_hi(xv[r][j].x), bf_lo(xv[r][j].y), bf_hi(xv[r][j].y)};
#pragma unroll
                for (int u = 0; u < 4; u++) {
                    const int o = 8 * j + 2 * r + (u & 1) + 4 * (u >> 1);
                    acc[o] = fmaf(xf[u], fmaf(gv[r], d[u], om[r]), fresh ? 0.f : acc[o]);
                }
            }
        };
        const uint32_t xbuf = sb + (67 % NST) * SLOT + at * 16;

        if (wg == 1) {
            float outB[64];
            load_x();
            row_setup();
#pragma unroll
            for (int j = 0; j < 8; j++) { add_skip(outB, j, true); pace_until(tstart); }
            pin64(outB);
            STAMPIF(at == 0, 46);
            mbar_wait(bar_fp);
            {
                const float4 o4 = lds128f(sb + OFF_XS + at * 16);
                const float o[4] = {o4.x, o4.y, o4.z, o4.w};
                __nv_bfloat16* hp = g_hid + ((cta & 1) * 8 + 2 * c) * F_ + (cta >> 1) * 64 - 512 + w * 16 + g;
#pragma unroll
                for (int u = 0; u < 4; u++) {
                    const float v = rbf(facc[u] + o[u]);
                    if (has_gu) hp[(u & 1) * F_ + 8 * (u >> 1)] = __float2bfloat16_rn((cta & 1) ? v : __fdividef(v, 1.0f + __expf(-v)));
                }
            }
            named_bar(2, 128);
            STAMPIF(at == 0, 47);
            if (w == 0) {
                if (lane == 0) red_release(&g_cnt[1 * 32]);
                __syncwarp();
                STAMPIF(at == 0, 48);
                wait_count(&g_cnt[1 * 32], tag * NCTA);
            }
            named_bar(2, 128);
            {
                uint4 hv[4], hu[4];
#pragma unroll
                for (int i = 0; i < 4; i++) {
                    const __nv_bfloat16* hp = g_hid + (2 * i + (at >> 6)) * F_ + (cta >> 4) * 448 + min(at & 63, 55) * 8;
                    hv[i] = ldg_cg128(hp); hu[i] = ldg_cg128(hp + 8 * F_);
                }
#pragma unroll
                for (int i = 0; i < 4; i++) {
                    const int tk = 2 * i + (at >> 6), ck = at & 63;
                    sts128(sb + OFF_XS + (ck >> 3) * 1024 + tk * 128 + (((ck & 7) ^ tk) << 4), mul_bf2(hv[i].x, hu[i].x), mul_bf2(hv[i].y, hu[i].y),
                           mul_bf2(hv[i].z, hu[i].z), mul_bf2(hv[i].w, hu[i].w));
                }
                asm volatile("fence.proxy.async.shared::cta;" ::: "memory");
                __syncwarp();
                if (lane == 0) mbar_arrive(bar_hs);
                STAMPIF(at == 0, 49);
            }
            ring.slot = 64 % NST;
            ring.prev = bar_dummy;
            mbar_wait(bar_order2);
#pragma unroll 1
            for (int i = 64; i < NENT; i++) run_small<1>(ring, i, outB);
            if (lane == 0) mbar_arrive(bar_order3);
            mbar_wait(bar_accb);
            float4 pb[16];
#pragma unroll
            for (int u = 0; u < 16; u++) pb[u] = lds128f(xbuf + u * 2048);
            wgmma_wait<0>();
            pin64(outB);
            KSTAMP(NENT);
            STAMPIF(at == 0, 50);
#pragma unroll
            for (int u = 0; u < 16; u++) {
                const int o = 8 * (u >> 1) + 2 * (u & 1);
                put4(op + (u & 1) * 8 * D_ + 16 * (u >> 1), outB[o] + pb[u].x, outB[o + 1] + pb[u].y, outB[o + 4] + pb[u].z, outB[o + 5] + pb[u].w, routed[u & 1]);
            }
            STAMPIF(at == 0, 51);
        } else {
            float outA[64], outB[64], gacc[4];
            mbar_wait(bar_xs);
            row_setup();
            STAMPIF(at == 0, 52);
            ring.slot = 32 % NST;
            ring.prev = bar_dummy;
            mbar_wait(bar_order1);
            run_entries<1, 2>(ring, 32, GU0 + 32, outA, outB, gacc, true, true);
            run_small<0>(ring, 52, outA);
            pin4(gacc);
            sts128(sb + OFF_XS + at * 16, __float_as_uint(gacc[0]), __float_as_uint(gacc[1]), __float_as_uint(gacc[2]), __float_as_uint(gacc[3]));
            __syncwarp();
            if (lane == 0) mbar_arrive(bar_fp);
            run_small<0>(ring, 53, outA);
            run_entries<1, 0>(ring, 54, 55, outA, outB, gacc, false, false, load_x);
#pragma unroll 1
            for (int i = 55; i < 64; i += 3) {
                run_small<0>(ring, i, outA);
                run_small<0>(ring, i + 1, outA);
                run_entries<1, 0>(ring, i + 2, i + 3, outA, outB, gacc);
            }
            if (lane == 0) mbar_arrive(bar_order2);
            wgmma_wait<0>();
            pin64(outA); pin64(outB);
            if (lane == 0) mbar_arrive(ring.prev);
            STAMPIF(at == 0, 53);
#pragma unroll
            for (int j = 0; j < 8; j++) {
                add_skip(outA, j, false);
                put4(op + 16 * j, outA[8 * j], outA[8 * j + 1], outA[8 * j + 4], outA[8 * j + 5], routed[0]);
                put4(op + 8 * D_ + 16 * j, outA[8 * j + 2], outA[8 * j + 3], outA[8 * j + 6], outA[8 * j + 7], routed[1]);
                pace_until(tstart);
            }
            STAMPIF(at == 0, 54);
            mbar_wait(empty + 8 * 67);
#pragma unroll
            for (int u = 0; u < 16; u++) {
                const int o = 8 * (u >> 1) + 2 * (u & 1);
                sts128(xbuf + u * 2048, __float_as_uint(outB[o]), __float_as_uint(outB[o + 1]), __float_as_uint(outB[o + 4]), __float_as_uint(outB[o + 5]));
            }
            __syncwarp();
            if (lane == 0) mbar_arrive(bar_accb);
            STAMPIF(at == 0, 55);
            const uint2 sk = lds64(sb + OFF_SEL + 8 * c), fk = lds64(sb + OFF_FAC + 8 * c);
            float* y0 = prm.out + (~sk.x & 2047u) * D_ + (cta & 15) * 64 + w * 16 + g;
            float* y1 = prm.out + (~sk.y & 2047u) * D_ + (cta & 15) * 64 + w * 16 + g;
            float yacc[4];
            const uint64_t dw = make_desc(sb + OFF_DN), dh = make_desc(sb + OFF_XS);
            mbar_wait(bar_hs);
            mbar_wait(bar_dn);
            mbar_wait(bar_order3);
            STAMPIF(at == 0, 56);
            wgmma_fence();
#pragma unroll
            for (int n = 0; n < 28; n++) wgmma_n8<1>(yacc, dw + n * 128, dh + (n >> 2) * 64 + (n & 3) * 2, n > 0);
            wgmma_commit();
            wgmma_wait<0>();
            pin4(yacc);
            atomicAdd(y0, yacc[0] * __uint_as_float(fk.x)); atomicAdd(y1, yacc[1] * __uint_as_float(fk.y));
            atomicAdd(y0 + 8, yacc[2] * __uint_as_float(fk.x)); atomicAdd(y1 + 8, yacc[3] * __uint_as_float(fk.y));
            STAMPIF(at == 0, 57);
        }
    }
}

typedef CUresult (*EncodeFn)(CUtensorMap*, CUtensorMapDataType, cuuint32_t, void*, const cuuint64_t*, const cuuint64_t*, const cuuint32_t*,
                             const cuuint32_t*, CUtensorMapInterleave, CUtensorMapSwizzle, CUtensorMapL2promotion, CUtensorMapFloatOOBfill);

bool encode(EncodeFn fn, CUtensorMap* m, const void* ptr, int rank, const cuuint64_t* dims, const cuuint64_t* strides, const cuuint32_t* box,
            CUtensorMapSwizzle sw = CU_TENSOR_MAP_SWIZZLE_128B, CUtensorMapL2promotion promo = CU_TENSOR_MAP_L2_PROMOTION_NONE) {
    const cuuint32_t es[5] = {1, 1, 1, 1, 1};
    return fn(m, CU_TENSOR_MAP_DATA_TYPE_BFLOAT16, rank, const_cast<void*>(ptr), dims, strides, box, es, CU_TENSOR_MAP_INTERLEAVE_NONE,
              sw, promo, CU_TENSOR_MAP_FLOAT_OOB_FILL_NONE) == CUDA_SUCCESS;
}

}

extern "C" void kernel_launch(void* const* d_in, const int* in_sizes, int n_in, void* d_out, int out_size) {
    (void)in_sizes; (void)n_in; (void)out_size;
    Params prm;
    prm.x = (const __nv_bfloat16*)d_in[0];
    prm.lam_re = (const __nv_bfloat16*)d_in[1];
    prm.lam_im = (const __nv_bfloat16*)d_in[2];
    prm.b_re = (const __nv_bfloat16*)d_in[3];
    prm.b_im = (const __nv_bfloat16*)d_in[4];
    prm.c_re = (const __nv_bfloat16*)d_in[5];
    prm.c_im = (const __nv_bfloat16*)d_in[6];
    prm.log_dt = (const __nv_bfloat16*)d_in[7];
    prm.dskip = (const __nv_bfloat16*)d_in[8];
    prm.w_r = (const __nv_bfloat16*)d_in[10];
    prm.gate_w = (const __nv_bfloat16*)d_in[14];
    prm.out = (float*)d_out;
    prm.swapped = prm.b_im < prm.b_re;

    void* fnp = nullptr;
    cudaDriverEntryPointQueryResult qr;
    cudaGetDriverEntryPoint("cuTensorMapEncodeTiled", &fnp, cudaEnableDefault, &qr);
    EncodeFn fn = (EncodeFn)fnp;
    cudaFuncSetAttribute(fused_kernel, cudaFuncAttributeMaxDynamicSharedMemorySize, SMEM_BYTES);

    CUtensorMap mX, mB, mCre, mCim, mWg, mWu, mWd, mXr;
    const cuuint64_t row = 2048;
    {
        const cuuint64_t dims[4] = {1024, 2, 4, 976}, st[3] = {row, 32 * row, 2 * row};
        const cuuint32_t box[4] = {64, 2, 4, 16};
        encode(fn, &mX, prm.x, 4, dims, st, box, CU_TENSOR_MAP_SWIZZLE_128B, PROMO);
    }
    {
        const char *lo = (const char*)(prm.swapped ? prm.b_im : prm.b_re), *hi = (const char*)(prm.swapped ? prm.b_re : prm.b_im);
        const cuuint64_t dims[5] = {1024, 8, 2, 96, 2}, st[4] = {row, (cuuint64_t)(hi - lo), 8 * row, 256 * row};
        const cuuint32_t box[5] = {64, 8, 2, 4, 2};
        encode(fn, &mB, lo, 5, dims, st, box, CU_TENSOR_MAP_SWIZZLE_128B, PROMO);
    }
    {
        const cuuint64_t dims[5] = {1024, 2, 4, 2, 64}, st[4] = {row, 4 * row, 2 * row, 16 * row};
        const cuuint32_t box[5] = {64, 2, 4, 2, 8};
        encode(fn, &mCre, prm.c_re, 5, dims, st, box);
        encode(fn, &mCim, prm.c_im, 5, dims, st, box);
    }
    {
        const cuuint64_t dims[2] = {F_, D_}, st[1] = {F_ * 2}, dimsd[2] = {D_, F_}, std_[1] = {row};
        const cuuint32_t box[2] = {64, 32}, boxd[2] = {64, 64};
        encode(fn, &mWg, d_in[11], 2, dims, st, box, CU_TENSOR_MAP_SWIZZLE_128B, CU_TENSOR_MAP_L2_PROMOTION_NONE);
        encode(fn, &mWu, d_in[12], 2, dims, st, box, CU_TENSOR_MAP_SWIZZLE_128B, CU_TENSOR_MAP_L2_PROMOTION_NONE);
        encode(fn, &mWd, d_in[13], 2, dimsd, std_, boxd, CU_TENSOR_MAP_SWIZZLE_128B, CU_TENSOR_MAP_L2_PROMOTION_NONE);
    }
    {
        const cuuint64_t dims[3] = {D_ - 192, S_, 4}, st[2] = {row, 128};
        const cuuint32_t box[3] = {64, 16, 4};
        encode(fn, &mXr, prm.x, 3, dims, st, box, CU_TENSOR_MAP_SWIZZLE_128B, CU_TENSOR_MAP_L2_PROMOTION_NONE);
    }
    fused_kernel<<<NGRID, 384, SMEM_BYTES, cudaStreamPerThread>>>(mX, mB, mCre, mCim, mWg, mWu, mWd, mXr, prm);
}
```

```cpp
#include <cuda_runtime.h>
#include <cuda_bf16.h>
#include <cuda.h>
#include <stdint.h>

namespace {

constexpr int S_ = 2048, D_ = 1024, F_ = 3584;
constexpr int NCTA = 128, NGRID = 132;
constexpr uint32_t JOINT = 0x0AAFFFFFu;
constexpr int NENT = 72;
constexpr int NST = 5;
constexpr int RE0 = 4;
constexpr int GU0 = 20;
constexpr uint32_t SLOT = 32768, SMALL = 24576, ABYTES = 8192, WBYTES = 4096;
constexpr uint32_t OFF_XS = NST * SLOT;
constexpr uint32_t OFF_LIST = OFF_XS + 8192;
constexpr uint32_t OFF_W = OFF_XS + 16384;
constexpr uint32_t OFF_STG = OFF_W + 32768;
constexpr uint32_t OFF_DN = OFF_XS + 8192;
constexpr uint32_t OFF_DN5 = (63 % NST) * SLOT, OFF_DN6 = (67 % NST) * SLOT + ABYTES;
constexpr uint32_t OFF_CONST = OFF_STG;
constexpr uint32_t OFF_RED = OFF_STG + 4096;
constexpr uint32_t OFF_FULL = OFF_STG + 16384;
constexpr uint32_t OFF_EMPTY = OFF_FULL + 88 * 8;
constexpr uint32_t OFF_G = OFF_EMPTY + 96 * 8;
constexpr uint32_t OFF_DK = OFF_G + 256;
constexpr uint32_t OFF_KEYS = OFF_DK + 256;
constexpr uint32_t OFF_SEL = OFF_KEYS + 32;
constexpr uint32_t OFF_FAC = OFF_SEL + 32;
constexpr uint32_t OFF_EPOCH = OFF_FAC + 32;
constexpr uint32_t OFF_PROF = OFF_EPOCH + 16;
constexpr uint32_t SMEM_BYTES = OFF_PROF + 896;
static_assert(SMEM_BYTES <= 232448, "smem");

constexpr uint32_t SPIN_LIMIT = 1u << 18;

__device__ uint4 g_h[8 * 4 * 256 * 64];
__device__ unsigned long long g_rpack[S_ / 2];
__device__ unsigned long long g_gpack[S_ / 2];
__device__ float2 g_carry[16 * 1024];
__device__ unsigned int g_cnt[2 * 32];
__device__ unsigned int g_base[64 * 8];
__device__ uint4 g_hid[2 * F_];
#define STAMPW(cond, w) do {} while (0)
#define LATE(i, tt) do {} while (0)
#define STAMPIF(cond, i) STAMPW(cond, 80 + (i))
#define STAMP(i) STAMPW(1, 80 + (i))
#define KSTAMP(i) STAMPW((threadIdx.x & 127) == 0, i)

struct Params {
    const __nv_bfloat16 *x, *lam_re, *lam_im, *b_re, *b_im, *c_re, *c_im, *log_dt, *dskip, *w_r, *gate_w;
    float* out;
    int swapped;
};

__device__ __forceinline__ uint32_t smem_u32(const void* p) { return (uint32_t)__cvta_generic_to_shared(p); }
__device__ __forceinline__ void mbar_init(uint32_t bar, uint32_t cnt) { asm volatile("mbarrier.init.shared::cta.b64 [%0], %1;" ::"r"(bar), "r"(cnt) : "memory"); }
__device__ __forceinline__ void mbar_expect_tx(uint32_t bar, uint32_t bytes) { asm volatile("mbarrier.arrive.expect_tx.shared::cta.b64 _, [%0], %1;" ::"r"(bar), "r"(bytes) : "memory"); }
__device__ __forceinline__ void mbar_arrive(uint32_t bar) { asm volatile("mbarrier.arrive.shared::cta.b64 _, [%0];" ::"r"(bar) : "memory"); }
__device__ __forceinline__ bool mbar_try(uint32_t bar, uint32_t parity = 0) {
    uint32_t ok;
    asm volatile("{ .reg .pred p; mbarrier.try_wait.parity.shared::cta.b64 p, [%1], %2; selp.u32 %0, 1, 0, p; }" : "=r"(ok) : "r"(bar), "r"(parity) : "memory");
    return ok;
}
__device__ __forceinline__ bool mbar_test(uint32_t bar) {
    uint32_t ok;
    asm volatile("{ .reg .pred p; mbarrier.test_wait.parity.shared::cta.b64 p, [%1], 0; selp.u32 %0, 1, 0, p; }" : "=r"(ok) : "r"(bar) : "memory");
    return ok;
}
__device__ __forceinline__ void mbar_wait(uint32_t bar, uint32_t parity = 0) {
    if (mbar_try(bar, parity)) return;
#pragma unroll 1
    for (uint32_t it = 0; it < SPIN_LIMIT; ++it)
        if (mbar_try(bar, parity)) return;
    __trap();
}
__device__ __forceinline__ bool elect_one() {
    uint32_t pred;
    asm volatile("{ .reg .pred P; elect.sync _|P, 0xffffffff; selp.b32 %0, 1, 0, P; }" : "=r"(pred));
    return pred;
}
__device__ __forceinline__ void named_bar(int id, int n) { asm volatile("bar.sync %0, %1;" ::"r"(id), "r"(n) : "memory"); }

__device__ __forceinline__ void bulk_load(uint32_t dst, const void* src, uint32_t bytes, uint32_t bar) {
    asm volatile("cp.async.bulk.shared::cluster.global.mbarrier::complete_tx::bytes [%0], [%1], %2, [%3];" ::"r"(dst), "l"(src), "r"(bytes), "r"(bar) : "memory");
}
__device__ __forceinline__ void sts128(uint32_t a, uint32_t x, uint32_t y, uint32_t z, uint32_t w) {
    asm volatile("st.shared.v4.u32 [%0], {%1,%2,%3,%4};" ::"r"(a), "r"(x), "r"(y), "r"(z), "r"(w) : "memory");
}
__device__ __forceinline__ uint2 lds64(uint32_t a) {
    uint2 v;
    asm volatile("ld.shared.v2.u32 {%0,%1}, [%2];" : "=r"(v.x), "=r"(v.y) : "r"(a) : "memory");
    return v;
}
__device__ __forceinline__ uint32_t clk32() { uint32_t c; asm volatile("mov.u32 %0, %%clock;" : "=r"(c)); return c; }
__device__ __forceinline__ void pace_until(uint32_t t) { while ((int)(clk32() - t) < 0) {} }
#define SLEEP_MARGIN 200
__device__ __forceinline__ void sleep_until(uint32_t t) {
    while ((int)(clk32() + SLEEP_MARGIN - t) < 0) __nanosleep(40);
    pace_until(t);
}
__device__ __forceinline__ void tma2(uint32_t dst, const CUtensorMap* m, int c0, int c1, uint32_t bar) {
    asm volatile("cp.async.bulk.tensor.2d.shared::cluster.global.mbarrier::complete_tx::bytes [%0], [%1, {%3, %4}], [%2];"
                 ::"r"(dst), "l"(m), "r"(bar), "r"(c0), "r"(c1) : "memory");
}
__device__ __forceinline__ void tma3(uint32_t dst, const CUtensorMap* m, int c0, int c1, uint32_t bar) {
    asm volatile("cp.async.bulk.tensor.3d.shared::cluster.global.mbarrier::complete_tx::bytes [%0], [%1, {%3, %4, %5}], [%2];"
                 ::"r"(dst), "l"(m), "r"(bar), "r"(c0), "r"(c1), "r"(0) : "memory");
}
__device__ __forceinline__ void tma4(uint32_t dst, const CUtensorMap* m, int c0, int c3, uint32_t bar) {
    asm volatile("cp.async.bulk.tensor.4d.shared::cluster.global.mbarrier::complete_tx::bytes [%0], [%1, {%3, %5, %5, %4}], [%2];"
                 ::"r"(dst), "l"(m), "r"(bar), "r"(c0), "r"(c3), "r"(0) : "memory");
}
__device__ __forceinline__ void tma5(uint32_t dst, const CUtensorMap* m, int c0, int c4, uint32_t bar) {
    asm volatile("cp.async.bulk.tensor.5d.shared::cluster.global.mbarrier::complete_tx::bytes [%0], [%1, {%3, %5, %5, %5, %4}], [%2];"
                 ::"r"(dst), "l"(m), "r"(bar), "r"(c0), "r"(c4), "r"(0) : "memory");
}
__device__ __forceinline__ void tma5b(uint32_t dst, const CUtensorMap* m, int c0, int c3, uint32_t bar) {
    asm volatile("cp.async.bulk.tensor.5d.shared::cluster.global.mbarrier::complete_tx::bytes [%0], [%1, {%3, %5, %5, %4, %5}], [%2];"
                 ::"r"(dst), "l"(m), "r"(bar), "r"(c0), "r"(c3), "r"(0) : "memory");
}
__device__ __forceinline__ void prefetch_l2(const void* p) {
    asm volatile("prefetch.global.L2 [%0];" ::"l"(p));
}

__device__ __forceinline__ uint32_t lds32(uint32_t a) {
    uint32_t v;
    asm volatile("ld.volatile.shared.u32 %0, [%1];" : "=r"(v) : "r"(a) : "memory");
    return v;
}
__device__ __forceinline__ uint32_t uni(uint32_t v) { return __shfl_sync(0xffffffffu, v, 0); }   __device__ __forceinline__ uint32_t ld_acquire(const unsigned int* p) {
    uint32_t v;
    asm volatile("ld.acquire.gpu.global.u32 %0, [%1];" : "=r"(v) : "l"(p) : "memory");
    return v;
}
__device__ __forceinline__ void red_release(unsigned int* p) { asm volatile("red.release.gpu.global.add.u32 [%0], 1;" ::"l"(p) : "memory"); }
__device__ __forceinline__ void wait_count(const unsigned int* p, uint32_t target) {
#pragma unroll 1
    for (uint32_t it = 0; it < SPIN_LIMIT; ++it)
        if ((int)(ld_acquire(p) - target) >= 0) return;
    __trap();
}
__device__ __forceinline__ void wait_count_slow(const unsigned int* p, uint32_t target) {
#pragma unroll 1
    for (uint32_t it = 0; it < SPIN_LIMIT; ++it) {
        if ((int)(ld_acquire(p) - target) >= 0) return;
        __nanosleep(200);
    }
    __trap();
}
__device__ __forceinline__ unsigned long long ld_relaxed1(const void* p) {
    unsigned long long v;
    asm volatile("ld.relaxed.gpu.global.b64 %0, [%1];" : "=l"(v) : "l"(p) : "memory");
    return v;
}
__device__ __forceinline__ ulonglong2 ld_relaxed2(const void* p) {
    ulonglong2 v;
    asm volatile("ld.relaxed.gpu.global.v2.b64 {%0, %1}, [%2];" : "=l"(v.x), "=l"(v.y) : "l"(p) : "memory");
    return v;
}
__device__ __forceinline__ void ld_cell(uint32_t (&v)[4], const void* p) {
    asm volatile("{ .reg .b64 l, h; .reg .b128 t; ld.relaxed.gpu.global.b128 t, [%4]; mov.b128 {l, h}, t; mov.b64 {%0, %1}, l; mov.b64 {%2, %3}, h; }"
                 : "=r"(v[0]), "=r"(v[1]), "=r"(v[2]), "=r"(v[3]) : "l"(p) : "memory");
}

__device__ __forceinline__ uint64_t make_desc(uint32_t addr, uint32_t sbo = 1024) {
    return (uint64_t)((addr & 0x3FFFF) >> 4) | ((uint64_t)1 << 16) | ((uint64_t)(sbo >> 4) << 32) | ((uint64_t)1 << 62);
}
__device__ __forceinline__ void wgmma_fence() { asm volatile("wgmma.fence.sync.aligned;" ::: "memory"); }
__device__ __forceinline__ void wgmma_commit() { asm volatile("wgmma.commit_group.sync.aligned;" ::: "memory"); }
template <int N> __device__ __forceinline__ void wgmma_wait() { asm volatile("wgmma.wait_group.sync.aligned %0;" ::"n"(N) : "memory"); }

#define R8(d, i) "+f"(d[i]), "+f"(d[i + 1]), "+f"(d[i + 2]), "+f"(d[i + 3]), "+f"(d[i + 4]), "+f"(d[i + 5]), "+f"(d[i + 6]), "+f"(d[i + 7])
#define R64(d) R8(d, 0), R8(d, 8), R8(d, 16), R8(d, 24), R8(d, 32), R8(d, 40), R8(d, 48), R8(d, 56)
template <int TA>
__device__ __forceinline__ void wgmma_n128(float (&d)[64], uint64_t da, uint64_t db, int scale_d = 1) {
    asm volatile("{ .reg .pred p; setp.ne.b32 p, %66, 0;\n"
                 "wgmma.mma_async.sync.aligned.m64n128k16.f32.bf16.bf16 "
                 "{%0,%1,%2,%3,%4,%5,%6,%7,%8,%9,%10,%11,%12,%13,%14,%15,%16,%17,%18,%19,%20,%21,%22,%23,%24,%25,%26,%27,%28,%29,%30,%31,"
                 "%32,%33,%34,%35,%36,%37,%38,%39,%40,%41,%42,%43,%44,%45,%46,%47,%48,%49,%50,%51,%52,%53,%54,%55,%56,%57,%58,%59,%60,%61,%62,%63}, "
                 "%64, %65, p, 1, 1, %67, 0; }"
                 : R64(d)
                 : "l"(da), "l"(db), "r"(scale_d), "n"(TA));
}
__device__ __forceinline__ void pin4(float (&d)[4]) { asm volatile("" : "+f"(d[0]), "+f"(d[1]), "+f"(d[2]), "+f"(d[3])::"memory"); }
__device__ __forceinline__ void pin64(float (&d)[64]) { asm volatile("" : R64(d)::"memory"); }

template <int TA, int TB = 0>
__device__ __forceinline__ void wgmma_n8(float (&d)[4], uint64_t da, uint64_t db, int scale_d = 1) {
    asm volatile("{ .reg .pred p; setp.ne.b32 p, %7, 0;\n"
                 "wgmma.mma_async.sync.aligned.m64n8k16.f32.bf16.bf16 {%0,%1,%2,%3}, %4, %5, p, 1, 1, %6, %8; }"
                 : "+f"(d[0]), "+f"(d[1]), "+f"(d[2]), "+f"(d[3])
                 : "l"(da), "l"(db), "n"(TA), "r"(scale_d), "n"(TB));
}

__device__ __forceinline__ float bf_lo(uint32_t u) { return __uint_as_float(u << 16); }
__device__ __forceinline__ float bf_hi(uint32_t u) { return __uint_as_float(u & 0xFFFF0000u); }
__device__ __forceinline__ float rbf(float v) { return __bfloat162float(__float2bfloat16_rn(v)); }
__device__ __forceinline__ uint32_t pack_bf(float lo, float hi) {
    uint32_t r;
    asm("cvt.rn.bf16x2.f32 %0, %1, %2;" : "=r"(r) : "f"(hi), "f"(lo));
    return r;
}
__device__ __forceinline__ uint32_t mul_bf2(uint32_t a, uint32_t b) {
    __nv_bfloat162 r = __hmul2(*reinterpret_cast<__nv_bfloat162*>(&a), *reinterpret_cast<__nv_bfloat162*>(&b));
    return *reinterpret_cast<uint32_t*>(&r);
}
__device__ __forceinline__ float2 cmul(float2 a, float2 b) { return make_float2(a.x * b.x - a.y * b.y, a.x * b.y + a.y * b.x); }
__device__ __forceinline__ float2 cfma(float2 a, float2 b, float2 c) {
    return make_float2(fmaf(a.x, b.x, fmaf(-a.y, b.y, c.x)), fmaf(a.x, b.y, fmaf(a.y, b.x, c.y)));
}
__device__ __forceinline__ float sigmoidf_(float v) { return __fdividef(1.0f, 1.0f + expf(-v)); }

__device__ __forceinline__ void bulk_store(void* dst, uint32_t src, uint32_t bytes) {
    asm volatile("cp.async.bulk.global.shared::cta.bulk_group [%0], [%1], %2;" ::"l"(dst), "r"(src), "r"(bytes) : "memory");
}
__device__ __forceinline__ float4 lds128f(uint32_t a) {
    float4 v;
    asm volatile("ld.shared.v4.f32 {%0,%1,%2,%3}, [%4];" : "=f"(v.x), "=f"(v.y), "=f"(v.z), "=f"(v.w) : "r"(a) : "memory");
    return v;
}
__device__ __forceinline__ void stsm4(uint32_t a, uint32_t x, uint32_t y, uint32_t z, uint32_t w) {
    asm volatile("stmatrix.sync.aligned.m8n8.x4.shared.b16 [%0], {%1,%2,%3,%4};" ::"r"(a), "r"(x), "r"(y), "r"(z), "r"(w) : "memory");
}
__device__ __forceinline__ uint4 ldsm4(uint32_t a) {
    uint4 v;
    asm volatile("ldmatrix.sync.aligned.m8n8.x4.shared.b16 {%0,%1,%2,%3}, [%4];" : "=r"(v.x), "=r"(v.y), "=r"(v.z), "=r"(v.w) : "r"(a) : "memory");
    return v;
}
__device__ __forceinline__ void put4(float* p, float a, float b, float c, float d, uint32_t routed) {
    asm volatile("{ .reg .pred p; setp.ne.u32 p, %5, 0;\n"
                 "@p red.global.add.v4.f32 [%0], {%1,%2,%3,%4};\n"
                 "@!p st.global.v4.f32 [%0], {%1,%2,%3,%4}; }" ::"l"(p), "f"(a), "f"(b), "f"(c), "f"(d), "r"(routed) : "memory");
}

#define TT0 3652
#define P1 516
#define P2 520
#define P3 520
#define P4 260
#define PF0 500
#define PF_PACE 350
#define PF2_PACE 450
#define G0 900
#define R0 3000
#define R_PACE 400
#define W_SHIFT 250
#define PROMO CU_TENSOR_MAP_L2_PROMOTION_L2_256B
#define PSCAN 100
#define POLL_S 24
#define ST_SHIFT 300
#define HG0 900
constexpr bool is_small(int i) { return i >= 64 || (i >= 32 && !((JOINT >> (i - 32)) & 1)); }
constexpr uint32_t duration(int i) {
    return (is_small(i) ? P4 : i < 16 ? P1 : i < 32 ? P2 : P3) + (i >= RE0 && i < RE0 + 4 ? 72 : 0) + (i >= GU0 && i < GU0 + 32 ? 36 : 0) +
           (i == 16 || i == 32 ? PSCAN : 0);
}
constexpr uint32_t issue_time(int i) { return i <= NST ? TT0 : issue_time(i - 1) + duration(i - NST); }
constexpr uint32_t PMIN = 240;
constexpr uint64_t pack_periods(int i0) {
    uint64_t r = 0;
    for (int k = 0; k < 8; k++) r |= (uint64_t)((issue_time(i0 + k + 1) / 4 - issue_time(i0 + k) / 4 - PMIN / 4) & 255) << (8 * k);
    return r;
}
template <int I> struct Sched { static constexpr uint32_t t = issue_time(I) / 4 * 4; static constexpr uint64_t p = pack_periods(I); };
template <int LO, int HI, class F>
__device__ __forceinline__ void for_entries(uint32_t base, F body) {
    uint32_t tt = base + Sched<LO>::t;
    uint64_t pk = Sched<LO>::p;
#pragma unroll 1
    for (int i = LO; i < HI; i++) {
        body(i, tt);
        tt += PMIN + 4 * ((uint32_t)pk & 255u);
        pk >>= 8;
        if (LO + 8 < HI && i == LO + 7) pk = Sched<LO + 8>::p;
        if (LO + 16 < HI && i == LO + 15) pk = Sched<LO + 16>::p;
        static_assert(HI - LO <= 24, "segment too long");
    }
}

struct Ring { uint32_t sb, prev; int slot; };
struct NoHook { __device__ void operator()() const {} };
template <int TA, int SM, class H = NoHook>
__device__ __forceinline__ void run_entries(Ring& r, int lo, int hi, float (&accA)[64], float (&accB)[64], float (&small)[4],
                                            bool fresh = false, bool sfresh = false, H released = H()) {
    const uint32_t sb = r.sb;
    const uint64_t d0 = make_desc(sb);
    const bool leader = (threadIdx.x & 31) == 0;
#pragma unroll 1
    for (int i = lo; i < hi; i++) {
        const uint32_t bar = sb + OFF_FULL + 8 * i;
        const uint64_t da = d0 + (uint64_t)(r.slot * (SLOT >> 4));
        const int n = i - (SM == 1 ? RE0 : GU0);
        const uint64_t dw = d0 + (uint64_t)((OFF_W >> 4) + (SM == 1 ? n * 512 : (n & 7) * 256));
        const uint64_t dt8 = d0 + (uint64_t)((OFF_XS >> 4) + (SM == 1 ? n * 64 : (n >> 1) * 64 + (n & 1) * 4));
        r.slot = r.slot == NST - 1 ? 0 : r.slot + 1;
        mbar_wait(bar);
        KSTAMP(i);
        wgmma_fence();
#pragma unroll
        for (int kk = 0; kk < 4; kk++) {
            wgmma_n128<TA>(accA, da + kk * (TA ? 128 : 2), da + 1024 + kk * 2, kk > 0 || !fresh);
            if (SM == 1) wgmma_n8<0>(small, dw + kk * 2, dt8 + kk * 2, kk > 0 || !sfresh);
            if (SM == 2 && (kk & 1)) wgmma_n8<1>(small, dw + (kk >> 1) * 128, dt8 + (kk >> 1) * 2, kk > 1 || !sfresh);
            wgmma_n128<TA>(accB, da + 512 + kk * (TA ? 128 : 2), da + 1024 + kk * 2, kk > 0 || !fresh);
            if (kk == 1) {
                wgmma_commit();
                wgmma_wait<1>();
                if (leader) mbar_arrive(r.prev);
                released();
            }
        }
        wgmma_commit();
        r.prev = bar + (OFF_EMPTY - OFF_FULL);
        fresh = sfresh = false;
    }
}
template <int HALF>
__device__ __forceinline__ void run_small(Ring& r, int i, float (&acc)[64], bool fresh = false) {
    const uint32_t sb = r.sb, bar = sb + OFF_FULL + 8 * i;
    const uint64_t da = make_desc(sb) + (uint64_t)(r.slot * (SLOT >> 4));
    r.slot = r.slot == NST - 1 ? 0 : r.slot + 1;
    mbar_wait(bar);
    KSTAMP(i);
    wgmma_fence();
#pragma unroll
    for (int kk = 0; kk < 4; kk++) wgmma_n128<1>(acc, da + HALF * 512 + kk * 128, da + 1024 + kk * 2, kk > 0 || !fresh);
    wgmma_commit();
    wgmma_wait<1>();
    if ((threadIdx.x & 31) == 0) mbar_arrive(r.prev);
    r.prev = bar + (OFF_EMPTY - OFF_FULL);
}

__global__ void __launch_bounds__(384, 1)
fused_kernel(const __grid_constant__ CUtensorMap mX, const __grid_constant__ CUtensorMap mB, const __grid_constant__ CUtensorMap mCre,
             const __grid_constant__ CUtensorMap mCim, const __grid_constant__ CUtensorMap mWg, const __grid_constant__ CUtensorMap mWu,
             const __grid_constant__ CUtensorMap mWd, const __grid_constant__ CUtensorMap mXr, const __grid_constant__ CUtensorMap mXe,
             const __grid_constant__ Params prm) {
    extern __shared__ __align__(1024) uint8_t smem[];
    uint32_t sb;
    asm volatile("mov.u32 %0, %1;" : "=r"(sb) : "r"(smem_u32(smem)));
    const int tid = threadIdx.x, warp = __shfl_sync(0xffffffffu, tid >> 5, 0), lane = tid & 31;
    const uint32_t cstart = clk32();
    uint32_t smid, nsmid;
    asm volatile("mov.u32 %0, %%smid;" : "=r"(smid));
    asm volatile("mov.u32 %0, %%nsmid;" : "=r"(nsmid));
    const uint32_t su = (smid - 64) >> 1, sq = (su * 37) >> 8;
    int cta = smid < 64 ? (smid & 14) * 8 + (smid >> 4) * 2 + (smid & 1) : smid < 120 ? (su - 7 * sq) * 16 + 24 + sq * 2 + (smid & 1) : smid < 124 ? smid + 8 : smid - 116;
    if (nsmid != NGRID) cta = blockIdx.x;
    if (cta >= NCTA) {
        if (tid == 0) wait_count_slow(&g_cnt[0], (atomicAdd(&g_cnt[0], 1u) / NGRID + 1) * NGRID);
        return;
    }
    const int chunk = (cta >> 5) * 4 + ((cta >> 2) & 3);
    const int dt = ((cta >> 4) & 1) * 4 + (cta & 3);
    const bool has_gu = cta >= 16;
    const uint32_t full = sb + OFF_FULL, empty = sb + OFF_EMPTY;
    const uint32_t bar_epoch = full + 8 * 72, bar_vec = full + 8 * 73, bar_xs = full + 8 * 74, bar_dn = full + 8 * 75, bar_xb = full + 8 * 76, bar_xa = full + 8 * 77, bar_retry = full + 8 * 78, bar_zero = full + 8 * 79, bar_out = full + 8 * 80;
    const uint32_t bar_order2 = empty + 8 * 72, bar_order3 = empty + 8 * 73, bar_fp = empty + 8 * 74, bar_hs = empty + 8 * 75,
        bar_accb = empty + 8 * 76, bar_xbfree = empty + 8 * 78, bar_st = empty + 8 * 80, bar_init2 = empty + 8 * 88, bar_order0 = empty + 8 * 89,
        bar_order1 = empty + 8 * 90, bar_rdone = empty + 8 * 91, bar_cand = empty + 8 * 92, bar_dummy = empty + 8 * 95;

    STAMPIF(tid == 0, 0);
    if (warp == 5) {
        if (elect_one()) {
#pragma unroll
            for (int i = 0; i < NST; i++) mbar_init(full + 8 * i, 1);
            asm volatile("fence.proxy.async.shared::cta;" ::: "memory");
        }
        __syncwarp();
        asm volatile("bar.arrive 0, 288;" ::: "memory");
        if (elect_one()) {
#pragma unroll
            for (int i = 0; i < NST; i++) {
                mbar_expect_tx(full + 8 * i, i >= RE0 ? SLOT + ABYTES : SLOT);
                tma5b(sb + i * SLOT, &mB, i * 64, dt * 4, full + 8 * i);
                tma4(sb + i * SLOT + 2 * ABYTES, &mX, i * 64, chunk * 64, full + 8 * i);
                STAMPIF(i == 0, 1);
            }
        }
    } else if (warp == 4) {
        if (!(cta & 1) && lane < 8) asm volatile("st.relaxed.gpu.global.u32 [%0], %1;" ::"l"(&g_base[cta * 4 + lane]), "r"(cstart) : "memory");
        const int r = cta * 8 + ((lane & 15) >> 1);
        prefetch_l2((const char*)prm.x + (cta * 16 + (lane >> 1)) * 2048 + (lane & 1) * 128);
        prefetch_l2((const char*)((r & 512) ? prm.b_im : prm.b_re) + (r & 511) * 2048 + (lane & 1) * 128);
    } else if (warp < 4) {
        if (elect_one()) {
            const uint32_t base = warp == 0 ? empty : warp == 1 ? empty + 640 : warp == 2 ? full + 576 : full + 8 * NST;
            const uint32_t cnt = warp < 2 ? 4 : 1;
#pragma unroll
            for (int i = 0; i < 16; i++) mbar_init(base + 8 * i, cnt);
            *reinterpret_cast<uint32_t*>(smem + OFF_KEYS + 16) = 0;
            *reinterpret_cast<uint32_t*>(smem + OFF_EPOCH + 4) = cstart;
            *reinterpret_cast<uint32_t*>(smem + OFF_EPOCH + 8) = 0;
            if (sb & 1023) __trap();
            asm volatile("fence.proxy.async.shared::cta;" ::: "memory");
        }
    }
    __syncwarp();

    if (warp >= 8) {
        asm volatile("setmaxnreg.dec.sync.aligned.u32 72;");
        named_bar(0, 288);
        const uint32_t c0 = uni(lds32(sb + OFF_EPOCH + 4));
        if (warp == 8) {
            uint32_t dst = sb;
            const uint32_t wb = has_gu ? SLOT + WBYTES : SLOT;
            auto gemm1 = [&](int i, uint32_t tt) {
                if (lane == 0) mbar_expect_tx(full + 8 * i, i < RE0 + 4 ? SLOT + ABYTES : i >= GU0 ? wb : SLOT);
                mbar_wait(empty + 8 * (i - NST));
                LATE(i, tt);
                pace_until(tt);
                if (elect_one()) {
                    tma5b(dst, &mB, (i & 15) * 64, (i >> 4) * 64 + dt * 4, full + 8 * i);
                    tma4(dst + 2 * ABYTES, &mX, (i & 15) * 64, chunk * 64, full + 8 * i);
                }
                dst = dst == sb + (NST - 1) * SLOT ? sb : dst + SLOT;
            };
            for_entries<NST, 9>(c0, gemm1);
            mbar_wait(bar_init2);
            const uint32_t cb = uni(lds32(sb + OFF_EPOCH + 4));
            for_entries<9, 32>(cb, gemm1);
            const char* hsrc = reinterpret_cast<const char*>(g_h) + (size_t)chunk * 524288;
            auto gemm2 = [&](int i, int kb, uint32_t bytes, uint32_t hoff, uint32_t hbytes, bool first, uint32_t tt) {
                if (lane < 2) mbar_expect_tx(full + 8 * (lane ? i & 31 : i), lane ? hbytes : bytes);
                if (first && !(i & 3)) {
                    mbar_wait(bar_out + 2 * (i & 28));
                    STAMP(16 + ((i >> 2) & 7));
                }
                mbar_wait(empty + 8 * (i - NST));
                LATE(i, tt);
                pace_until(tt);
                if (elect_one()) {
                    bulk_load(dst + hoff, hsrc + (kb & 31) * 16384 + hoff, hbytes, full + 8 * (i & 31));
                    tma5(dst + 2 * ABYTES, (kb & 4) ? &mCim : &mCre, ((kb & 3) + ((kb >> 1) & 12)) * 64, dt * 8, full + 8 * i);
                }
                dst = dst == sb + (NST - 1) * SLOT ? sb : dst + SLOT;
            };
            for_entries<32, 52>(cb, [&](int i, uint32_t tt) { gemm2(i, i, wb - 2 * ABYTES, 0, 2 * ABYTES, true, tt); });
            for_entries<52, 64>(cb, [&](int i, uint32_t tt) {
                gemm2(i, i, 2 * ABYTES, 0, (JOINT >> (i - 32)) & 1 ? 2 * ABYTES : ABYTES, true, tt);
            });
            for_entries<64, NENT>(cb, [&](int i, uint32_t tt) { gemm2(i, min(2 * i - 108, i - 40), 2 * ABYTES, ABYTES, ABYTES, false, tt); });
            STAMP(4);
        } else if (warp == 9) {
#pragma unroll
            for (int u = 0; u < 8; u++) {
                const int row = (u >> 2) * 4 + (lane >> 3);
                asm volatile("cp.async.cg.shared.global [%0], [%1], 16;" ::"r"(sb + OFF_XS + (u & 3) * 1024 + row * 128 + (((lane & 7) ^ row) << 4)),
                             "l"((const char*)(u < 4 ? prm.w_r : prm.gate_w) + (u & 3) * 512 + lane * 16) : "memory");
            }
            if (elect_one()) {
                *reinterpret_cast<volatile uint32_t*>(smem + OFF_EPOCH) = atomicAdd(&g_cnt[0], 1u) / NGRID;
                mbar_arrive(bar_epoch);
            }
            __syncwarp();
            asm volatile("cp.async.wait_all;" ::: "memory");
            asm volatile("fence.proxy.async.shared::cta;" ::: "memory");
            __syncwarp();
            if (lane == 0) mbar_arrive(bar_vec);
#pragma unroll 1
            for (int it = 0; it < 3; it++) {
                uint32_t b0, b1;
                asm volatile("ld.relaxed.gpu.global.u32 %0, [%1];" : "=r"(b0) : "l"(&g_base[(cta & ~15) * 4]) : "memory");
                asm volatile("ld.relaxed.gpu.global.u32 %0, [%1];" : "=r"(b1) : "l"(&g_base[(cta & ~1) * 4]) : "memory");
                const bool ok0 = b0 - c0 + 400u < 800u, ok1 = b1 - c0 + 400u < 800u;
                if (ok0 || ok1) *reinterpret_cast<volatile uint32_t*>(smem + OFF_EPOCH + 4) = ok0 ? b0 : b1;
                if (__all_sync(0xffffffffu, ok0)) break;
            }
            STAMP(5);
            mbar_wait(bar_cand);
            {
                const uint32_t* list = reinterpret_cast<const uint32_t*>(smem + OFF_LIST);
                const int n = (int)lds32(sb + OFF_KEYS + 16);
#pragma unroll 1
                for (int i0 = 0; i0 < n; i0 += 32) {
                    const uint32_t k = list[i0 + lane];
                    int rank = 0;
#pragma unroll 2
                    for (int o = 0; o < n; o += 4) {
                        const uint4 l4 = *reinterpret_cast<const uint4*>(list + o);
                        rank += (l4.x > k) + (l4.y > k) + (l4.z > k) + (l4.w > k);
                    }
                    if (rank < 8) reinterpret_cast<uint32_t*>(smem + OFF_SEL)[rank] = k;
                }
                __syncwarp();
                STAMP(6);
                const uint32_t key = lds32(sb + OFF_SEL + 4 * (lane & 7)), tok = ~key & 2047u, tag = lds32(sb + OFF_EPOCH) + 1;
#pragma unroll
                for (int s0 = 0; s0 < 8; s0 += 4) {
                    const int s = s0 + (lane >> 3);
                    const uint32_t t = __shfl_sync(0xffffffffu, tok, s);
                    const uint32_t d = sb + OFF_XS + s * 128 + (((lane & 7) ^ s) << 4);
                    const char* src = (const char*)prm.x + t * 2048 + (lane & 7) * 16;
#pragma unroll
                    for (int u = 0; u < 16; u++) asm volatile("cp.async.cg.shared.global [%0], [%1], 16;" ::"r"(d + u * 1024), "l"(src + u * 128) : "memory");
                }
                if ((tok >> 7) == (uint32_t)chunk) {
                    float4* zp = reinterpret_cast<float4*>(prm.out + tok * D_ + dt * 128) + (lane >> 3) * 2;
#pragma unroll
                    for (int u = 0; u < 8; u++) zp[(u >> 1) * 8 + (u & 1)] = make_float4(0.f, 0.f, 0.f, 0.f);
                }
                uint32_t it = 0;
                unsigned long long u;
                do {
                    u = ld_relaxed1(&g_gpack[tok >> 1]);
                    if (++it > SPIN_LIMIT) __trap();
                } while (!__all_sync(0xffffffffu, (uint32_t)(u >> 32) == tag));
                const uint32_t kb = key >> 16;
                const float r = bf_lo((kb & 0x8000u) ? (kb & 0x7FFFu) : (~kb & 0xFFFFu)), gv = (tok & 1) ? bf_hi((uint32_t)u) : bf_lo((uint32_t)u);
                reinterpret_cast<float*>(smem + OFF_FAC)[lane & 7] = rbf(1.0f - gv) * rbf(sigmoidf_(r));
                asm volatile("cp.async.wait_all;" ::: "memory");
                asm volatile("fence.proxy.async.shared::cta;" ::: "memory");
                __syncwarp();
                if (lane == 0) mbar_arrive(bar_xs);
                STAMP(7);
            }
            char* hd = reinterpret_cast<char*>(g_h) + (size_t)chunk * 524288 + (dt >> 1) * 16384 + (dt & 1) * 4096;
            static_assert(P2 == P3, "constant period");
            uint32_t tt = uni(lds32(sb + OFF_EPOCH + 4)) + ST_SHIFT + Sched<GU0 + 4>::t;
#pragma unroll 1
            for (int np = 0; np < 16; np++) {
                if (!(np & 2)) {
                    mbar_wait(bar_st + 4 * (np & 12) + 8 * (np & 1));
                    asm volatile("fence.proxy.async.shared::cta;" ::: "memory");
                }
                if (np == 8) tt += PSCAN;
                const uint32_t now = clk32();
#pragma unroll 1
                while ((int)(tt - now) < 0) tt += P2 + 36;
                const uint32_t src = sb + OFF_STG + (np & 3) * 4096;
                pace_until(tt);
                if (elect_one()) {
                    bulk_store(hd, src, 4096);
                    if ((np & 3) == 3) {
                        asm volatile("cp.async.bulk.commit_group;" ::: "memory");
                        asm volatile("cp.async.bulk.wait_group.read 0;" ::: "memory");
                    }
                    if (np & 1) mbar_arrive(bar_out + 4 * (np - 1));
                }
                STAMPIF(np & 1, 8 + (np >> 1));
                hd += (np & 1) ? 65536 - 8192 : 8192;
            }
            wait_count(&g_cnt[32], (lds32(sb + OFF_EPOCH) + 1) * NCTA);
            if (lane == 0) mbar_arrive(bar_zero);
        } else if (warp == 10) {
            const char* pb = (const char*)((cta & 64) ? prm.b_im : prm.b_re) + ((cta & 63) * 8 + ((lane & 15) >> 1)) * 2048 + (lane & 1) * 128;
#pragma unroll 1
            for (int k = 1; k < 16; k++) {
                sleep_until(c0 + (k < 6 ? PF0 + k * PF2_PACE : TT0 - 5500 + k * 1050));
                prefetch_l2(pb + (k >> 3) * 1048576 + (k & 7) * 256);
            }
            asm volatile("prefetch.tensormap [%0];" ::"l"(&mCre));
            asm volatile("prefetch.tensormap [%0];" ::"l"(&mCim));
            mbar_wait(bar_init2);
            mbar_wait(bar_epoch);
            mbar_wait(full);
            mbar_wait(bar_xs);
            if (lane == 0) red_release(&g_cnt[32]);
            __syncwarp();
            const uint32_t t2 = lds32(sb + OFF_EPOCH) + 1, tagw = (t2 & 1) | ((t2 & 2) << 15);
            uint32_t src = sb + (32 % NST) * SLOT + lane * 32 + (lane & 4) * 4 + (lane >> 3) * 4, rpar = 0;
            auto check = [&](int i, int kb, uint32_t hoff, bool both) {
                mbar_wait(full + 8 * (i & 31), i < 64);
#pragma unroll 1
                for (uint32_t it = 0;; it++) {
                    uint32_t bad = 0;
#pragma unroll
                    for (int u = 0; u < 8; u++) bad |= lds32(src + hoff + u * 1024) ^ tagw;
                    if (both) {
#pragma unroll
                        for (int u = 8; u < 16; u++) bad |= lds32(src + u * 1024) ^ tagw;
                    }
                    if (__all_sync(0xffffffffu, (bad & 0x00010001u) == 0)) break;
                    if (it > SPIN_LIMIT) __trap();
                    STAMP(56);
                    if (elect_one()) {
                        mbar_expect_tx(bar_retry, both ? 2 * ABYTES : ABYTES);
                        bulk_load((src & ~1023u) + hoff, reinterpret_cast<const char*>(g_h) + (size_t)chunk * 524288 + (kb & 31) * 16384 + hoff,
                                  both ? 2 * ABYTES : ABYTES, bar_retry);
                    }
                    mbar_wait(bar_retry, rpar);
                    rpar ^= 1;
                }
                if (lane == 0) mbar_arrive(full + 8 * i);
                src = src >= sb + (NST - 1) * SLOT ? src - (NST - 1) * SLOT : src + SLOT;
            };
#pragma unroll 1
            for (int i = 32; i < 64; i++) check(i, i, 0, (JOINT >> (i - 32)) & 1);
#pragma unroll 1
            for (int i = 64; i < NENT; i++) check(i, min(2 * i - 108, i - 40), ABYTES, false);
        } else {
            const CUtensorMap* mw = (cta & 1) ? &mWu : &mWg;
            asm volatile("prefetch.tensormap [%0];" ::"l"(&mXr));
            const char* pp = (const char*)prm.x + (cta * 16 + (lane >> 1)) * 2048 + (lane & 1) * 128;
#pragma unroll 1
            for (int k = 1; k < 8; k++) {
                sleep_until(c0 + PF0 + k * PF_PACE);
                prefetch_l2(pp + k * 256);
            }
#pragma unroll 1
            for (int u = 0; u < 4; u++) {
                sleep_until(c0 + R0 + u * R_PACE);
                if (elect_one()) tma3(sb + OFF_W + u * ABYTES, &mXr, u * 256, cta * 16, full + 8 * (RE0 + u));
            }
            asm volatile("prefetch.tensormap [%0];" ::"l"(mw));
            mbar_wait(bar_init2);
            mbar_wait(empty + 8 * 10);
            const uint32_t cb = uni(lds32(sb + OFF_EPOCH + 4)) + W_SHIFT;
            const uint32_t crow = (cta * 8 + ((lane & 15) >> 1)) * 2048 + (lane & 1) * 128;
            const char *pcr = (const char*)prm.c_re + crow, *pci = (const char*)prm.c_im + crow;
            auto gutile = [&](int i, uint32_t tt) {
                const int n = i + 3 - GU0;
                mbar_wait(empty + 8 * (i - NST));
                pace_until(tt);
                if (has_gu && elect_one()) tma2(sb + OFF_W + (n & 7) * WBYTES, mw, (cta >> 1) * 64 - 512, n * 32, full + 8 * (i + 3));
                if (n & 1) prefetch_l2(((n & 4) ? pci : pcr) + (n & 2) * 128 + (n & 24) * 64);
            };
            for_entries<GU0 - 3, GU0 + 13>(cb, gutile);
            for_entries<GU0 + 13, GU0 + 29>(cb, gutile);
            asm volatile("prefetch.tensormap [%0];" ::"l"(&mWd));
            asm volatile("prefetch.tensormap [%0];" ::"l"(&mXe));
            if (lane < 3) mbar_expect_tx(bar_dn + 8 * lane, lane ? 2 * ABYTES : 7 * ABYTES);
            const int dc = (cta & 15) * 64, dr = (cta >> 4) * 448;
            for_entries<GU0 + 29, GU0 + 37>(cb, [&](int i, uint32_t tt) {
                const int n = i - GU0 - 29;
                if (n == 6) mbar_wait(bar_out + 56);
                mbar_wait(empty + 8 * (i - NST));
                pace_until(tt);
                if (elect_one()) {
                    tma2(sb + OFF_W + n * WBYTES, &mWd, dc, dr + 64 + n * 32, bar_dn);
                    if (n < 4) asm volatile("cp.async.bulk.prefetch.tensor.2d.L2.global [%0, {%1, %2}];" ::"l"(&mWd), "r"(dc), "r"(dr + 320 + n * 32) : "memory");
                    if (n >= 6) tma5(sb + OFF_STG + (n & 1) * ABYTES, &mXe, dt * 128 + (n & 1) * 64, chunk * 64 + 8, bar_xb);
                }
            });
            for_entries<57, 64>(cb, [&](int i, uint32_t tt) {
                if (i & 1) {
                    if (i == 61) mbar_wait(bar_xbfree);
                    mbar_wait(empty + 8 * (i - NST));
                    pace_until(tt);
                    if (elect_one()) {
                        if (i < 61) tma2(sb + OFF_DN + (i & 2) * (WBYTES / 2), &mWd, dc, dr + (i & 2) * 16, bar_dn);
                        else tma5(sb + OFF_STG + (i & 2) * (ABYTES / 2), &mXe, dt * 128 + (i & 2) * 32, chunk * 64, bar_xa);
                    }
                }
            });
            mbar_wait(empty + 8 * 63);
            mbar_wait(empty + 8 * 67);
            if (elect_one()) {
#pragma unroll
                for (int u = 0; u < 4; u++) tma2(sb + (u < 2 ? OFF_DN5 : OFF_DN6) + (u & 1) * WBYTES, &mWd, dc, dr + 320 + u * 32, bar_dn);
            }
            STAMP(27);
        }
    } else {
        asm volatile("setmaxnreg.inc.sync.aligned.u32 216;");
        const int wg = warp >> 2, w = warp & 3, g = lane >> 2, c = lane & 3, at = tid & 127;
        float facc[4];
        float2 a[2], m0[2], a32[2], a128[2];
        auto load_const = [&]() {
            const float2* cp = reinterpret_cast<const float2*>(smem + OFF_CONST) + wg * 64 + w * 8 + g;
#pragma unroll
            for (int h = 0; h < 2; h++) { a[h] = cp[32 * h]; m0[h] = cp[128 + 32 * h]; a32[h] = cp[256 + 32 * h]; a128[h] = cp[384 + 32 * h]; }
        };
        if (wg == 0) {
            named_bar(0, 288);
            asm volatile("bar.arrive 1, 192;" ::: "memory");

        } else {
            const int pc = (at >> 5) * 256 + dt * 32 + (at & 31);
            const float lr = __bfloat162float(prm.lam_re[pc]), li = __bfloat162float(prm.lam_im[pc]), ld = __bfloat162float(prm.log_dt[pc]);
            const uint32_t dk = __ldg(reinterpret_cast<const uint32_t*>(prm.dskip + dt * 128) + (at & 63));
            if (w >= 2) {
                if (elect_one()) {
#pragma unroll 1
                    for (int r = 0; r < 4; r++) {
                        const uint32_t base = w == 2 ? empty + 8 * (16 + 16 * r) : full + 8 * (r ? min(16 + 16 * r, 56) : NST + 16), cnt = w == 2 ? 4 : r ? 2 : 1;
#pragma unroll
                        for (int i = 0; i < 16; i++) mbar_init(base + 8 * i, cnt);
                    }
                }
                asm volatile("fence.proxy.async.shared::cta;" ::: "memory");
                named_bar(1, 192);
                if (lane < 2) mbar_arrive(bar_init2);
            }
#pragma unroll
            for (int i = 0; i < 4; i++) sts128(sb + OFF_LIST + i * 2048 + at * 16, 0u, 0u, 0u, 0u);

            {
                reinterpret_cast<uint32_t*>(smem + OFF_DK)[at & 63] = dk;
                const float dtv = rbf(expf(ld));
                const float er = expf(dtv * lr);
                float sn, cs;
                sincosf(dtv * li, &sn, &cs);
                const float ar = er * cs, ai = er * sn;
                const float nr = ar - 1.0f, ni = ai;
                const bool big = fabsf(lr) >= fabsf(li);
                const float t = (big ? li : lr) / (big ? lr : li), dn = big ? lr + li * t : lr * t + li;
                const float cr = (big ? nr + ni * t : nr * t + ni) / dn, ci = (big ? ni - nr * t : ni * t - nr) / dn;
                float2* cp = reinterpret_cast<float2*>(smem + OFF_CONST) + at;
                float2 pw = make_float2(ar, -ai);
                cp[0] = pw;
                cp[128] = prm.swapped ? make_float2(-2.f * ci, 2.f * cr) : make_float2(2.f * cr, -2.f * ci);
#pragma unroll
                for (int i = 1; i <= 7; i++) {
                    pw = cmul(pw, pw);
                    if (i == 5) cp[256] = pw;
                    if (i == 7) cp[384] = pw;
                }
                __syncwarp();
            }
            named_bar(2, 128);
            load_const();
            mbar_wait(bar_epoch);
            const uint32_t tag = *reinterpret_cast<volatile uint32_t*>(smem + OFF_EPOCH) + 1;
            mbar_wait(bar_rdone);

            const uint32_t tpub = clk32();
            if (w < 2) {
                const float2* red = reinterpret_cast<const float2*>(smem + OFF_RED) + w * 8 + (lane & 7);
                const float2 r0 = red[0], r1 = red[16], r2 = red[32], r3 = red[48];
                const float v0 = (r0.x + r1.x) + (r2.x + r3.x), v1 = (r0.y + r1.y) + (r2.y + r3.y);
                uint32_t pk2;
                if (w == 0) {
                    pk2 = pack_bf(v0, v1);
                    pk2 ^= (((pk2 >> 15) & 0x00010001u) * 0x7FFFu) ^ 0x80008000u;
                } else pk2 = pack_bf(sigmoidf_(rbf(v0)), sigmoidf_(rbf(v1)));
                if (lane < 8) asm volatile("st.relaxed.gpu.global.b64 [%0], %1;" ::"l"((w ? g_gpack : g_rpack) + cta * 8 + lane), "l"(((unsigned long long)tag << 32) | pk2) : "memory");
                __syncwarp();
            }
            STAMPIF(at == 0, 24);
            uint32_t it = 0, pr[8], g1;
            sleep_until(tpub + G0);
            while (true) {
                bool ok = true;
#pragma unroll
                for (int k = 0; k < 4; k++) {
                    const ulonglong2 u = ld_relaxed2(&g_rpack[k * 256 + 2 * at]);
                    ok = ok && (uint32_t)(u.x >> 32) == tag && (uint32_t)(u.y >> 32) == tag;
                    pr[2 * k] = (uint32_t)u.x; pr[2 * k + 1] = (uint32_t)u.y;
                }
                const unsigned long long u1 = ld_relaxed1(&g_gpack[chunk * 64 + (at & 63)]);
                ok = ok && (uint32_t)(u1 >> 32) == tag;
                g1 = (uint32_t)u1;
                if (__all_sync(0xffffffffu, ok)) break;
                if (++it > SPIN_LIMIT) __trap();
            }
            STAMPIF(at == 0, 25);
            uint32_t m = __vmaxu2(__vimax3_u16x2(__vimax3_u16x2(pr[0], pr[1], pr[2]), pr[3], pr[4]), __vimax3_u16x2(pr[5], pr[6], pr[7]));
            m = (max(m, m << 16) & 0xFFFF0000u) | (uint32_t)lane;
            const uint32_t m1 = __reduce_max_sync(0xffffffffu, m), m2 = __reduce_max_sync(0xffffffffu, m == m1 ? 0u : m);
            uint32_t* keys = reinterpret_cast<uint32_t*>(smem + OFF_KEYS);
            if (lane == 0) keys[w] = m2;
            sts128(sb + OFF_XS + 4096 + at * 16, pr[0], pr[1], pr[2], pr[3]);
            sts128(sb + OFF_XS + 6144 + at * 16, pr[4], pr[5], pr[6], pr[7]);
            *reinterpret_cast<uint32_t*>(smem + OFF_G + 4 * (at & 63)) = g1;
            named_bar(2, 128);
            const uint4 th4 = *reinterpret_cast<const uint4*>(keys);
            const uint32_t th = (max(min(min(th4.x, th4.y), min(th4.z, th4.w)) >> 16, 1u) - 1u) * 0x00010001u;
            uint32_t mask = 0;
#pragma unroll
            for (int k = 7; k >= 0; k--) mask = mask * 2 + __vminu2(__vmaxu2(pr[k], th) ^ th, 0x00010001u);
            uint32_t pos = 0;
            asm volatile("{ .reg .pred p; setp.ne.u32 p, %2, 0; @p atom.shared.add.u32 %0, [%1], %2; }" : "+r"(pos) : "r"(sb + OFF_KEYS + 16), "r"(__popc(mask)) : "memory");
            while (mask) {
                const int bit = __ffs(mask) - 1, k = bit & 7, hi = bit >> 4;
                mask &= mask - 1;
                const uint32_t sc = *reinterpret_cast<const uint16_t*>(smem + OFF_XS + 4096 + (k >> 2) * 2048 + at * 16 + (k & 3) * 4 + hi * 2);
                *reinterpret_cast<uint32_t*>(smem + OFF_LIST + 4 * pos++) = (sc << 16) | (0x8000u + 2047u - (uint32_t)((k >> 1) * 512 + 4 * at + 2 * (k & 1) + hi));
            }
            __syncwarp();
            if (lane == 0) mbar_arrive(bar_cand);
            STAMPIF(at == 0, 26);
            mbar_wait(bar_order0);
        }

        float accA[64], accB[64];
        Ring ring = {sb, bar_dummy, wg};
        {
            static_assert(GU0 - 16 == RE0, "segments");
            run_entries<0, 0>(ring, wg * 16, wg * 16 + RE0, accA, accB, facc, true);
            if (wg == 0) {
                float racc[4];
                mbar_wait(bar_vec);
                run_entries<0, 1>(ring, RE0, RE0 + 4, accA, accB, racc, false, true);
                const uint32_t red = sb + OFF_RED + 4 * (w * 32 + (c >> 1) * 16 + g);
                run_entries<0, 0>(ring, RE0 + 4, RE0 + 5, accA, accB, facc, false, false, [&]() {
                    pin4(racc);
                    asm volatile("{ .reg .pred p; setp.ne.u32 p, %3, 0; @p st.shared.f32 [%0], %1; @p st.shared.f32 [%0 + 32], %2; }" ::"r"(red),
                                 "f"((w & 1) ? racc[1] : racc[0]), "f"((w & 1) ? racc[3] : racc[2]), "r"((uint32_t)((c & 1) == (w >> 1))) : "memory");
                    __syncwarp();
                    if (lane == 0) mbar_arrive(bar_rdone);
                });
                run_entries<0, 0>(ring, RE0 + 5, 16, accA, accB, facc);
                if (lane == 0) mbar_arrive(bar_order0);
                mbar_wait(bar_epoch);
                mbar_wait(bar_cand);
                load_const();
                named_bar(3, 128);
            } else {
                mbar_wait(bar_xs);
                run_entries<0, 2>(ring, GU0, 32, accA, accB, facc, false, true);
                if (lane == 0) mbar_arrive(bar_order1);
            }
        }
        const uint32_t tag = *reinterpret_cast<volatile uint32_t*>(smem + OFF_EPOCH) + 1;
        const float sgn = prm.swapped ? -1.f : 1.f;
        float2 m1[2], a64[2];
#pragma unroll
        for (int h = 0; h < 2; h++) {
            m1[h] = make_float2(sgn * m0[h].y, -sgn * m0[h].x);
            a64[h] = cmul(a32[h], a32[h]);
        }
        const uint32_t tstart = clk32();
        wgmma_wait<0>();
        pin64(accA); pin64(accB); pin4(facc);
        if (lane == 0) mbar_arrive(ring.prev);
        STAMPIF(at == 0, 28 + wg);

        {
            const uint32_t t2 = tag & 3u;
            float2* cslot = &g_carry[wg * 512 + dt * 32 + w * 8 + g];
            const int j1 = chunk - 1 - c;
            uint2 v[4];
            auto poll = [&](int h) {
#pragma unroll
                for (int m = 0; m < 4; m++)
                    asm volatile("ld.relaxed.gpu.global.v2.b32 {%0, %1}, [%2];" : "=r"(v[m].x), "=r"(v[m].y) : "l"(cslot + max(j1 - 4 * m, 0) * 1024 + 256 * h) : "memory");
            };
            const uint32_t zmask = lds32(sb + OFF_EPOCH + 8);
            const uint32_t stg = sb + OFF_STG + w * 1024 + (lane & 7) * 128 + (((lane >> 3) ^ (lane & 7)) << 4);
            const uint32_t keep = c == (g >> 1) ? 0xFFFEFFFEu : 0xFFFFFFFFu, tagw = ((t2 & 1) | ((t2 & 2) << 15)) & ~keep;
#pragma unroll
            for (int h = 0; h < 2; h++) {
                float (&acc)[64] = h ? accB : accA;
                const float2 a1 = make_float2(a[h].x, -sgn * a[h].y);
                float2 e = make_float2(acc[0], acc[2]);
#pragma unroll
                for (int s = 1; s < 32; s++) {
                    const int i0 = 4 * (s >> 1) + (s & 1);
                    e = cfma(a1, e, make_float2(acc[i0], acc[i0 + 2]));
                }
                e = make_float2(m0[h].x * e.x + m0[h].y * e.y, m1[h].x * e.x + m1[h].y * e.y);
                float2 y = make_float2(__shfl_up_sync(0xffffffffu, e.x, 1, 4), __shfl_up_sync(0xffffffffu, e.y, 1, 4));
                if (c >= 1) e = cfma(a32[h], y, e);
                y = make_float2(__shfl_up_sync(0xffffffffu, e.x, 2, 4), __shfl_up_sync(0xffffffffu, e.y, 2, 4));
                if (c >= 2) e = cfma(a64[h], y, e);
                asm volatile("{ .reg .pred p; setp.eq.u32 p, %3, 3; @p st.relaxed.gpu.global.v2.b32 [%0], {%1, %2}; }" ::"l"(cslot + chunk * 1024 + 256 * h),
                             "r"((__float_as_uint(e.x) & ~3u) | t2), "r"((__float_as_uint(e.y) & ~3u) | t2), "r"(c) : "memory");
                pace_until(tstart);
                STAMPIF(at == 0, 30 + 2 * wg + h);
                float2 w0 = make_float2(__shfl_up_sync(0xffffffffu, e.x, 1, 4), __shfl_up_sync(0xffffffffu, e.y, 1, 4));
                if (c == 0) w0 = make_float2(0.f, 0.f);
                const float2 one = make_float2(1.f, 0.f), a256 = cmul(a128[h], a128[h]), a512 = cmul(a256, a256);
                const float2 pw128 = cmul((c & 1) ? a128[h] : one, (c & 2) ? a256 : one), pw32 = cmul((c & 1) ? a32[h] : one, (c & 2) ? a64[h] : one);
                float z = 0.f;
#pragma unroll
                for (int s = 0; s < 32; s++) {
                    const int i0 = 4 * (s >> 1) + (s & 1);
                    if (s == POLL_S) { pace_until(tstart); poll(h); }
                    const float f = acc[i0], k = acc[i0 + 2];
                    acc[i0] = fmaf(m0[h].x, f, fmaf(m0[h].y, k, z)); acc[i0 + 2] = fmaf(m1[h].x, f, fmaf(m1[h].y, k, z));
                    z = __uint_as_float(__float_as_uint(acc[i0]) & zmask);
                }
                pace_until(tstart);
                STAMPIF(at == 0, 34 + 2 * wg + h);
                if (h || wg) mbar_wait(bar_out + 32 * wg + 16 * h - 8);
                if (chunk > 0) {
                    uint32_t it = 0;
                    while (true) {
                        uint32_t bad = 0;
#pragma unroll
                        for (int m = 0; m < 4; m++) bad |= (v[m].x ^ t2) | (v[m].y ^ t2);
                        if (__all_sync(0xffffffffu, (bad & 3u) == 0)) break;
                        poll(h);
                        if (++it > SPIN_LIMIT) __trap();
                    }
                    float2 hin = make_float2(0.f, 0.f);
#pragma unroll
                    for (int m = 3; m >= 0; m--)
                        hin = cfma(a512, hin, j1 - 4 * m >= 0 ? make_float2(__uint_as_float(v[m].x), __uint_as_float(v[m].y)) : make_float2(0.f, 0.f));
                    hin = cmul(pw128, hin);
                    hin.x += __shfl_xor_sync(0xffffffffu, hin.x, 1); hin.y += __shfl_xor_sync(0xffffffffu, hin.y, 1);
                    hin.x += __shfl_xor_sync(0xffffffffu, hin.x, 2); hin.y += __shfl_xor_sync(0xffffffffu, hin.y, 2);
                    w0 = cfma(pw32, hin, w0);
                }
                STAMPIF(at == 0, 38 + 2 * wg + h);
#pragma unroll
                for (int j = 0; j < 4; j++) {
                    uint32_t ra[4], ia[4];
#pragma unroll
                    for (int u = 0; u < 4; u++) {
                        const int i0 = 16 * j + 4 * u;
                        y = cfma(a[h], w0, make_float2(acc[i0], acc[i0 + 2]));
                        w0 = cfma(a[h], y, make_float2(acc[i0 + 1], acc[i0 + 3]));
                        ra[u] = pack_bf(y.x, w0.x);
                        ia[u] = pack_bf(y.y, w0.y);
                    }
                    const uint32_t hd = (stg ^ ((j & 1) * 64)) + (j >> 1) * 4096;
                    stsm4(hd, (ra[0] & keep) | tagw, ra[1], (ra[2] & keep) | tagw, ra[3]);
                    stsm4(hd + 8192, (ia[0] & keep) | tagw, ia[1], (ia[2] & keep) | tagw, ia[3]);
                    if (j & 1) {
                        __syncwarp();
                        if (lane == 0) mbar_arrive(bar_st + 32 * wg + 16 * h + 4 * (j & 2));
                    }
                }
                pace_until(tstart);
                STAMPIF(at == 0, 42 + 2 * wg + h);
            }
        }

        const int tl = 32 * (g >> 1) + (g & 1) + 4 * w + 16 * wg, t0 = chunk * 128 + tl;
        float* op = prm.out + (size_t)t0 * D_ + dt * 128 + 4 * c;
        float gv[2], om[2];
        uint32_t routed[2];
        auto row_setup = [&]() {
            const uint4 sa = *reinterpret_cast<const uint4*>(smem + OFF_SEL), sc = *reinterpret_cast<const uint4*>(smem + OFF_SEL + 16);
#pragma unroll
            for (int r = 0; r < 2; r++) {
                const uint32_t id = 0x8000u + 2047u - (uint32_t)(t0 + 2 * r);
                routed[r] = (uint16_t)sa.x == id || (uint16_t)sa.y == id || (uint16_t)sa.z == id || (uint16_t)sa.w == id ||
                            (uint16_t)sc.x == id || (uint16_t)sc.y == id || (uint16_t)sc.z == id || (uint16_t)sc.w == id;
                gv[r] = __bfloat162float(reinterpret_cast<const __nv_bfloat16*>(smem + OFF_G)[tl + 2 * r]);
                om[r] = rbf(1.0f - gv[r]);
            }
        };
        const uint32_t xr = 2 * (g & 3) + (g >> 2), xa = sb + OFF_STG + (16 * w + xr) * 128 + (((c >> 1) ^ xr) << 4) + (c & 1) * 8;
        auto skip_term = [&](float (&sk)[8], int j) {
            const uint2 dk = lds64(sb + OFF_DK + 32 * j + 8 * c);
            const float d[4] = {bf_lo(dk.x), bf_hi(dk.x), bf_lo(dk.y), bf_hi(dk.y)};
#pragma unroll
            for (int r = 0; r < 2; r++) {
                const uint2 xv = lds64((xa ^ (32 * (j & 3))) + (j >> 2) * ABYTES + r * 1024);
                const float xf[4] = {bf_lo(xv.x), bf_hi(xv.x), bf_lo(xv.y), bf_hi(xv.y)};
#pragma unroll
                for (int u = 0; u < 4; u++) sk[4 * r + u] = xf[u] * fmaf(gv[r], d[u], om[r]);
            }
        };
        const uint32_t xbuf = sb + w * 2048 + lane * 16;

        if (wg == 1) {
            float outB[64], sk[8][8];
            row_setup();
            const uint32_t tagw = (tag & 1) | ((tag & 2) << 15);
            mbar_wait(bar_fp);
            {
                const float4 o4 = lds128f(sb + OFF_XS + at * 16);
                const float o[4] = {o4.x, o4.y, o4.z, o4.w};
                float v[4];
#pragma unroll
                for (int u = 0; u < 4; u++) {
                    v[u] = rbf(facc[u] + o[u]);
                    if (!(cta & 1)) v[u] = __fdividef(v[u], 1.0f + __expf(-v[u]));
                }
                uint32_t w0 = pack_bf(v[0], v[1]), w1 = pack_bf(v[2], v[3]), cell[4];
                if (c == (g & 3)) { w0 = (w0 & 0xFFFEFFFEu) | tagw; w1 = (w1 & 0xFFFEFFFEu) | tagw; }
#pragma unroll
                for (int u = 0; u < 4; u++) {
                    const uint32_t s0 = __shfl_sync(0xffffffffu, w0, u, 4), s1 = __shfl_sync(0xffffffffu, w1, u, 4);
                    cell[u] = (c & 1) ? s1 : s0;
                }
                if (has_gu && c < 2)
                    asm volatile("{ .reg .b64 l, h; .reg .b128 t; mov.b64 l, {%1, %2}; mov.b64 h, {%3, %4}; mov.b128 t, {l, h}; st.relaxed.gpu.global.b128 [%0], t; }"
                                 ::"l"(g_hid + (cta & 1) * F_ + (cta >> 1) * 64 - 512 + w * 16 + g + 8 * c), "r"(cell[0]), "r"(cell[1]), "r"(cell[2]), "r"(cell[3]) : "memory");
            }
            const uint32_t tpub = clk32();
            STAMPIF(at == 0, 47);
            mbar_wait(bar_xb);
#pragma unroll
            for (int j = 0; j < 8; j++) { skip_term(sk[j], j); pace_until(tstart); }
            named_bar(2, 128);
            if (lane == 0) mbar_arrive(bar_xbfree);
            STAMPIF(at == 0, 46);
            {
                uint32_t hv[4][4], hu[4][4], it = 0;
                pace_until(tpub + HG0);
                while (true) {
                    uint32_t bad = 0;
#pragma unroll
                    for (int i = 0; i < 4; i++) {
                        const uint4* hp = g_hid + (cta >> 4) * 448 + (i < 3 ? i * 128 + at : 384 + (at & 63));
                        ld_cell(hv[i], hp); ld_cell(hu[i], hp + F_);
                    }
#pragma unroll
                    for (int i = 0; i < 4; i++)
                        bad |= (((c & 2) ? ((c & 1) ? hv[i][3] : hv[i][2]) : ((c & 1) ? hv[i][1] : hv[i][0])) ^ tagw) |
                               (((c & 2) ? ((c & 1) ? hu[i][3] : hu[i][2]) : ((c & 1) ? hu[i][1] : hu[i][0])) ^ tagw);
                    if (__all_sync(0xffffffffu, (bad & 0x00010001u) == 0)) break;
                    if (++it > SPIN_LIMIT) __trap();
                }
                STAMPIF(at == 0, 48);
#pragma unroll
                for (int i = 0; i < 4; i++)
                    sts128(sb + OFF_XS + 16 * (i < 3 ? i * 128 + at : 384 + (at & 63)), mul_bf2(hv[i][0], hu[i][0]), mul_bf2(hv[i][1], hu[i][1]),
                           mul_bf2(hv[i][2], hu[i][2]), mul_bf2(hv[i][3], hu[i][3]));
                asm volatile("fence.proxy.async.shared::cta;" ::: "memory");
                __syncwarp();
                if (lane == 0) mbar_arrive(bar_hs);
                STAMPIF(at == 0, 49);
            }
            ring.slot = 64 % NST;
            ring.prev = bar_dummy;
            auto fold = [&](int u0) {
                mbar_wait(bar_accb + 4 * u0);
#pragma unroll
                for (int v = 0; v < 8; v++) {
                    const uint4 pb = ldsm4(xbuf + ((59 + u0 + (v >> 2)) % NST) * SLOT + (v & 3) * 512);
                    float* q = &sk[2 * u0 + (v >> 1)][2 * (v & 1)];
                    q[0] = fmaf(gv[0], __uint_as_float(pb.x), q[0]); q[1] = fmaf(gv[0], __uint_as_float(pb.y), q[1]);
                    q[4] = fmaf(gv[1], __uint_as_float(pb.z), q[4]); q[5] = fmaf(gv[1], __uint_as_float(pb.w), q[5]);
                }
            };
            fold(0);
            mbar_wait(bar_order2);
#pragma unroll 1
            for (int i = 64; i < NENT; i++) run_small<1>(ring, i, outB, i == 64);
            if (lane == 0) mbar_arrive(bar_order3);
            fold(2);
            wgmma_wait<0>();
            pin64(outB);
            KSTAMP(NENT);
            STAMPIF(at == 0, 50);
#pragma unroll
            for (int u = 0; u < 16; u++) {
                const int o = 8 * (u >> 1) + 2 * (u & 1);
                const float* q = &sk[u >> 1][4 * (u & 1)];
                const float gr = gv[u & 1];
                put4(op + (u & 1) * 2 * D_ + 16 * (u >> 1), fmaf(gr, outB[o], q[0]), fmaf(gr, outB[o + 1], q[1]), fmaf(gr, outB[o + 4], q[2]),
                     fmaf(gr, outB[o + 5], q[3]), routed[u & 1]);
            }
            STAMPIF(at == 0, 51);
        } else {
            float outA[64], outB[64], gacc[4];
            mbar_wait(bar_xs);
            row_setup();
            STAMPIF(at == 0, 52);
            ring.slot = 32 % NST;
            ring.prev = bar_dummy;
            mbar_wait(bar_order1);
            run_entries<1, 2>(ring, 32, GU0 + 32, outA, outB, gacc, true, true);
            run_small<0>(ring, 52, outA);
            pin4(gacc);
            sts128(sb + OFF_XS + at * 16, __float_as_uint(gacc[0]), __float_as_uint(gacc[1]), __float_as_uint(gacc[2]), __float_as_uint(gacc[3]));
            __syncwarp();
            if (lane == 0) mbar_arrive(bar_fp);
#pragma unroll 1
            for (int i = 53; i < 61; i += 2) {
                run_entries<1, 0>(ring, i, i + 1, outA, outB, gacc);
                run_small<0>(ring, i + 1, outA);
            }
            pin64(outB);
#pragma unroll
            for (int u = 0; u < 4; u++) {
                if (u) run_small<0>(ring, 60 + u, outA);
                if (u == 3 && lane == 0) mbar_arrive(bar_order2);
                mbar_wait(empty + 8 * (59 + u));
#pragma unroll
                for (int v = 0; v < 4; v++) {
                    const int o = 16 * u + 4 * v;
                    stsm4(xbuf + ((59 + u) % NST) * SLOT + v * 512, __float_as_uint(outB[o]), __float_as_uint(outB[o + 1]), __float_as_uint(outB[o + 2]), __float_as_uint(outB[o + 3]));
                }
                __syncwarp();
                if ((u & 1) && lane == 0) mbar_arrive(bar_accb + 4 * (u - 1));
            }
            STAMPIF(at == 0, 55);
            mbar_wait(bar_xa);
            wgmma_wait<0>();
            pin64(outA);
            if (lane == 0) mbar_arrive(ring.prev);
            STAMPIF(at == 0, 53);
#pragma unroll
            for (int j = 0; j < 8; j++) {
                float sk[8];
                skip_term(sk, j);
#pragma unroll
                for (int r = 0; r < 2; r++) {
                    const int o = 8 * j + 2 * r;
                    put4(op + r * 2 * D_ + 16 * j, fmaf(gv[r], outA[o], sk[4 * r]), fmaf(gv[r], outA[o + 1], sk[4 * r + 1]), fmaf(gv[r], outA[o + 4], sk[4 * r + 2]),
                         fmaf(gv[r], outA[o + 5], sk[4 * r + 3]), routed[r]);
                }
                pace_until(tstart);
            }
            STAMPIF(at == 0, 54);
            const uint2 sk = lds64(sb + OFF_SEL + 8 * c), fk = lds64(sb + OFF_FAC + 8 * c);
            float* y0 = prm.out + (~sk.x & 2047u) * D_ + (cta & 15) * 64 + w * 16 + g;
            float* y1 = prm.out + (~sk.y & 2047u) * D_ + (cta & 15) * 64 + w * 16 + g;
            float yacc[4];
            const uint64_t dw = make_desc(sb), dh = (uint64_t)(((sb + OFF_XS) & 0x3FFFF) >> 4) | ((uint64_t)8 << 16) | ((uint64_t)8 << 32);
            mbar_wait(bar_hs);
            mbar_wait(bar_zero);
            mbar_wait(bar_dn);
            mbar_wait(bar_order3);
            STAMPIF(at == 0, 2);
            wgmma_fence();
#pragma unroll
            for (int n = 0; n < 28; n++) wgmma_n8<1, 1>(yacc, dw + ((n < 20 ? OFF_DN + (n >> 2) * ABYTES : n < 24 ? OFF_DN5 : OFF_DN6) >> 4) + (n & 3) * 128, dh + n * 16, n > 0);
            wgmma_commit();
            wgmma_wait<0>();
            pin4(yacc);
            atomicAdd(y0, yacc[0] * __uint_as_float(fk.x)); atomicAdd(y1, yacc[1] * __uint_as_float(fk.y));
            atomicAdd(y0 + 8, yacc[2] * __uint_as_float(fk.x)); atomicAdd(y1 + 8, yacc[3] * __uint_as_float(fk.y));
            STAMPIF(at == 0, 3);
        }
    }
}

typedef CUresult (*EncodeFn)(CUtensorMap*, CUtensorMapDataType, cuuint32_t, void*, const cuuint64_t*, const cuuint64_t*, const cuuint32_t*,
                             const cuuint32_t*, CUtensorMapInterleave, CUtensorMapSwizzle, CUtensorMapL2promotion, CUtensorMapFloatOOBfill);

bool encode(EncodeFn fn, CUtensorMap* m, const void* ptr, int rank, const cuuint64_t* dims, const cuuint64_t* strides, const cuuint32_t* box,
            CUtensorMapSwizzle sw = CU_TENSOR_MAP_SWIZZLE_128B, CUtensorMapL2promotion promo = CU_TENSOR_MAP_L2_PROMOTION_NONE) {
    const cuuint32_t es[5] = {1, 1, 1, 1, 1};
    return fn(m, CU_TENSOR_MAP_DATA_TYPE_BFLOAT16, rank, const_cast<void*>(ptr), dims, strides, box, es, CU_TENSOR_MAP_INTERLEAVE_NONE,
              sw, promo, CU_TENSOR_MAP_FLOAT_OOB_FILL_NONE) == CUDA_SUCCESS;
}

}

extern "C" void kernel_launch(void* const* d_in, const int* in_sizes, int n_in, void* d_out, int out_size) {
    (void)in_sizes; (void)n_in; (void)out_size;
    Params prm;
    prm.x = (const __nv_bfloat16*)d_in[0];
    prm.lam_re = (const __nv_bfloat16*)d_in[1];
    prm.lam_im = (const __nv_bfloat16*)d_in[2];
    prm.b_re = (const __nv_bfloat16*)d_in[3];
    prm.b_im = (const __nv_bfloat16*)d_in[4];
    prm.c_re = (const __nv_bfloat16*)d_in[5];
    prm.c_im = (const __nv_bfloat16*)d_in[6];
    prm.log_dt = (const __nv_bfloat16*)d_in[7];
    prm.dskip = (const __nv_bfloat16*)d_in[8];
    prm.w_r = (const __nv_bfloat16*)d_in[10];
    prm.gate_w = (const __nv_bfloat16*)d_in[14];
    prm.out = (float*)d_out;
    prm.swapped = prm.b_im < prm.b_re;

    void* fnp = nullptr;
    cudaDriverEntryPointQueryResult qr;
    cudaGetDriverEntryPoint("cuTensorMapEncodeTiled", &fnp, cudaEnableDefault, &qr);
    EncodeFn fn = (EncodeFn)fnp;
    cudaFuncSetAttribute(fused_kernel, cudaFuncAttributeMaxDynamicSharedMemorySize, SMEM_BYTES);

    CUtensorMap mX, mB, mCre, mCim, mWg, mWu, mWd, mXr, mXe;
    const cuuint64_t row = 2048;
    {
        const cuuint64_t dims[4] = {1024, 2, 4, 976}, st[3] = {row, 32 * row, 2 * row};
        const cuuint32_t box[4] = {64, 2, 4, 16};
        encode(fn, &mX, prm.x, 4, dims, st, box, CU_TENSOR_MAP_SWIZZLE_128B, PROMO);
    }
    {
        const char *lo = (const char*)(prm.swapped ? prm.b_im : prm.b_re), *hi = (const char*)(prm.swapped ? prm.b_re : prm.b_im);
        const cuuint64_t dims[5] = {1024, 8, 2, 96, 2}, st[4] = {row, (cuuint64_t)(hi - lo), 8 * row, 256 * row};
        const cuuint32_t box[5] = {64, 8, 2, 4, 2};
        encode(fn, &mB, lo, 5, dims, st, box, CU_TENSOR_MAP_SWIZZLE_128B, PROMO);
    }
    {
        const cuuint64_t dims[5] = {1024, 2, 4, 2, 64}, st[4] = {row, 4 * row, 2 * row, 16 * row};
        const cuuint32_t box[5] = {64, 2, 4, 2, 8};
        encode(fn, &mCre, prm.c_re, 5, dims, st, box);
        encode(fn, &mCim, prm.c_im, 5, dims, st, box);
    }
    {
        const cuuint64_t dims[2] = {F_, D_}, st[1] = {F_ * 2}, dimsd[2] = {D_, F_}, std_[1] = {row};
        const cuuint32_t box[2] = {64, 32}, boxd[2] = {64, 32};
        encode(fn, &mWg, d_in[11], 2, dims, st, box, CU_TENSOR_MAP_SWIZZLE_128B, CU_TENSOR_MAP_L2_PROMOTION_NONE);
        encode(fn, &mWu, d_in[12], 2, dims, st, box, CU_TENSOR_MAP_SWIZZLE_128B, CU_TENSOR_MAP_L2_PROMOTION_NONE);
        encode(fn, &mWd, d_in[13], 2, dimsd, std_, boxd, CU_TENSOR_MAP_SWIZZLE_128B, CU_TENSOR_MAP_L2_PROMOTION_NONE);
    }
    {
        const cuuint64_t dims[3] = {D_ - 192, S_, 4}, st[2] = {row, 128};
        const cuuint32_t box[3] = {64, 16, 4};
        encode(fn, &mXr, prm.x, 3, dims, st, box, CU_TENSOR_MAP_SWIZZLE_128B, CU_TENSOR_MAP_L2_PROMOTION_NONE);
    }
    {
        const cuuint64_t dims[5] = {D_, 2, 2, 2, 976}, st[4] = {64 * row, row, 32 * row, 2 * row};
        const cuuint32_t box[5] = {64, 2, 2, 2, 8};
        encode(fn, &mXe, prm.x, 5, dims, st, box);
    }
    fused_kernel<<<NGRID, 384, SMEM_BYTES, cudaStreamPerThread>>>(mX, mB, mCre, mCim, mWg, mWu, mWd, mXr, mXe, prm);
}
```

```cpp
#include <cuda_runtime.h>
#include <cuda_bf16.h>
#include <cuda.h>
#include <stdint.h>

namespace {

constexpr int S_ = 2048, D_ = 1024, F_ = 3584;
constexpr int NCTA = 128, NGRID = 132;
constexpr int NENT = 64, FIN = 58, XE = 60;
constexpr int NST = 5;
constexpr int RE0 = 4;
constexpr int GU0 = 20;
constexpr uint32_t SLOT = 32768, ABYTES = 8192, WBYTES = 4096;
constexpr uint32_t OFF_XS = NST * SLOT;
constexpr uint32_t OFF_LIST = OFF_XS + 8192;
constexpr uint32_t OFF_W = OFF_XS + 16384;
constexpr uint32_t OFF_STG = OFF_W + 32768;
__host__ __device__ constexpr uint32_t slot_off(int i) { return i < XE ? (i % NST) * SLOT : i == XE ? OFF_W : ((i - 1) % NST) * SLOT; }
__host__ __device__ constexpr uint32_t sum_off(int v) { return (v < 4 ? OFF_XS + ABYTES : slot_off(FIN - 1 + v / 4)) + (v & 3) * 512; }
__host__ __device__ constexpr uint32_t dn_off(int u) {
    return u < 2 ? OFF_STG + u * ABYTES : u < 4 ? slot_off(FIN + 1 + u) : u < 6 ? sum_off(4 * (u - 4)) : slot_off(NENT - 1);
}
constexpr uint32_t OFF_CONST = OFF_STG;
constexpr uint32_t OFF_RED = OFF_STG + 4096;
constexpr uint32_t OFF_FULL = OFF_STG + 16384;
constexpr uint32_t OFF_EMPTY = OFF_FULL + 112 * 8;
constexpr uint32_t OFF_G = OFF_EMPTY + 96 * 8;
constexpr uint32_t OFF_DK = OFF_G + 256;
constexpr uint32_t OFF_KEYS = OFF_DK + 256;
constexpr uint32_t OFF_SEL = OFF_KEYS + 32;
constexpr uint32_t OFF_FAC = OFF_SEL + 32;
constexpr uint32_t OFF_EPOCH = OFF_FAC + 32;
constexpr uint32_t OFF_PROF = OFF_EPOCH + 16;
constexpr uint32_t SMEM_BYTES = OFF_PROF + 768;
static_assert(SMEM_BYTES <= 232448, "smem");

constexpr uint32_t sb = 1024;
constexpr uint32_t SPIN_LIMIT = 1u << 18;

__device__ uint4 g_h[8 * 4 * 256 * 64];
__device__ unsigned long long g_rpack[S_ / 2];
__device__ unsigned long long g_gpack[S_ / 2];
__device__ float4 g_carry[16 * 512];
__device__ unsigned int g_cnt[2 * 32];
__device__ unsigned int g_base[64 * 8];
__device__ uint4 g_time[NCTA * 2];
__device__ uint4 g_hid[2 * F_];
#define STAMPW(cond, w) do {} while (0)
#define LATE(i, tt) do {} while (0)
#define LANDED(i) do {} while (0)
#define STAMPIF(cond, i) STAMPW(cond, 72 + (i))
#define STAMP(i) STAMPW(1, 72 + (i))
#define KSTAMP(i) STAMPW((threadIdx.x & 127) == 0, i)

struct Params {
    const __nv_bfloat16 *x, *b_re, *b_im;
    int by_smid;
    int swapped;
    const __nv_bfloat16 *lam_re, *lam_im, *c_re, *c_im, *log_dt, *dskip, *w_r, *gate_w;
    float* out;
};

__device__ __forceinline__ uint32_t smem_u32(const void* p) { return (uint32_t)__cvta_generic_to_shared(p); }
__device__ __forceinline__ void mbar_init(uint32_t bar, uint32_t cnt) { asm volatile("mbarrier.init.shared::cta.b64 [%0], %1;" ::"r"(bar), "r"(cnt) : "memory"); }
__device__ __forceinline__ void mbar_expect_tx(uint32_t bar, uint32_t bytes) { asm volatile("mbarrier.arrive.expect_tx.shared::cta.b64 _, [%0], %1;" ::"r"(bar), "r"(bytes) : "memory"); }
__device__ __forceinline__ void mbar_arrive(uint32_t bar) { asm volatile("mbarrier.arrive.shared::cta.b64 _, [%0];" ::"r"(bar) : "memory"); }
__device__ __forceinline__ void mbar_wait(uint32_t bar, uint32_t parity = 0) {
    asm volatile("{ .reg .pred p; .reg .u32 n;\n"
                 "mbarrier.try_wait.parity.shared::cta.b64 p, [%0], %1;\n"
                 "@p bra.uni DONE;\n"
                 "mov.u32 n, 0;\n"
                 "AGAIN: mbarrier.try_wait.parity.shared::cta.b64 p, [%0], %1;\n"
                 "@p bra.uni DONE;\n"
                 "add.u32 n, n, 1;\n"
                 "setp.lt.u32 p, n, %2;\n"
                 "@p bra.uni AGAIN;\n"
                 "trap;\n"
                 "DONE: }" ::"r"(bar), "r"(parity), "n"(SPIN_LIMIT) : "memory");
}
__device__ __forceinline__ bool elect_one() {
    uint32_t pred;
    asm volatile("{ .reg .pred P; elect.sync _|P, 0xffffffff; selp.b32 %0, 1, 0, P; }" : "=r"(pred));
    return pred;
}
__device__ __forceinline__ void named_bar(int id, int n) { asm volatile("bar.sync %0, %1;" ::"r"(id), "r"(n) : "memory"); }

#define ONE "{ .reg .pred e; elect.sync _|e, 0xffffffff;\n@e "
__device__ __forceinline__ void bulk_load(uint32_t dst, const void* src, uint32_t bytes, uint32_t bar) {
    asm volatile(ONE "cp.async.bulk.shared::cluster.global.mbarrier::complete_tx::bytes [%0], [%1], %2, [%3]; }" ::"r"(dst), "l"(src), "r"(bytes), "r"(bar) : "memory");
}
__device__ __forceinline__ void sts128(uint32_t a, uint32_t x, uint32_t y, uint32_t z, uint32_t w) {
    asm volatile("st.shared.v4.u32 [%0], {%1,%2,%3,%4};" ::"r"(a), "r"(x), "r"(y), "r"(z), "r"(w) : "memory");
}
__device__ __forceinline__ uint2 lds64(uint32_t a) {
    uint2 v;
    asm volatile("ld.shared.v2.u32 {%0,%1}, [%2];" : "=r"(v.x), "=r"(v.y) : "r"(a) : "memory");
    return v;
}
__device__ __forceinline__ uint32_t clk32() { uint32_t c; asm volatile("mov.u32 %0, %%clock;" : "=r"(c)); return c; }
__device__ __forceinline__ void gap() { asm volatile("pmevent 1;" ::: "memory"); }
__device__ __forceinline__ void pace_until(uint32_t t) { while ((int)(clk32() - t) < 0) {} }
#define SLEEP_MARGIN 200
__device__ __forceinline__ void sleep_until(uint32_t t) {
    while ((int)(clk32() + SLEEP_MARGIN - t) < 0) __nanosleep(40);
    pace_until(t);
}
__device__ __forceinline__ void tma2(uint32_t dst, const CUtensorMap* m, int c0, int c1, uint32_t bar) {
    asm volatile("{ .reg .pred e; .reg .b64 pol; createpolicy.fractional.L2::evict_first.b64 pol, 1.0; elect.sync _|e, 0xffffffff;\n"
                 "@e cp.async.bulk.tensor.2d.shared::cluster.global.mbarrier::complete_tx::bytes.L2::cache_hint [%0], [%1, {%3, %4}], [%2], pol; }"
                 ::"r"(dst), "l"(m), "r"(bar), "r"(c0), "r"(c1) : "memory");
}
__device__ __forceinline__ void tma3(uint32_t dst, const CUtensorMap* m, int c0, int c1, uint32_t bar) {
    asm volatile(ONE "cp.async.bulk.tensor.3d.shared::cluster.global.mbarrier::complete_tx::bytes [%0], [%1, {%3, %4, %5}], [%2]; }"
                 ::"r"(dst), "l"(m), "r"(bar), "r"(c0), "r"(c1), "r"(0) : "memory");
}
__device__ __forceinline__ void tma4(uint32_t dst, const CUtensorMap* m, int c0, int c3, uint32_t bar) {
    asm volatile(ONE "cp.async.bulk.tensor.4d.shared::cluster.global.mbarrier::complete_tx::bytes [%0], [%1, {%3, %5, %5, %4}], [%2]; }"
                 ::"r"(dst), "l"(m), "r"(bar), "r"(c0), "r"(c3), "r"(0) : "memory");
}
__device__ __forceinline__ void tma5(uint32_t dst, const CUtensorMap* m, int c0, int c4, uint32_t bar) {
    asm volatile(ONE "cp.async.bulk.tensor.5d.shared::cluster.global.mbarrier::complete_tx::bytes [%0], [%1, {%3, %5, %5, %5, %4}], [%2]; }"
                 ::"r"(dst), "l"(m), "r"(bar), "r"(c0), "r"(c4), "r"(0) : "memory");
}
__device__ __forceinline__ void tma5b(uint32_t dst, const CUtensorMap* m, int c0, int c3, uint32_t bar) {
    asm volatile(ONE "cp.async.bulk.tensor.5d.shared::cluster.global.mbarrier::complete_tx::bytes [%0], [%1, {%3, %5, %5, %4, %5}], [%2]; }"
                 ::"r"(dst), "l"(m), "r"(bar), "r"(c0), "r"(c3), "r"(0) : "memory");
}
__device__ __forceinline__ void prefetch_l2(const void* p) {
    asm volatile("prefetch.global.L2 [%0];" ::"l"(p));
}

__device__ __forceinline__ uint32_t lds32(uint32_t a) {
    uint32_t v;
    asm volatile("ld.volatile.shared.u32 %0, [%1];" : "=r"(v) : "r"(a) : "memory");
    return v;
}
__device__ __forceinline__ uint32_t uni(uint32_t v) { return __shfl_sync(0xffffffffu, v, 0); }   __device__ __forceinline__ uint32_t ld_acquire(const unsigned int* p) {
    uint32_t v;
    asm volatile("ld.acquire.gpu.global.u32 %0, [%1];" : "=r"(v) : "l"(p) : "memory");
    return v;
}
__device__ __forceinline__ void red_release(unsigned int* p) { asm volatile("red.release.gpu.global.add.u32 [%0], 1;" ::"l"(p) : "memory"); }
__device__ __forceinline__ void wait_count(const unsigned int* p, uint32_t target) {
#pragma unroll 1
    for (uint32_t it = 0; it < SPIN_LIMIT; ++it)
        if ((int)(ld_acquire(p) - target) >= 0) return;
    __trap();
}
__device__ __forceinline__ void wait_count_slow(const unsigned int* p, uint32_t target) {
#pragma unroll 1
    for (uint32_t it = 0; it < SPIN_LIMIT; ++it) {
        if ((int)(ld_acquire(p) - target) >= 0) return;
        __nanosleep(200);
    }
    __trap();
}
__device__ __forceinline__ unsigned long long ld_relaxed1(const void* p) {
    unsigned long long v;
    asm volatile("ld.relaxed.gpu.global.b64 %0, [%1];" : "=l"(v) : "l"(p) : "memory");
    return v;
}
__device__ __forceinline__ ulonglong2 ld_relaxed2(const void* p) {
    ulonglong2 v;
    asm volatile("ld.relaxed.gpu.global.v2.b64 {%0, %1}, [%2];" : "=l"(v.x), "=l"(v.y) : "l"(p) : "memory");
    return v;
}
__device__ __forceinline__ void ld_cell(uint32_t (&v)[4], const void* p, bool on = true) {
    asm volatile("{ .reg .pred p; .reg .b64 l, h; .reg .b128 t; setp.ne.u32 p, %5, 0; mov.b64 l, {%0, %1}; mov.b64 h, {%2, %3}; mov.b128 t, {l, h};\n"
                 "@p ld.relaxed.gpu.global.b128 t, [%4]; mov.b128 {l, h}, t; mov.b64 {%0, %1}, l; mov.b64 {%2, %3}, h; }"
                 : "+r"(v[0]), "+r"(v[1]), "+r"(v[2]), "+r"(v[3]) : "l"(p), "r"((uint32_t)on) : "memory");
}
__device__ __forceinline__ void st_cell(void* p, uint32_t a, uint32_t b, uint32_t c, uint32_t d, bool on) {
    asm volatile("{ .reg .pred p; .reg .b64 l, h; .reg .b128 t; setp.ne.u32 p, %5, 0; mov.b64 l, {%1, %2}; mov.b64 h, {%3, %4}; mov.b128 t, {l, h};\n"
                 "@p st.relaxed.gpu.global.b128 [%0], t; }" ::"l"(p), "r"(a), "r"(b), "r"(c), "r"(d), "r"((uint32_t)on) : "memory");
}

__device__ __forceinline__ uint64_t make_desc(uint32_t addr, uint32_t sbo = 1024) {
    return (uint64_t)((addr & 0x3FFFF) >> 4) | ((uint64_t)1 << 16) | ((uint64_t)(sbo >> 4) << 32) | ((uint64_t)1 << 62);
}
__device__ __forceinline__ void wgmma_fence() { asm volatile("wgmma.fence.sync.aligned;" ::: "memory"); }
__device__ __forceinline__ void wgmma_commit() { asm volatile("wgmma.commit_group.sync.aligned;" ::: "memory"); }
template <int N> __device__ __forceinline__ void wgmma_wait() { asm volatile("wgmma.wait_group.sync.aligned %0;" ::"n"(N) : "memory"); }

#define R8(d, i) "+f"(d[i]), "+f"(d[i + 1]), "+f"(d[i + 2]), "+f"(d[i + 3]), "+f"(d[i + 4]), "+f"(d[i + 5]), "+f"(d[i + 6]), "+f"(d[i + 7])
#define R64(d) R8(d, 0), R8(d, 8), R8(d, 16), R8(d, 24), R8(d, 32), R8(d, 40), R8(d, 48), R8(d, 56)
template <int TA>
__device__ __forceinline__ void wgmma_n128(float (&d)[64], uint64_t da, uint64_t db, int scale_d = 1) {
    asm volatile("{ .reg .pred p; setp.ne.b32 p, %66, 0;\n"
                 "wgmma.mma_async.sync.aligned.m64n128k16.f32.bf16.bf16 "
                 "{%0,%1,%2,%3,%4,%5,%6,%7,%8,%9,%10,%11,%12,%13,%14,%15,%16,%17,%18,%19,%20,%21,%22,%23,%24,%25,%26,%27,%28,%29,%30,%31,"
                 "%32,%33,%34,%35,%36,%37,%38,%39,%40,%41,%42,%43,%44,%45,%46,%47,%48,%49,%50,%51,%52,%53,%54,%55,%56,%57,%58,%59,%60,%61,%62,%63}, "
                 "%64, %65, p, 1, 1, %67, 0; }"
                 : R64(d)
                 : "l"(da), "l"(db), "r"(scale_d), "n"(TA));
}
__device__ __forceinline__ void pin4(float (&d)[4]) { asm volatile("" : "+f"(d[0]), "+f"(d[1]), "+f"(d[2]), "+f"(d[3])::"memory"); }
__device__ __forceinline__ void pin64(float (&d)[64]) { asm volatile("" : R64(d)::"memory"); }

template <int TA, int TB = 0>
__device__ __forceinline__ void wgmma_n8(float (&d)[4], uint64_t da, uint64_t db, int scale_d = 1) {
    asm volatile("{ .reg .pred p; setp.ne.b32 p, %7, 0;\n"
                 "wgmma.mma_async.sync.aligned.m64n8k16.f32.bf16.bf16 {%0,%1,%2,%3}, %4, %5, p, 1, 1, %6, %8; }"
                 : "+f"(d[0]), "+f"(d[1]), "+f"(d[2]), "+f"(d[3])
                 : "l"(da), "l"(db), "n"(TA), "r"(scale_d), "n"(TB));
}

__device__ __forceinline__ float bf_lo(uint32_t u) { return __uint_as_float(u << 16); }
__device__ __forceinline__ float bf_hi(uint32_t u) { return __uint_as_float(u & 0xFFFF0000u); }
__device__ __forceinline__ float rbf(float v) { return __bfloat162float(__float2bfloat16_rn(v)); }
__device__ __forceinline__ uint32_t pack_bf(float lo, float hi) {
    uint32_t r;
    asm("cvt.rn.bf16x2.f32 %0, %1, %2;" : "=r"(r) : "f"(hi), "f"(lo));
    return r;
}
__device__ __forceinline__ uint32_t mul_bf2(uint32_t a, uint32_t b) {
    __nv_bfloat162 r = __hmul2(*reinterpret_cast<__nv_bfloat162*>(&a), *reinterpret_cast<__nv_bfloat162*>(&b));
    return *reinterpret_cast<uint32_t*>(&r);
}
__device__ __forceinline__ float2 cmul(float2 a, float2 b) { return make_float2(a.x * b.x - a.y * b.y, a.x * b.y + a.y * b.x); }
__device__ __forceinline__ float2 cfma(float2 a, float2 b, float2 c) {
    return make_float2(fmaf(a.x, b.x, fmaf(-a.y, b.y, c.x)), fmaf(a.x, b.y, fmaf(a.y, b.x, c.y)));
}
__device__ __forceinline__ float sigmoidf_(float v) { return __fdividef(1.0f, 1.0f + expf(-v)); }

__device__ __forceinline__ void bulk_store(void* dst, uint32_t src, uint32_t bytes) {
    asm volatile(ONE "cp.async.bulk.global.shared::cta.bulk_group [%0], [%1], %2; }" ::"l"(dst), "r"(src), "r"(bytes) : "memory");
}
__device__ __forceinline__ float4 lds128f(uint32_t a) {
    float4 v;
    asm volatile("ld.shared.v4.f32 {%0,%1,%2,%3}, [%4];" : "=f"(v.x), "=f"(v.y), "=f"(v.z), "=f"(v.w) : "r"(a) : "memory");
    return v;
}
__device__ __forceinline__ void stsm4(uint32_t a, uint32_t x, uint32_t y, uint32_t z, uint32_t w) {
    asm volatile("stmatrix.sync.aligned.m8n8.x4.shared.b16 [%0], {%1,%2,%3,%4};" ::"r"(a), "r"(x), "r"(y), "r"(z), "r"(w) : "memory");
}
__device__ __forceinline__ uint4 ldsm4(uint32_t a) {
    uint4 v;
    asm volatile("ldmatrix.sync.aligned.m8n8.x4.shared.b16 {%0,%1,%2,%3}, [%4];" : "=r"(v.x), "=r"(v.y), "=r"(v.z), "=r"(v.w) : "r"(a) : "memory");
    return v;
}
__device__ __forceinline__ void stg4_unless(float* p, float a, float b, float c, float d, uint32_t skip) {
    asm volatile("{ .reg .pred p; setp.eq.u32 p, %5, 0; @p st.global.v4.f32 [%0], {%1,%2,%3,%4}; }" ::"l"(p), "f"(a), "f"(b), "f"(c), "f"(d), "r"(skip) : "memory");
}
__device__ __forceinline__ void red4(float* p, float a, float b, float c, float d) {
    asm volatile("red.global.add.v4.f32 [%0], {%1,%2,%3,%4};" ::"l"(p), "f"(a), "f"(b), "f"(c), "f"(d) : "memory");
}

#define TT0 3600
#define PER 520
#define PCUT 60
#define PFIN 360
#define T2 0
#define P2 0
#define PF0 500
#define PF2_PACE 450
#define G0 700
#define R0 1200
#define R_PACE 700
#define W_SHIFT 250
#define PROMO CU_TENSOR_MAP_L2_PROMOTION_L2_256B
#define POLL_S 20
#define ST_TOL 100
#define ST_SHIFT 300
#define NBPF 16
#define CLK_NS 435
#define MARGIN 100
#define CPF0 4500
#define CPF_PACE 600
#define HG0 900
constexpr uint32_t duration(int i) { return PER + (i >= RE0 && i < RE0 + 4 ? 72 : 0) + (i >= GU0 && i < GU0 + 32 ? 36 : 0); }
constexpr uint32_t cmax(uint32_t a, uint32_t b) { return a > b ? a : b; }
constexpr uint32_t issue_time(int i) {
    return i <= NST ? TT0 : i < XE ? issue_time(i - 1) + duration(i - NST) : issue_time(XE - 1) + cmax((i - XE + 1) * PFIN, (i - XE) * (PER - PCUT));
}
template <int I> struct Sched { static constexpr uint32_t t = issue_time(I); };
template <int LO, int HI, class F>
__device__ __forceinline__ void for_entries(uint32_t base, F body) {
    constexpr uint32_t per = Sched<LO + 1>::t - Sched<LO>::t;
    static_assert(Sched<HI - 1>::t - Sched<LO>::t == (HI - 1 - LO) * per, "period");
    uint32_t tt = base + Sched<LO>::t;
#pragma unroll 1
    for (int i = LO; i < HI; i++) {
        body(i, tt);
        tt += per;
    }
}

struct Ring { uint32_t prev; int slot; };
struct NoHook { __device__ void operator()() const {} };
template <int TA, int SM, class H = NoHook>
__device__ __forceinline__ void run_entries(Ring& r, int lo, int hi, float (&accA)[64], float (&accB)[64], float (&small)[4],
                                            bool fresh = false, bool sfresh = false, H released = H()) {
    const uint64_t d0 = make_desc(sb);
    const bool leader = (threadIdx.x & 31) == 0;
#pragma unroll 1
    for (int i = lo; i < hi; i++) {
        const uint32_t bar = sb + OFF_FULL + 8 * i;
        const uint64_t da = d0 + (uint64_t)(r.slot * (SLOT >> 4));
        const int n = i - (SM == 1 ? RE0 : GU0);
        const uint64_t dw = d0 + (uint64_t)((OFF_W >> 4) + (SM == 1 ? n * 512 : (n & 7) * 256));
        const uint64_t dt8 = d0 + (uint64_t)((OFF_XS >> 4) + (SM == 1 ? n * 64 : (n >> 1) * 64 + (n & 1) * 4));
        r.slot = r.slot == NST - 1 ? 0 : r.slot + 1;
        mbar_wait(bar);
        KSTAMP(i);
        wgmma_fence();
#pragma unroll
        for (int kk = 0; kk < 4; kk++) {
            wgmma_n128<TA>(accA, da + kk * (TA ? 128 : 2), da + 1024 + kk * 2, kk > 0 || !fresh);
            if (SM == 1) wgmma_n8<0>(small, dw + kk * 2, dt8 + kk * 2, kk > 0 || !sfresh);
            if (SM == 2 && (kk & 1)) wgmma_n8<1>(small, dw + (kk >> 1) * 128, dt8 + (kk >> 1) * 2, kk > 1 || !sfresh);
            wgmma_n128<TA>(accB, da + 512 + kk * (TA ? 128 : 2), da + 1024 + kk * 2, kk > 0 || !fresh);
            if (kk == 1) {
                wgmma_commit();
                wgmma_wait<1>();
                if (leader) mbar_arrive(r.prev);
                released();
            }
        }
        wgmma_commit();
        r.prev = bar + (OFF_EMPTY - OFF_FULL);
        fresh = sfresh = false;
    }
}
template <int HALF, int I, class H>
__device__ __forceinline__ void run_small(float (&acc)[64], H side) {
    const uint64_t da = make_desc(sb) + (slot_off(I) >> 4);
    KSTAMP(I + HALF * (NENT - FIN));
    wgmma_fence();
#pragma unroll
    for (int kk = 0; kk < 4; kk++) {
        wgmma_n128<1>(acc, da + HALF * 512 + kk * 128, da + 1024 + kk * 2);
        side(kk);
    }
    wgmma_commit();
}
template <int V> struct Int { __host__ __device__ constexpr operator int() const { return V; } };
template <int N, class F> __device__ __forceinline__ void static_for(F f) {
    if constexpr (N > 0) { static_for<N - 1>(f); f(Int<N - 1>()); }
}

__global__ void __launch_bounds__(384, 1)
fused_kernel(const __grid_constant__ Params prm, const __grid_constant__ CUtensorMap mX, const __grid_constant__ CUtensorMap mB, const __grid_constant__ CUtensorMap mCre,
             const __grid_constant__ CUtensorMap mCim, const __grid_constant__ CUtensorMap mWg, const __grid_constant__ CUtensorMap mWu,
             const __grid_constant__ CUtensorMap mWd, const __grid_constant__ CUtensorMap mXr, const __grid_constant__ CUtensorMap mXe) {
    extern __shared__ __align__(1024) uint8_t smem[];
    const uint32_t cstart = clk32();
    const int tid = threadIdx.x, lane = tid & 31;
    const int warp = __shfl_sync(0xffffffffu, tid >> 5, 0);
    if (warp < 2) {
        const uint32_t b = blockIdx.x & 127;
        const char* pp = warp ? (const char*)((b & 64) ? prm.b_im : prm.b_re) + (b & 63) * 16384 : (const char*)prm.x + b * 32768;
        prefetch_l2(pp + ((lane >> 1) & (15 >> warp)) * 2048 + (lane & 1) * 128);
    }
    int cta;
    asm volatile("{ .reg .pred p; .reg .u32 s, a, b, u, q;\n"
                 "mov.u32 s, %%smid;\n"
                 "and.b32 a, s, 14; shl.b32 a, a, 2; shr.u32 b, s, 4; add.u32 a, a, b;\n"
                 "sub.u32 u, s, 64; shr.u32 u, u, 1; mul.lo.u32 q, u, 37; shr.u32 q, q, 8; shl.b32 u, u, 3; mad.lo.u32 u, q, -55, u; add.u32 u, u, 12;\n"
                 "setp.lt.u32 p, s, 64; selp.u32 a, a, u, p; and.b32 b, s, 1; mad.lo.u32 a, a, 2, b;\n"
                 "setp.lt.u32 p, s, 124; selp.u32 b, 8, -116, p; add.u32 b, b, s; setp.lt.u32 p, s, 120; selp.u32 a, a, b, p;\n"
                 "setp.ne.u32 p, %2, 0; selp.u32 %0, a, %1, p; }" : "=r"(cta) : "r"(blockIdx.x), "r"(prm.by_smid));
    if (cta >= NCTA) {
        if (smem_u32(smem) != sb) __trap();
        if (tid == 0) wait_count_slow(&g_cnt[0], (atomicAdd(&g_cnt[0], 1u) / NGRID + 1) * NGRID);
        return;
    }
    const int chunk = (cta >> 5) * 4 + ((cta >> 2) & 3);
    const int dt = ((cta >> 4) & 1) * 4 + (cta & 3);
    const bool has_gu = cta >= 16;
    constexpr uint32_t full = sb + OFF_FULL, empty = sb + OFF_EMPTY;
    constexpr uint32_t raw = full + 8 * 32;
    constexpr uint32_t bar_epoch = full + 8 * 96, bar_base = full + 8 * 97, bar_xs = full + 8 * 98, bar_dn = full + 8 * 99, bar_xb = full + 8 * 100,
        bar_xa = full + 8 * 101, bar_retry = full + 8 * 102, bar_out = full + 8 * 104;
    constexpr uint32_t bar_order2 = empty + 8 * 72, bar_order3 = empty + 8 * 73, bar_fp = empty + 8 * 74, bar_hs = empty + 8 * 75,
        bar_accb = empty + 8 * 76, bar_xbfree = empty + 8 * 78, bar_fold = empty + 8 * 79, bar_xafree = empty + 8 * 71, bar_st = empty + 8 * 80, bar_init2 = empty + 8 * 88, bar_order0 = empty + 8 * 89,
        bar_order1 = empty + 8 * 90, bar_rdone = empty + 8 * 91, bar_cand = empty + 8 * 92, bar_xs0 = empty + 8 * 93,
        bar_vec = empty + 8 * 94, bar_zero = empty + 8 * 70, bar_dummy = empty + 8 * 95;

    if (warp == 5) {
        if (elect_one()) {
#pragma unroll
            for (int i = 0; i < RE0 + 4; i++) mbar_init(full + 8 * i, 1);
            asm volatile("fence.proxy.async.shared::cta;" ::: "memory");
        }
        __syncwarp();
        asm volatile("bar.arrive 1, 192;" ::: "memory");
        STAMP(52);
#pragma unroll 1
        for (int i = 0; i < NST; i++) {
            if (i >= 2) pace_until(cstart + T2 + i * P2);
            tma5b(sb + i * SLOT, &mB, i * 64, dt * 4, full + 8 * i);
            tma4(sb + i * SLOT + 2 * ABYTES, &mX, i * 64, chunk * 64, full + 8 * i);
            STAMPIF(i == 0, 1);
        }
    } else if (warp < 4) {
        named_bar(1, 192);
        if (elect_one()) {
            if (warp < 3) {
                const uint32_t base = warp == 0 ? empty : warp == 1 ? empty + 640 : full + 768, cnt = warp < 2 ? 4 : 1;
#pragma unroll
                for (int i = 0; i < 16; i++) mbar_init(base + 8 * i, cnt);
            } else {
#pragma unroll
                for (int i = RE0 + 4; i < 9; i++) mbar_init(full + 8 * i, 1);
#pragma unroll
                for (int i = 0; i < 9; i++) mbar_expect_tx(full + 8 * i, i >= RE0 && i < RE0 + 4 ? SLOT + ABYTES : SLOT);
            }
            *reinterpret_cast<uint32_t*>(smem + OFF_KEYS + 16) = 0;
            *reinterpret_cast<uint32_t*>(smem + OFF_EPOCH + 4) = cstart;
            asm volatile("fence.proxy.async.shared::cta;" ::: "memory");
        }
        __syncwarp();
        asm volatile("bar.arrive 0, 256;" ::: "memory");
        named_bar(5, 224);
    } else if (warp < 8) {
        named_bar(5, 224);
        if (elect_one()) {
            if (warp == 4) {
                const uint32_t wb = has_gu ? SLOT + WBYTES : SLOT;
#pragma unroll
                for (int i = 9; i < 32; i++) mbar_init(full + 8 * i, 1);
#pragma unroll
                for (int i = 9; i < 32; i++) mbar_expect_tx(full + 8 * i, i < GU0 ? SLOT : wb);
                mbar_arrive(bar_init2);
            } else {
                const uint32_t base = warp == 6 ? full + 256 : empty + 128;
#pragma unroll
                for (int i = 0; i < 64; i++) mbar_init(base + 8 * i, warp == 7 ? 4 : i < 32 ? 3 : 1);
            }
            asm volatile("fence.proxy.async.shared::cta;" ::: "memory");
            mbar_arrive(bar_init2);
            STAMP(21);
        }
    }
    __syncwarp();

    if (warp >= 8) {
        asm volatile("setmaxnreg.dec.sync.aligned.u32 72;");
        const uint32_t c0 = cstart;
        STAMP(19);
        const CUtensorMap* mw = (cta & 1) ? &mWu : &mWg;
        const int dc = (cta & 15) * 64, dr = (cta >> 4) * 448;
        auto gutile = [&](int i) {
            const int n = i + 3 - GU0;
            if (has_gu) tma2(sb + OFF_W + (n & 7) * WBYTES, mw, (cta >> 1) * 64 - 512, n * 32, full + 8 * (i + 3));
        };
        if (warp == 8) {
            named_bar(0, 256);
            uint32_t dst = sb, base = c0;
            int i = NST;
#pragma unroll 1
            for (int sg = 0; sg < 5; sg++) {
                if (sg & 1) {
                    if (sg == 1) mbar_wait(bar_init2); else mbar_wait(bar_base);
                    base = uni(lds32(sb + OFF_EPOCH + 2 + 2 * sg));
                }
                const int end = (0x20611349 >> (6 * sg)) & 63;
                const uint32_t per = PER + (sg == 1 ? 72 : sg == 4 ? 36 : 0);
                uint32_t tt = base + (sg == 0 ? Sched<NST>::t : sg == 1 ? Sched<9>::t : sg == 2 ? Sched<13>::t : sg == 3 ? Sched<17>::t : Sched<24>::t);
#pragma unroll 1
                for (; i < end; i++) {
                    mbar_wait(empty + 8 * (i - NST));
                    LATE(i, tt);
                    pace_until(tt);
                    tma5b(dst, &mB, (i & 15) * 64, (i >> 4) * 64 + dt * 4, full + 8 * i);
                    tma4(dst + 2 * ABYTES, &mX, (i & 15) * 64, chunk * 64, full + 8 * i);
                    dst = dst == sb + (NST - 1) * SLOT ? sb : dst + SLOT;
                    tt += per;
                }
            }
            const char* hsrc = reinterpret_cast<const char*>(g_h) + (size_t)chunk * 524288;
            auto gemm2 = [&](int i, uint32_t d, int freed, uint32_t tt) {
                if (!(i & 3)) mbar_wait(bar_out + 2 * (i & 28));
                mbar_wait(empty + 8 * freed);
                LATE(i, tt);
                pace_until(tt);
                bulk_load(d, hsrc, 2 * ABYTES, raw + 8 * i);
                tma5(d + 2 * ABYTES, (i & 4) ? &mCim : &mCre, ((i & 3) + ((i >> 1) & 12)) * 64, dt * 8, full + 8 * i);
                hsrc += 2 * ABYTES;
            };
            {
                uint32_t tt = base + Sched<32>::t;
#pragma unroll 1
                for (int u = 0; u < 4; u++) {
                    const CUtensorMap* mc = (u & 1) ? &mCim : &mCre;
                    mbar_wait(bar_out + 8 * u);
#pragma unroll 1
                    for (int col = (u >> 1) * 256; i < 36 + 4 * u; i++, col += 64) {
                        mbar_wait(empty + 8 * (i - NST));
                        LATE(i, tt);
                        pace_until(tt);
                        bulk_load(dst, hsrc, 2 * ABYTES, raw + 8 * i);
                        tma5(dst + 2 * ABYTES, mc, col, dt * 8, full + 8 * i);
                        gutile(i);
                        hsrc += 2 * ABYTES;
                        dst = dst == sb + (NST - 1) * SLOT ? sb : dst + SLOT;
                        tt += PER + 36;
                    }
                }
            }
            for_entries<48, FIN - 1>(base, [&](int i, uint32_t tt) {
                gemm2(i, dst, i - NST, tt);
                const int n = i - GU0 - 29;
                if (n < 0) gutile(i);
                else if ((n & 5) == 1) tma5(sb + OFF_W + (n & 2) * (ABYTES / 2), &mXe, dt * 128 + (n & 2) * 32, chunk * 64, bar_xa);
                else asm volatile(ONE "cp.async.bulk.prefetch.tensor.2d.L2.global [%0, {%1, %2}]; }" ::"l"(&mWd), "r"(dc), "r"(dr + 64 * (n < 4 ? 1 + n / 2 : n - 1)) : "memory");
                dst = dst == sb + (NST - 1) * SLOT ? sb : dst + SLOT;
            });
            static_for<NENT - FIN + 1>([&](auto u) {
                constexpr int i = FIN - 1 + u;
                gemm2(i, sb + slot_off(i), i < XE ? i - NST : i == XE ? 71   : i - NST - 1, base + Sched<i>::t);
            });
            STAMP(4);
        } else if (warp == 9) {
            if (!(cta & 1) && lane < 8) asm volatile("st.relaxed.gpu.global.u32 [%0], %1;" ::"l"(&g_base[cta * 4 + lane]), "r"(cstart) : "memory");
#pragma unroll
            for (int u = 0; u < 8; u++) {
                const int row = (u >> 2) * 4 + (lane >> 3);
                asm volatile("cp.async.cg.shared.global [%0], [%1], 16;" ::"r"(sb + OFF_XS + (u & 3) * 1024 + row * 128 + (((lane & 7) ^ row) << 4)),
                             "l"((const char*)(u < 4 ? prm.w_r : prm.gate_w) + (u & 3) * 512 + lane * 16) : "memory");
            }
            uint32_t ticket = 0;
            if (lane == 0) ticket = atomicAdd(&g_cnt[0], 1u);
            named_bar(0, 256);
            if (lane == 0) {
                *reinterpret_cast<volatile uint32_t*>(smem + OFF_EPOCH) = ticket / NGRID;
                mbar_arrive(bar_epoch);
            }
            __syncwarp();
            asm volatile("cp.async.wait_all;" ::: "memory");
            asm volatile("fence.proxy.async.shared::cta;" ::: "memory");
            __syncwarp();
            if (lane < 4) mbar_arrive(bar_vec);
            STAMP(18);
#pragma unroll 1
            for (int it = 0; it < 3; it++) {
                uint32_t b0, b1;
                asm volatile("ld.relaxed.gpu.global.u32 %0, [%1];" : "=r"(b0) : "l"(&g_base[(cta & ~15) * 4]) : "memory");
                asm volatile("ld.relaxed.gpu.global.u32 %0, [%1];" : "=r"(b1) : "l"(&g_base[(cta & ~1) * 4]) : "memory");
                const bool ok0 = b0 - c0 + 400u < 800u, ok1 = b1 - c0 + 400u < 800u;
                if (ok0 || ok1) *reinterpret_cast<volatile uint32_t*>(smem + OFF_EPOCH + 4) = ok0 ? b0 : b1;
                if (__all_sync(0xffffffffu, ok0)) break;
            }
            STAMP(5);
            mbar_wait(bar_cand);
            {
                const uint32_t* list = reinterpret_cast<const uint32_t*>(smem + OFF_LIST);
                const int n = (int)lds32(sb + OFF_KEYS + 16);
#pragma unroll 1
                for (int i0 = 0; i0 < n; i0 += 32) {
                    const uint32_t k = list[i0 + lane];
                    int rank = 0;
#pragma unroll 2
                    for (int o = 0; o < n; o += 4) {
                        const uint4 l4 = *reinterpret_cast<const uint4*>(list + o);
                        rank += (l4.x > k) + (l4.y > k) + (l4.z > k) + (l4.w > k);
                    }
                    if (rank < 8) reinterpret_cast<uint32_t*>(smem + OFF_SEL)[rank] = k;
                }
                __syncwarp();
                STAMP(6);
                const uint32_t key = lds32(sb + OFF_SEL + 4 * (lane & 7)), tok = ~key & 2047u, tag = lds32(sb + OFF_EPOCH) + 1;
                const uint32_t ta = __shfl_sync(0xffffffffu, tok, lane >> 3), tb = __shfl_sync(0xffffffffu, tok, 4 + (lane >> 3));
                const uint32_t da = sb + OFF_XS + (lane >> 3) * 128 + (((lane & 7) ^ (lane >> 3)) << 4), db = (da ^ 64) + 512;
                const char *sa = (const char*)prm.x + ta * 2048 + (lane & 7) * 16, *sc = (const char*)prm.x + tb * 2048 + (lane & 7) * 16;
#pragma unroll
                for (int u = 0; u < 16; u++) {
                    asm volatile("cp.async.cg.shared.global [%0], [%1], 16;" ::"r"(da + u * 1024), "l"(sa + u * 128) : "memory");
                    asm volatile("cp.async.cg.shared.global [%0], [%1], 16;" ::"r"(db + u * 1024), "l"(sc + u * 128) : "memory");
                    if (u == 3) {
                        asm volatile("cp.async.wait_all;" ::: "memory");
                        asm volatile("fence.proxy.async.shared::cta;" ::: "memory");
                        __syncwarp();
                        if (lane < 4) mbar_arrive(bar_xs0);
                        STAMP(17);
                    }
                }
                if ((tok >> 7) == (uint32_t)chunk) {
                    float4* zp = reinterpret_cast<float4*>(prm.out + tok * D_ + dt * 128) + (lane >> 3) * 2;
#pragma unroll
                    for (int u = 0; u < 8; u++) zp[(u >> 1) * 8 + (u & 1)] = make_float4(0.f, 0.f, 0.f, 0.f);
                }
                uint32_t it = 0;
                unsigned long long u;
                do {
                    u = ld_relaxed1(&g_gpack[tok >> 1]);
                    if (++it > SPIN_LIMIT) __trap();
                } while (!__all_sync(0xffffffffu, (uint32_t)(u >> 32) == tag));
                const uint32_t kb = key >> 16;
                const float r = bf_lo((kb & 0x8000u) ? (kb & 0x7FFFu) : (~kb & 0xFFFFu)), gv = (tok & 1) ? bf_hi((uint32_t)u) : bf_lo((uint32_t)u);
                reinterpret_cast<float*>(smem + OFF_FAC)[lane & 7] = rbf(1.0f - gv) * rbf(sigmoidf_(r));
                asm volatile("cp.async.wait_all;" ::: "memory");
                asm volatile("fence.proxy.async.shared::cta;" ::: "memory");
                __syncwarp();
                if (lane == 0) mbar_arrive(bar_xs);
                STAMP(7);
            }
            char* hd = reinterpret_cast<char*>(g_h) + (size_t)chunk * 524288 + (dt >> 1) * 16384 + (dt & 1) * 4096;
            const uint32_t cb = uni(lds32(sb + OFF_EPOCH + 8)) + ST_SHIFT;
            uint32_t tt = cb + Sched<GU0 + 4>::t;
#pragma unroll 1
            for (int np = 0; np < 16; np++) {
                if (!(np & (np & 4 ? 1 : 2))) mbar_wait(bar_st + 4 * (np & 12) + ((np & 3) ? 8 : 0));
                const uint32_t now = clk32() - ST_TOL;
#pragma unroll 1
                while ((int)(tt - now) < 0) tt += PER + 36;
                const uint32_t src = sb + OFF_STG + (np & 3) * 4096;
                pace_until(tt);
                bulk_store(hd, src, 4096);
                asm volatile("cp.async.bulk.commit_group;" ::: "memory");
                if (np & 2) {
                    if (np & 1) asm volatile("cp.async.bulk.wait_group.read 0;" ::: "memory");
                    else asm volatile("cp.async.bulk.wait_group.read 1;" ::: "memory");
                    __syncwarp();
                    if (lane == 0) mbar_arrive(bar_out + 4 * (np & 12) + 8 * (np & 1));
                }
                STAMPIF(np & 2, 8 + ((np >> 1) & 6) + (np & 1));
                hd += (np & 1) ? 65536 - 8192 : 8192;
                tt += PER + 36;
            }
#pragma unroll 1
            for (int u = 0; u < 2; u++) {
                pace_until(tt);
                tma5(sb + OFF_STG + u * ABYTES, &mXe, dt * 128 + u * 64, chunk * 64 + 8, bar_xb);
                tt += PER + 36;
            }
            wait_count(&g_cnt[32], (lds32(sb + OFF_EPOCH) + 1) * NCTA);
            if (lane < 4) mbar_arrive(bar_zero);
            mbar_wait(bar_xbfree);
            static_for<7>([&](auto u) {
                if (u >= 2 && u != 5) mbar_wait(u == 4 ? bar_fold : empty + 8 * (u < 4 ? FIN + 1 + u : NENT - 1));
                if (u < 2) pace_until(cb + Sched<(u == 0 ? 58 : NENT - 1)>::t);
                tma2(sb + dn_off(u), &mWd, dc, dr + u * 64, bar_dn);
            });
            STAMP(27);
        } else {
            if (warp == 10) {
                const char* pb = (const char*)((cta & 64) ? prm.b_im : prm.b_re) + ((cta & 63) * 8 + ((lane & 15) >> 1)) * 2048 + (lane & 1) * 128;
#pragma unroll 1
                for (int k = 1; k < NBPF; k++) {
                    sleep_until(c0 + (k < 6 ? PF0 + k * PF2_PACE : k * 1050 - 2000));
                    prefetch_l2(pb + (k >> 3) * 1048576 + (k & 7) * 256);
                    if (k == 1) named_bar(0, 256);
                    if (k == 6) mbar_wait(bar_init2);
                    if (k >= 8 && lane < 8) mbar_expect_tx(full + 8 * (8 * k - 32 + lane), 8 * k + lane < GU0 + 64 && has_gu ? 2 * ABYTES + WBYTES : 2 * ABYTES);
                }
                asm volatile("prefetch.tensormap [%0];" ::"l"(&mCre));
                asm volatile("prefetch.tensormap [%0];" ::"l"(&mCim));
                asm volatile("prefetch.tensormap [%0];" ::"l"(&mWd));
                asm volatile("prefetch.tensormap [%0];" ::"l"(&mXe));
                if (lane < 3) mbar_expect_tx(bar_dn + 8 * lane, lane ? 2 * ABYTES : 7 * ABYTES);
                mbar_wait(bar_xs);
                mbar_wait(bar_st);
                if (lane == 0) red_release(&g_cnt[32]);
                __syncwarp();
                STAMP(22);
            } else {
                named_bar(1, 192);
#pragma unroll 1
                for (int u = 0; u < 4; u++) {
                    sleep_until(c0 + R0 + u * R_PACE);
                    tma3(sb + OFF_W + u * ABYTES, &mXr, u * 256, cta * 16, full + 8 * (RE0 + u));
                    if (u == 0) named_bar(0, 256);
                }
                asm volatile("prefetch.tensormap [%0];" ::"l"(mw));
                const uint32_t crow = cta * 16384 + lane * 128;
#pragma unroll 1
                for (int k = 0; k < 8; k++) {
                    sleep_until(c0 + CPF0 + k * CPF_PACE);
                    prefetch_l2((const char*)(k & 1 ? prm.c_im : prm.c_re) + crow + (k >> 1) * 4096);
                }
                mbar_wait(bar_base);
                const uint32_t cb = uni(lds32(sb + OFF_EPOCH + 8)) + W_SHIFT;
                auto early = [&](int i, uint32_t tt) {
                    mbar_wait(empty + 8 * (i - NST));
                    pace_until(tt);
                    gutile(i);
                };
                for_entries<GU0 - 3, GU0 + 4>(cb, early);
                for_entries<GU0 + 4, 32>(cb, early);
            }
            mbar_wait(bar_epoch);
            const uint32_t t2 = lds32(sb + OFF_EPOCH) + 1, tagw = (t2 & 1) | ((t2 & 2) << 15), half = (warp & 1) * ABYTES;
            const uint32_t lo = half + lane * 32 + (lane & 4) * 4 + (lane >> 3) * 4, retry = bar_retry + (warp & 1) * 8;
            const bool leader = lane == 0;
            uint32_t slot = sb + (32 % NST) * SLOT, rpar = 0;
#pragma unroll 1
            for (int i = 32; i < NENT; i++) {
                const uint32_t src = i == XE ? sb + OFF_W : slot;
                if (i != XE) slot = slot == sb + (NST - 1) * SLOT ? sb : slot + SLOT;
                auto current = [&]() {
                    uint32_t v[8];
#pragma unroll
                    for (int u = 0; u < 8; u++) v[u] = lds32(src + lo + u * 1024);
#pragma unroll
                    for (int u = 0; u < 8; u += 2) asm("lop3.b32 %0, %0, %1, %2, 0x7e;" : "+r"(v[u]) : "r"(v[u + 1]), "r"(tagw));
                    return __all_sync(0xffffffffu, ((v[0] | v[2] | v[4] | v[6]) & 0x00010001u) == 0);
                };
                mbar_wait(raw + 8 * i);
                if (!current()) {
#pragma unroll 1
                    for (uint32_t it = 0;; it++) {
                        if (it > SPIN_LIMIT) __trap();
                        STAMP(16);
                        if (leader) mbar_expect_tx(retry, ABYTES);
                        bulk_load(src + half, reinterpret_cast<const char*>(g_h) + (size_t)chunk * 524288 + (i - 32) * 16384 + half, ABYTES, retry);
                        mbar_wait(retry, rpar);
                        rpar ^= 1;
                        if (current()) break;
                    }
                }
                if (leader) mbar_arrive(full + 8 * i);
            }
        }
    } else {
        asm volatile("setmaxnreg.inc.sync.aligned.u32 216;");
        const int wg = warp >> 2, w = warp & 3, g = lane >> 2, c = lane & 3, at = tid & 127;
        float facc[4];
        float2 a[2], m0[2], a32[2], a128[2];
        auto load_const = [&]() {
            const float2* cp = reinterpret_cast<const float2*>(smem + OFF_CONST) + wg * 64 + w * 8 + g;
#pragma unroll
            for (int h = 0; h < 2; h++) { a[h] = cp[32 * h]; m0[h] = cp[128 + 32 * h]; a32[h] = cp[256 + 32 * h]; a128[h] = cp[384 + 32 * h]; }
        };
        if (wg == 0) {
            STAMPIF(tid == 0, 20);
        } else {
            const int pc = (at >> 5) * 256 + dt * 32 + (at & 31);
            const float lr = __bfloat162float(prm.lam_re[pc]), li = __bfloat162float(prm.lam_im[pc]), ld = __bfloat162float(prm.log_dt[pc]);
            const uint32_t dk = __ldg(reinterpret_cast<const uint32_t*>(prm.dskip + dt * 128) + (at & 63));
#pragma unroll
            for (int i = 0; i < 4; i++) sts128(sb + OFF_LIST + i * 2048 + at * 16, 0u, 0u, 0u, 0u);

            {
                reinterpret_cast<uint32_t*>(smem + OFF_DK)[at & 63] = dk;
                const float dtv = rbf(expf(ld));
                const float er = expf(dtv * lr);
                float sn, cs;
                sincosf(dtv * li, &sn, &cs);
                const float ar = er * cs, ai = er * sn;
                const float nr = ar - 1.0f, ni = ai;
                const bool big = fabsf(lr) >= fabsf(li);
                const float t = (big ? li : lr) / (big ? lr : li), dn = big ? lr + li * t : lr * t + li;
                const float cr = (big ? nr + ni * t : nr * t + ni) / dn, ci = (big ? ni - nr * t : ni * t - nr) / dn;
                float2* cp = reinterpret_cast<float2*>(smem + OFF_CONST) + at;
                float2 pw = make_float2(ar, prm.swapped ? ai : -ai);
                cp[0] = pw;
                cp[128] = make_float2(prm.swapped ? -2.f * cr : 2.f * cr, -2.f * ci);
#pragma unroll
                for (int i = 1; i <= 7; i++) {
                    pw = cmul(pw, pw);
                    if (i == 5) cp[256] = pw;
                    if (i == 7) cp[384] = pw;
                }
                __syncwarp();
            }
            named_bar(2, 128);
            load_const();
            mbar_wait(bar_epoch);
            const uint32_t tag = *reinterpret_cast<volatile uint32_t*>(smem + OFF_EPOCH) + 1;
            st_cell(&g_carry[(chunk >> 2) * 2048 + ((w & 1) * 256 + dt * 32 + lane) * 4 + (chunk & 3)], tag + 2, 0, 0, 0, w < 2);
            if (w == 2) st_cell(lane < 4 ? (uint4*)g_rpack + cta * 4 + lane : lane < 8 ? (uint4*)g_gpack + cta * 4 + lane - 4 : g_time + cta * 2 + (lane & 1), 0, 0, 0, 0, lane < 10);
            {
                const uint32_t nt = ((tag & 1) | ((tag & 2) << 15)) ^ 0x00010001u;
                st_cell(g_hid + (cta & 1) * F_ + (cta >> 1) * 64 - 512 + (at & 63), nt, nt, nt, nt, has_gu && w >= 2);
            }
            named_bar(2, 128);
            mbar_wait(bar_rdone);

            uint32_t gown;
            asm volatile("mov.u32 %0, %%globaltimer_lo;" : "=r"(gown));
            const uint32_t tpub = clk32();
            st_cell(g_time + cta * 2, tag, tpub, gown, 0, at == 64);
            if (w < 2) {
                const float2* red = reinterpret_cast<const float2*>(smem + OFF_RED) + w * 8 + (lane & 7);
                const float2 r0 = red[0], r1 = red[16], r2 = red[32], r3 = red[48];
                const float v0 = (r0.x + r1.x) + (r2.x + r3.x), v1 = (r0.y + r1.y) + (r2.y + r3.y);
                uint32_t pk2;
                if (w == 0) {
                    pk2 = pack_bf(v0, v1);
                    pk2 ^= (((pk2 >> 15) & 0x00010001u) * 0x7FFFu) ^ 0x80008000u;
                } else pk2 = pack_bf(sigmoidf_(rbf(v0)), sigmoidf_(rbf(v1)));
                if (lane < 8) asm volatile("st.relaxed.gpu.global.b64 [%0], %1;" ::"l"((w ? g_gpack : g_rpack) + cta * 8 + lane), "l"(((unsigned long long)tag << 32) | pk2) : "memory");
                __syncwarp();
            }
            STAMPIF(at == 0, 24);
            uint32_t it = 0, pr[8], g1, tm[4] = {};
            sleep_until(tpub + G0);
            while (true) {
                bool ok = true;
#pragma unroll
                for (int k = 0; k < 4; k++) {
                    const ulonglong2 u = ld_relaxed2(&g_rpack[k * 256 + 2 * at]);
                    ok = ok && (uint32_t)(u.x >> 32) == tag && (uint32_t)(u.y >> 32) == tag;
                    pr[2 * k] = (uint32_t)u.x; pr[2 * k + 1] = (uint32_t)u.y;
                }
                const unsigned long long u1 = ld_relaxed1(&g_gpack[chunk * 64 + (at & 63)]);
                ok = ok && (uint32_t)(u1 >> 32) == tag;
                g1 = (uint32_t)u1;
                ld_cell(tm, g_time + at * 2);
                ok = ok && tm[0] == tag;
                if (__all_sync(0xffffffffu, ok)) break;
                if (++it > SPIN_LIMIT) __trap();
            }
            STAMPIF(lane == 0, 25);
            uint32_t m = __vmaxu2(__vimax3_u16x2(__vimax3_u16x2(pr[0], pr[1], pr[2]), pr[3], pr[4]), __vimax3_u16x2(pr[5], pr[6], pr[7]));
            m = (max(m, m << 16) & 0xFFFF0000u) | (uint32_t)lane;
            const uint32_t m1 = __reduce_max_sync(0xffffffffu, m), m2 = __reduce_max_sync(0xffffffffu, m == m1 ? 0u : m);
            uint32_t* keys = reinterpret_cast<uint32_t*>(smem + OFF_KEYS);
            const uint32_t glast = gown + (uint32_t)__reduce_max_sync(0xffffffffu, (int)(tm[2] - gown));
            if (lane == 0) { keys[w] = m2; reinterpret_cast<uint32_t*>(smem + OFF_XS + 1024)[w] = glast; }
            reinterpret_cast<uint2*>(smem + OFF_XS)[at] = make_uint2(tm[1], tm[2]);
            sts128(sb + OFF_XS + 4096 + at * 16, pr[0], pr[1], pr[2], pr[3]);
            sts128(sb + OFF_XS + 6144 + at * 16, pr[4], pr[5], pr[6], pr[7]);
            *reinterpret_cast<uint32_t*>(smem + OFF_G + 4 * (at & 63)) = g1;
            named_bar(2, 128);
            if (at == 96) {
                const uint4 g4 = *reinterpret_cast<const uint4*>(smem + OFF_XS + 1024);
                const int last = max(max((int)(g4.x - gown), (int)(g4.y - gown)), max((int)(g4.z - gown), (int)(g4.w - gown)));
                uint2 ref = reinterpret_cast<const uint2*>(smem + OFF_XS)[cta & ~15];
                if ((uint32_t)(ref.x - tpub - (((int)(ref.y - gown) * CLK_NS) >> 8) + 400) >= 800u) ref = reinterpret_cast<const uint2*>(smem + OFF_XS)[cta & ~1];
                *reinterpret_cast<volatile uint32_t*>(smem + OFF_EPOCH + 8) = ref.x + ((min((int)(gown + last - ref.y), 4000) * CLK_NS) >> 8) + MARGIN - Sched<RE0 + 8>::t;
                mbar_arrive(bar_base);
                STAMP(23);
            }
            __syncwarp();
            const uint4 th4 = *reinterpret_cast<const uint4*>(keys);
            const uint32_t th = (max(min(min(th4.x, th4.y), min(th4.z, th4.w)) >> 16, 1u) - 1u) * 0x00010001u;
            uint32_t mask = 0;
#pragma unroll
            for (int k = 7; k >= 0; k--) mask = mask * 2 + __vminu2(__vmaxu2(pr[k], th) ^ th, 0x00010001u);
            uint32_t pos = 0;
            asm volatile("{ .reg .pred p; setp.ne.u32 p, %2, 0; @p atom.shared.add.u32 %0, [%1], %2; }" : "+r"(pos) : "r"(sb + OFF_KEYS + 16), "r"(__popc(mask)) : "memory");
            while (mask) {
                const int bit = __ffs(mask) - 1, k = bit & 7, hi = bit >> 4;
                mask &= mask - 1;
                const uint32_t sc = *reinterpret_cast<const uint16_t*>(smem + OFF_XS + 4096 + (k >> 2) * 2048 + at * 16 + (k & 3) * 4 + hi * 2);
                *reinterpret_cast<uint32_t*>(smem + OFF_LIST + 4 * pos++) = (sc << 16) | (0x8000u + 2047u - (uint32_t)((k >> 1) * 512 + 4 * at + 2 * (k & 1) + hi));
            }
            __syncwarp();
            if (lane == 0) mbar_arrive(bar_cand);
            STAMPIF(lane == 0, 26);
            mbar_wait(bar_order0);
        }

        float accA[64], accB[64];
        Ring ring = {bar_dummy, wg};
        {
            static_assert(GU0 - 16 == RE0, "segments");
            run_entries<0, 0>(ring, wg * 16, wg * 16 + RE0, accA, accB, facc, true);
            if (wg == 0) {
                float racc[4];
                mbar_wait(bar_vec);
                mbar_wait(bar_init2);
                run_entries<0, 1>(ring, RE0, RE0 + 4, accA, accB, racc, false, true);
                const uint32_t red = sb + OFF_RED + 4 * (w * 32 + (c >> 1) * 16 + g);
                run_entries<0, 0>(ring, RE0 + 4, RE0 + 5, accA, accB, facc, false, false, [&]() {
                    pin4(racc);
                    asm volatile("{ .reg .pred p; setp.ne.u32 p, %3, 0; @p st.shared.f32 [%0], %1; @p st.shared.f32 [%0 + 32], %2; }" ::"r"(red),
                                 "f"((w & 1) ? racc[1] : racc[0]), "f"((w & 1) ? racc[3] : racc[2]), "r"((uint32_t)((c & 1) == (w >> 1))) : "memory");
                    __syncwarp();
                    if (lane == 0) mbar_arrive(bar_rdone);
                });
                run_entries<0, 0>(ring, RE0 + 5, 16, accA, accB, facc);
                if (lane == 0) mbar_arrive(bar_order0);
                mbar_wait(bar_epoch);
                mbar_wait(bar_cand);
                load_const();
                named_bar(3, 128);
            } else {
#pragma unroll
                for (int u = 0; u < 2; u++) {
                    mbar_wait(u ? bar_xs : bar_xs0);
                    run_entries<0, 2>(ring, GU0 + 8 * u, GU0 + 8 + 4 * u, accA, accB, facc, false, u == 0);
                }
                if (lane == 0) mbar_arrive(bar_order1);
            }
        }
        const uint32_t tag = *reinterpret_cast<volatile uint32_t*>(smem + OFF_EPOCH) + 1;
        const float2 a64[2] = {cmul(a32[0], a32[0]), cmul(a32[1], a32[1])};
        wgmma_wait<0>();
        pin64(accA); pin64(accB); pin4(facc);
        if (lane == 0) mbar_arrive(ring.prev);
        STAMPIF(at == 0, 28 + wg);

        const int tl = 32 * (g >> 1) + (g & 1) + 4 * w + 16 * wg, t0 = chunk * 128 + tl;
        float* op = prm.out + (size_t)t0 * D_ + dt * 128 + 4 * c;
        uint2 xv[8][2], dk[8];
        float gv[2], om[2];
        uint32_t routed[2];
        auto row_setup = [&]() {
            const uint4 sa = *reinterpret_cast<const uint4*>(smem + OFF_SEL), sc = *reinterpret_cast<const uint4*>(smem + OFF_SEL + 16);
#pragma unroll
            for (int r = 0; r < 2; r++) {
                const uint32_t id = 0x8000u + 2047u - (uint32_t)(t0 + 2 * r);
                routed[r] = (uint16_t)sa.x == id || (uint16_t)sa.y == id || (uint16_t)sa.z == id || (uint16_t)sa.w == id ||
                            (uint16_t)sc.x == id || (uint16_t)sc.y == id || (uint16_t)sc.z == id || (uint16_t)sc.w == id;
                gv[r] = __bfloat162float(reinterpret_cast<const __nv_bfloat16*>(smem + OFF_G)[tl + 2 * r]);
                om[r] = rbf(1.0f - gv[r]);
            }
#pragma unroll
            for (int j = 0; j < 8; j++) dk[j] = lds64(sb + OFF_DK + 32 * j + 8 * c);
        };
        auto release = [&](uint32_t bar) {
            asm volatile("fence.proxy.async.shared::cta;" ::: "memory");
            __syncwarp();
            if (lane == 0) mbar_arrive(bar);
        };

        {
            const uint32_t t2 = tag & 3u;
            float4* cslot = &g_carry[(wg * 256 + dt * 32 + w * 8 + g) * 4];
            float2 e[2], w0[2];
#pragma unroll
            for (int h = 0; h < 2; h++) {
                float (&acc)[64] = h ? accB : accA;
                const float2 a1 = make_float2(a[h].x, -a[h].y);
                e[h] = make_float2(acc[0], acc[2]);
#pragma unroll
                for (int s = 1; s < 32; s++) {
                    const int i0 = 4 * (s >> 1) + (s & 1);
                    e[h] = cfma(a1, e[h], make_float2(acc[i0], acc[i0 + 2]));
                }
                asm volatile("" : "+f"(e[h].x), "+f"(e[h].y), "+f"(accB[0]), "+f"(accB[2]));
                if (!h) gap();
            }
#pragma unroll
            for (int h = 0; h < 2; h++) {
                e[h] = make_float2(fmaf(m0[h].x, e[h].x, m0[h].y * e[h].y), fmaf(-m0[h].x, e[h].y, m0[h].y * e[h].x));
                float2 y = make_float2(__shfl_up_sync(0xffffffffu, e[h].x, 1, 4), __shfl_up_sync(0xffffffffu, e[h].y, 1, 4));
                if (c >= 1) e[h] = cfma(a32[h], y, e[h]);
                y = make_float2(__shfl_up_sync(0xffffffffu, e[h].x, 2, 4), __shfl_up_sync(0xffffffffu, e[h].y, 2, 4));
                if (c >= 2) e[h] = cfma(a64[h], y, e[h]);
            }
            st_cell(cslot + (chunk >> 2) * 2048 + (chunk & 3), (__float_as_uint(e[0].x) & ~3u) | t2, __float_as_uint(e[0].y), __float_as_uint(e[1].x), __float_as_uint(e[1].y), c == 3);
            gap();
            STAMPIF(lane == 0, 30 + 2 * wg);
            const int j1 = chunk - 1 - c;
            uint32_t v[4][4] = {{t2, 0, 0, 0}, {t2, 0, 0, 0}, {t2, 0, 0, 0}, {t2, 0, 0, 0}};
            auto poll = [&]() {
#pragma unroll
                for (int m = 0; m < 4; m++) ld_cell(v[m], cslot + (j1 >> 2) * 2048 + c - m * 2048, j1 >= 4 * m);
            };
            float2 a512[2], pw128[2], pw32[2];
#pragma unroll
            for (int h = 0; h < 2; h++) {
                float (&acc)[64] = h ? accB : accA;
                w0[h] = make_float2(__shfl_up_sync(0xffffffffu, e[h].x, 1, 4), __shfl_up_sync(0xffffffffu, e[h].y, 1, 4));
                if (c == 0) w0[h] = make_float2(0.f, 0.f);
                const float2 one = make_float2(1.f, 0.f), a256 = cmul(a128[h], a128[h]);
                a512[h] = cmul(a256, a256);
                pw128[h] = cmul((j1 & 1) ? a128[h] : one, (j1 & 2) ? a256 : one);
                pw32[h] = cmul((c & 1) ? a32[h] : one, (c & 2) ? a64[h] : one);
                asm volatile("" : "+f"(a512[h].x), "+f"(a512[h].y), "+f"(pw128[h].x), "+f"(pw128[h].y), "+f"(pw32[h].x), "+f"(pw32[h].y));
                gap();
#pragma unroll
                for (int n = 0; n < 16; n++) {
                    if (16 * h + n == POLL_S) poll();
                    asm volatile("{ .reg .f32 a, b, c, d, n; neg.f32 n, %4; mul.f32 a, %1, %5; mul.f32 b, %0, %5; mul.f32 c, %3, %5; mul.f32 d, %2, %5;\n"
                                 "fma.rn.f32 %0, %0, %4, a; fma.rn.f32 %1, %1, n, b; fma.rn.f32 %2, %2, %4, c; fma.rn.f32 %3, %3, n, d; }"
                                 : "+f"(acc[4 * n]), "+f"(acc[4 * n + 2]), "+f"(acc[4 * n + 1]), "+f"(acc[4 * n + 3]) : "f"(m0[h].x), "f"(m0[h].y));
                    if (n & 1) gap();
                }
            }
            STAMPIF(lane == 0, 34 + 2 * wg);
            {
                uint32_t it = 0;
                while (!__all_sync(0xffffffffu, (((v[0][0] ^ t2) | (v[1][0] ^ t2) | (v[2][0] ^ t2) | (v[3][0] ^ t2)) & 3u) == 0)) {
                    poll();
                    if (++it > SPIN_LIMIT) __trap();
                }
                STAMPIF(lane == 0, 35 + 2 * wg);
#pragma unroll
                for (int h = 0; h < 2; h++) {
                    float2 hin = make_float2(__uint_as_float(v[3][2 * h]), __uint_as_float(v[3][2 * h + 1]));
#pragma unroll
                    for (int m = 2; m >= 0; m--) hin = cfma(a512[h], hin, make_float2(__uint_as_float(v[m][2 * h]), __uint_as_float(v[m][2 * h + 1])));
                    hin = cmul(pw128[h], hin);
                    hin.x += __shfl_xor_sync(0xffffffffu, hin.x, 1); hin.y += __shfl_xor_sync(0xffffffffu, hin.y, 1);
                    hin.x += __shfl_xor_sync(0xffffffffu, hin.x, 2); hin.y += __shfl_xor_sync(0xffffffffu, hin.y, 2);
                    w0[h] = cfma(pw32[h], hin, w0[h]);
                }
            }
            if (wg) mbar_wait(bar_out + 24);
            STAMPIF(lane == 0, 38 + 2 * wg);
            const uint32_t stg = sb + OFF_STG + prm.swapped * 8192 + w * 1024 + (lane & 7) * 128 + (((lane >> 3) ^ (lane & 7)) << 4);
            const uint32_t second = prm.swapped ? -8192 : 8192;
            const uint32_t keep = c == (g >> 1) ? 0xFFFEFFFEu : 0xFFFFFFFFu, tagw = ((t2 & 1) | ((t2 & 2) << 15)) & ~keep;
#pragma unroll
            for (int h = 0; h < 2; h++) {
                float (&acc)[64] = h ? accB : accA;
                uint32_t ra[16], ia[16];
                auto stage = [&](uint32_t (&r)[16], uint32_t base, int j) {
                    stsm4((base ^ ((j & 1) * 64)) + (j >> 1) * 4096, r[4 * j], r[4 * j + 1], r[4 * j + 2], r[4 * j + 3]);
                };
#pragma unroll
                for (int n = 0; n < 16; n++) {
                    const float2 y = cfma(a[h], w0[h], make_float2(acc[4 * n], acc[4 * n + 2]));
                    w0[h] = cfma(a[h], y, make_float2(acc[4 * n + 1], acc[4 * n + 3]));
                    ra[n] = pack_bf(y.x, w0[h].x);
                    ia[n] = pack_bf(y.y, w0[h].y);
                    if (!(n & 1)) { ra[n] = (ra[n] & keep) | tagw; ia[n] = (ia[n] & keep) | tagw; }
                    if (!h && (n & 3) == 3) {
                        if (n == 11) { asm volatile("" : "+r"(ra[n]), "+r"(ia[n])); gap(); release(bar_st + 32 * wg); }
                        stage(ra, stg, n >> 2); stage(ia, stg + second, n >> 2);
                        gap();
                    }
                    if (h && n == 3) { asm volatile("" : "+r"(ra[n]), "+r"(ia[n])); gap(); release(bar_st + 32 * wg + 8); }
                }
                if (h) {
                    STAMPIF(lane == 0, 39 + 2 * wg);
                    mbar_wait(bar_out + 32 * wg);
                    if (prm.swapped) {
#pragma unroll
                        for (int n = 0; n < 16; n++) { const uint32_t t = ra[n]; ra[n] = ia[n]; ia[n] = t; }
                    }
                    const uint32_t st0 = stg - prm.swapped * 8192;
#pragma unroll
                    for (int j = 0; j < 4; j++) stage(ra, st0, j);
                    mbar_wait(bar_xs);
                    row_setup();
                    release(bar_st + 32 * wg + 16);
                    mbar_wait(bar_out + 32 * wg + 8);
#pragma unroll
                    for (int j = 0; j < 4; j++) stage(ia, st0 + 8192, j);
                    release(bar_st + 32 * wg + 24);
                }
                STAMPIF(lane == 0, 42 + 2 * wg + h);
            }
        }

        const uint32_t xr = 2 * (g & 3) + (g >> 2), xa = sb + (wg ? OFF_STG : OFF_W) + (16 * w + xr) * 128 + (((c >> 1) ^ xr) << 4) + (c & 1) * 8;
        auto load_x = [&](int j0, int j1) {
#pragma unroll
            for (int j = j0; j < j1; j++)
#pragma unroll
                for (int r = 0; r < 2; r++) xv[j][r] = lds64((xa ^ (32 * (j & 3))) + (j >> 2) * ABYTES + r * 1024);
        };
        auto finish = [&](float (&acc)[64], int j, bool gaps) {
            const float d[4] = {bf_lo(dk[j].x), bf_hi(dk[j].x), bf_lo(dk[j].y), bf_hi(dk[j].y)};
#pragma unroll
            for (int r = 0; r < 2; r++) {
                const float xf[4] = {bf_lo(xv[j][r].x), bf_hi(xv[j][r].x), bf_lo(xv[j][r].y), bf_hi(xv[j][r].y)};
                const int o = 8 * j + 2 * r;
#pragma unroll
                for (int u = 0; u < 4; u++) {
                    float& v = acc[o + (u & 1) + 4 * (u >> 1)];
                    v = fmaf(gv[r], fmaf(xf[u], d[u], v), om[r] * xf[u]);
                }
                stg4_unless(op + r * 2 * D_ + 16 * j, acc[o], acc[o + 1], acc[o + 4], acc[o + 5], routed[r]);
                if (gaps) gap();
            }
        };
        auto finish_routed = [&](float (&acc)[64]) {
#pragma unroll
            for (int r = 0; r < 2; r++)
                if (routed[r]) {
#pragma unroll
                    for (int j = 0; j < 8; j++) red4(op + r * 2 * D_ + 16 * j, acc[8 * j + 2 * r], acc[8 * j + 2 * r + 1], acc[8 * j + 2 * r + 4], acc[8 * j + 2 * r + 5]);
                }
            __syncwarp();
        };
        const uint32_t xbuf = sb + w * 2048 + lane * 16;

        if (wg == 1) {
            float outB[64];
            const uint32_t tagw = (tag & 1) | ((tag & 2) << 15);
            mbar_wait(bar_fp);
            {
                const float4 o4 = lds128f(sb + OFF_XS + at * 16);
                const float o[4] = {o4.x, o4.y, o4.z, o4.w};
                float v[4];
#pragma unroll
                for (int u = 0; u < 4; u++) {
                    v[u] = rbf(facc[u] + o[u]);
                    if (!(cta & 1)) v[u] = __fdividef(v[u], 1.0f + __expf(-v[u]));
                }
                uint32_t w0 = pack_bf(v[0], v[1]), w1 = pack_bf(v[2], v[3]), cell[4];
                if (c == (g & 3)) { w0 = (w0 & 0xFFFEFFFEu) | tagw; w1 = (w1 & 0xFFFEFFFEu) | tagw; }
#pragma unroll
                for (int u = 0; u < 4; u++) {
                    const uint32_t s0 = __shfl_sync(0xffffffffu, w0, u, 4), s1 = __shfl_sync(0xffffffffu, w1, u, 4);
                    cell[u] = (c & 1) ? s1 : s0;
                }
                st_cell(g_hid + (cta & 1) * F_ + (cta >> 1) * 64 - 512 + w * 16 + g + 8 * c, cell[0], cell[1], cell[2], cell[3], has_gu && c < 2);
            }
            const uint32_t tpub = clk32();
            STAMPIF(lane == 0, 47);
            mbar_wait(bar_xb);
            load_x(0, 8);
            release(bar_xbfree);
            STAMPIF(lane == 0, 46);
            named_bar(2, 128);
            {
                uint32_t hv[4][4] = {}, hu[4][4] = {}, it = 0;
                sleep_until(tpub + HG0);
                while (true) {
                    uint32_t bad = 0;
#pragma unroll
                    for (int i = 0; i < 4; i++) {
                        const uint4* hp = g_hid + (cta >> 4) * 448 + (i < 3 ? i * 128 + at : 384 + (at & 63));
                        ld_cell(hv[i], hp); ld_cell(hu[i], hp + F_);
                    }
#pragma unroll
                    for (int i = 0; i < 4; i++)
                        bad |= (((c & 2) ? ((c & 1) ? hv[i][3] : hv[i][2]) : ((c & 1) ? hv[i][1] : hv[i][0])) ^ tagw) |
                               (((c & 2) ? ((c & 1) ? hu[i][3] : hu[i][2]) : ((c & 1) ? hu[i][1] : hu[i][0])) ^ tagw);
                    if (__all_sync(0xffffffffu, (bad & 0x00010001u) == 0)) break;
                    if (++it > SPIN_LIMIT) __trap();
                }
                STAMPIF(lane == 0, 48);
#pragma unroll
                for (int i = 0; i < 4; i++)
                    sts128(sb + OFF_XS + 16 * (i < 3 ? i * 128 + at : 384 + (at & 63)), mul_bf2(hv[i][0], hu[i][0]), mul_bf2(hv[i][1], hu[i][1]),
                           mul_bf2(hv[i][2], hu[i][2]), mul_bf2(hv[i][3], hu[i][3]));
                asm volatile("fence.proxy.async.shared::cta;" ::: "memory");
                __syncwarp();
                if (lane == 0) mbar_arrive(bar_hs);
                STAMPIF(lane == 0, 49);
            }
            uint4 pb[8];
            mbar_wait(bar_accb);
#pragma unroll
            for (int v = 0; v < 8; v++) {
                pb[v] = ldsm4(xbuf + sum_off(v));
                outB[4 * v] = __uint_as_float(pb[v].x); outB[4 * v + 1] = __uint_as_float(pb[v].y);
                outB[4 * v + 2] = __uint_as_float(pb[v].z); outB[4 * v + 3] = __uint_as_float(pb[v].w);
                outB[32 + 4 * v] = outB[33 + 4 * v] = outB[34 + 4 * v] = outB[35 + 4 * v] = 0.f;
            }
            pin64(outB);
            release(bar_fold);
            mbar_wait(bar_order2);
            static_for<NENT - FIN>([&](auto u) { run_small<1, FIN + u>(outB, [](int) {}); });
            if (lane == 0) mbar_arrive(bar_order3);
            mbar_wait(bar_accb + 8);
#pragma unroll
            for (int v = 0; v < 8; v++) pb[v] = ldsm4(xbuf + sum_off(8 + v));
            wgmma_wait<0>();
            pin64(outB);
            KSTAMP(2 * NENT - FIN);
            STAMPIF(at == 0, 50);
#pragma unroll
            for (int j = 0; j < 8; j++) {
                if (j >= 4) {
#pragma unroll
                    for (int v = 2 * j - 8; v < 2 * j - 6; v++) {
                        outB[32 + 4 * v] += __uint_as_float(pb[v].x); outB[33 + 4 * v] += __uint_as_float(pb[v].y);
                        outB[34 + 4 * v] += __uint_as_float(pb[v].z); outB[35 + 4 * v] += __uint_as_float(pb[v].w);
                    }
                }
                finish(outB, j, false);
            }
            finish_routed(outB);
            STAMPIF(lane == 0, 51);
        } else {
            float outA[64], outB[64], gacc[4];
            ring.slot = 32 % NST;
            ring.prev = bar_dummy;
            mbar_wait(bar_order1);
            run_entries<1, 2>(ring, 32, GU0 + 32, outA, outB, gacc, true, true);
            run_entries<1, 0>(ring, GU0 + 32, GU0 + 33, outA, outB, gacc, false, false, [&]() {
                pin4(gacc);
                sts128(sb + OFF_XS + at * 16, __float_as_uint(gacc[0]), __float_as_uint(gacc[1]), __float_as_uint(gacc[2]), __float_as_uint(gacc[3]));
                __syncwarp();
                if (lane == 0) mbar_arrive(bar_fp);
            });
            mbar_wait(bar_xa);
            run_entries<1, 0>(ring, GU0 + 33, GU0 + 34, outA, outB, gacc, false, false, [&]() { load_x(0, 2); });
            load_x(2, 4);
            run_entries<1, 0>(ring, GU0 + 34, GU0 + 35, outA, outB, gacc, false, false, [&]() { load_x(4, 6); });
            load_x(6, 8);
            run_entries<1, 0>(ring, GU0 + 35, GU0 + 36, outA, outB, gacc, false, false, [&]() { release(bar_xafree); });
            run_entries<1, 0>(ring, GU0 + 36, FIN, outA, outB, gacc);
            static_for<NENT - FIN>([&](auto u) {
                if (u >= 3) mbar_wait(empty + 8 * (FIN + u - 3));
                mbar_wait(full + 8 * (FIN + u));
                run_small<0, FIN + u>(outA, [&](int kk) {
                    const int v = 4 * (u == 1 ? 0 : u - 2) + kk;
                    if (u == 1 || u >= 3)
                        stsm4(xbuf + sum_off(v), __float_as_uint(outB[4 * v]), __float_as_uint(outB[4 * v + 1]), __float_as_uint(outB[4 * v + 2]), __float_as_uint(outB[4 * v + 3]));
                });
                if (u == 5 && lane == 0) mbar_arrive(bar_order2);
                wgmma_wait<1>();
                if (lane == 0) mbar_arrive(empty + 8 * (FIN + u - 1));
                if (u == 0) pin64(outB);
                if (u == 3) release(bar_accb);
            });
            release(bar_accb + 8);
            STAMPIF(lane == 0, 55);
            wgmma_wait<0>();
            pin64(outA);
            if (lane == 0) mbar_arrive(empty + 8 * (NENT - 1));
            STAMPIF(at == 0, 53);
#pragma unroll
            for (int j = 0; j < 8; j++) {
                finish(outA, j, true);
            }
            finish_routed(outA);
            STAMPIF(lane == 0, 54);
            const uint2 sk = lds64(sb + OFF_SEL + 8 * c), fk = lds64(sb + OFF_FAC + 8 * c);
            float* y0 = prm.out + (~sk.x & 2047u) * D_ + (cta & 15) * 64 + w * 16 + g;
            float* y1 = prm.out + (~sk.y & 2047u) * D_ + (cta & 15) * 64 + w * 16 + g;
            float yacc[4];
            const uint64_t dw = make_desc(sb), dh = (uint64_t)(((sb + OFF_XS) & 0x3FFFF) >> 4) | ((uint64_t)8 << 16) | ((uint64_t)8 << 32);
            mbar_wait(bar_hs);
            mbar_wait(bar_zero);
            mbar_wait(bar_dn);
            mbar_wait(bar_order3);
            STAMPIF(at == 0, 2);
            wgmma_fence();
#pragma unroll
            for (int n = 0; n < 28; n++) wgmma_n8<1, 1>(yacc, dw + (dn_off(n >> 2) >> 4) + (n & 3) * 128, dh + n * 16, n > 0);
            wgmma_commit();
            wgmma_wait<0>();
            pin4(yacc);
            atomicAdd(y0, yacc[0] * __uint_as_float(fk.x)); atomicAdd(y1, yacc[1] * __uint_as_float(fk.y));
            atomicAdd(y0 + 8, yacc[2] * __uint_as_float(fk.x)); atomicAdd(y1 + 8, yacc[3] * __uint_as_float(fk.y));
            STAMPIF(lane == 0, 3);
        }
    }
}

typedef CUresult (*EncodeFn)(CUtensorMap*, CUtensorMapDataType, cuuint32_t, void*, const cuuint64_t*, const cuuint64_t*, const cuuint32_t*,
                             const cuuint32_t*, CUtensorMapInterleave, CUtensorMapSwizzle, CUtensorMapL2promotion, CUtensorMapFloatOOBfill);

bool encode(EncodeFn fn, CUtensorMap* m, const void* ptr, int rank, const cuuint64_t* dims, const cuuint64_t* strides, const cuuint32_t* box,
            CUtensorMapSwizzle sw = CU_TENSOR_MAP_SWIZZLE_128B, CUtensorMapL2promotion promo = CU_TENSOR_MAP_L2_PROMOTION_NONE) {
    const cuuint32_t es[5] = {1, 1, 1, 1, 1};
    return fn(m, CU_TENSOR_MAP_DATA_TYPE_BFLOAT16, rank, const_cast<void*>(ptr), dims, strides, box, es, CU_TENSOR_MAP_INTERLEAVE_NONE,
              sw, promo, CU_TENSOR_MAP_FLOAT_OOB_FILL_NONE) == CUDA_SUCCESS;
}

}

extern "C" void kernel_launch(void* const* d_in, const int* in_sizes, int n_in, void* d_out, int out_size) {
    (void)in_sizes; (void)n_in; (void)out_size;
    Params prm;
    prm.x = (const __nv_bfloat16*)d_in[0];
    prm.lam_re = (const __nv_bfloat16*)d_in[1];
    prm.lam_im = (const __nv_bfloat16*)d_in[2];
    prm.b_re = (const __nv_bfloat16*)d_in[3];
    prm.b_im = (const __nv_bfloat16*)d_in[4];
    prm.c_re = (const __nv_bfloat16*)d_in[5];
    prm.c_im = (const __nv_bfloat16*)d_in[6];
    prm.log_dt = (const __nv_bfloat16*)d_in[7];
    prm.dskip = (const __nv_bfloat16*)d_in[8];
    prm.w_r = (const __nv_bfloat16*)d_in[10];
    prm.gate_w = (const __nv_bfloat16*)d_in[14];
    prm.out = (float*)d_out;
    int dev = 0, sms = 0;
    cudaGetDevice(&dev);
    cudaDeviceGetAttribute(&sms, cudaDevAttrMultiProcessorCount, dev);
    prm.by_smid = sms == NGRID;
    prm.swapped = prm.b_im < prm.b_re;

    void* fnp = nullptr;
    cudaDriverEntryPointQueryResult qr;
    cudaGetDriverEntryPoint("cuTensorMapEncodeTiled", &fnp, cudaEnableDefault, &qr);
    EncodeFn fn = (EncodeFn)fnp;
    cudaFuncSetAttribute(fused_kernel, cudaFuncAttributeMaxDynamicSharedMemorySize, SMEM_BYTES);

    CUtensorMap mX, mB, mCre, mCim, mWg, mWu, mWd, mXr, mXe;
    const cuuint64_t row = 2048;
    {
        const cuuint64_t dims[4] = {1024, 2, 4, 976}, st[3] = {row, 32 * row, 2 * row};
        const cuuint32_t box[4] = {64, 2, 4, 16};
        encode(fn, &mX, prm.x, 4, dims, st, box, CU_TENSOR_MAP_SWIZZLE_128B, PROMO);
    }
    {
        const char *lo = (const char*)(prm.swapped ? prm.b_im : prm.b_re), *hi = (const char*)(prm.swapped ? prm.b_re : prm.b_im);
        const cuuint64_t dims[5] = {1024, 8, 2, 96, 2}, st[4] = {row, (cuuint64_t)(hi - lo), 8 * row, 256 * row};
        const cuuint32_t box[5] = {64, 8, 2, 4, 2};
        encode(fn, &mB, lo, 5, dims, st, box, CU_TENSOR_MAP_SWIZZLE_128B, PROMO);
    }
    {
        const cuuint64_t dims[5] = {1024, 2, 4, 2, 64}, st[4] = {row, 4 * row, 2 * row, 16 * row};
        const cuuint32_t box[5] = {64, 2, 4, 2, 8};
        encode(fn, &mCre, prm.c_re, 5, dims, st, box);
        encode(fn, &mCim, prm.c_im, 5, dims, st, box);
    }
    {
        const cuuint64_t dims[2] = {F_, D_}, st[1] = {F_ * 2}, dimsd[2] = {D_, F_}, std_[1] = {row};
        const cuuint32_t box[2] = {64, 32}, boxd[2] = {64, 64};
        encode(fn, &mWg, d_in[11], 2, dims, st, box, CU_TENSOR_MAP_SWIZZLE_128B, CU_TENSOR_MAP_L2_PROMOTION_NONE);
        encode(fn, &mWu, d_in[12], 2, dims, st, box, CU_TENSOR_MAP_SWIZZLE_128B, CU_TENSOR_MAP_L2_PROMOTION_NONE);
        encode(fn, &mWd, d_in[13], 2, dimsd, std_, boxd, CU_TENSOR_MAP_SWIZZLE_128B, CU_TENSOR_MAP_L2_PROMOTION_NONE);
    }
    {
        const cuuint64_t dims[3] = {D_ - 192, S_, 4}, st[2] = {row, 128};
        const cuuint32_t box[3] = {64, 16, 4};
        encode(fn, &mXr, prm.x, 3, dims, st, box, CU_TENSOR_MAP_SWIZZLE_128B, CU_TENSOR_MAP_L2_PROMOTION_NONE);
    }
    {
        const cuuint64_t dims[5] = {D_, 2, 2, 2, 976}, st[4] = {64 * row, row, 32 * row, 2 * row};
        const cuuint32_t box[5] = {64, 2, 2, 2, 8};
        encode(fn, &mXe, prm.x, 5, dims, st, box);
    }
    fused_kernel<<<NGRID, 384, SMEM_BYTES, cudaStreamPerThread>>>(prm, mX, mB, mCre, mCim, mWg, mWu, mWd, mXr, mXe);
}
```

```cpp
#include <cuda_runtime.h>
#include <cuda_bf16.h>
#include <cuda.h>
#include <stdint.h>

namespace {

constexpr int S_ = 2048, D_ = 1024, F_ = 3584;
constexpr int NCTA = 128, NGRID = 132;
constexpr int NENT = 64, FIN = 58, XE = 60;
constexpr int NST = 5;
constexpr int RE0 = 4;
constexpr int GU0 = 20;
constexpr uint32_t SLOT = 32768, ABYTES = 8192, WBYTES = 4096;
constexpr uint32_t OFF_XS = NST * SLOT;
constexpr uint32_t OFF_LIST = OFF_XS + 8192;
constexpr uint32_t OFF_W = OFF_XS + 16384;
constexpr uint32_t OFF_STG = OFF_W + 32768;
__host__ __device__ constexpr uint32_t slot_off(int i) { return i < XE ? (i % NST) * SLOT : i == XE ? OFF_W : ((i - 1) % NST) * SLOT; }
__host__ __device__ constexpr uint32_t dn_off(int u) { return u == 0 ? OFF_XS + ABYTES : u < 3 ? OFF_STG + (u - 1) * ABYTES : slot_off(FIN - 2 + u); }
constexpr uint32_t OFF_CONST = OFF_STG;
constexpr uint32_t OFF_RED = OFF_STG + 4096;
constexpr uint32_t OFF_FULL = OFF_STG + 16384;
constexpr uint32_t OFF_EMPTY = OFF_FULL + 120 * 8;
constexpr uint32_t OFF_G = OFF_EMPTY + 88 * 8;
constexpr uint32_t OFF_DK = OFF_G + 256;
constexpr uint32_t OFF_KEYS = OFF_DK + 256;
constexpr uint32_t OFF_SEL = OFF_KEYS + 32;
constexpr uint32_t OFF_FAC = OFF_SEL + 32;
constexpr uint32_t OFF_EPOCH = OFF_FAC + 32;
constexpr uint32_t OFF_PROF = OFF_EPOCH + 16;
constexpr uint32_t SMEM_BYTES = OFF_PROF + 768;
static_assert(SMEM_BYTES <= 232448, "smem");

constexpr uint32_t sb = 1024;
constexpr uint32_t SPIN_LIMIT = 1u << 18;

struct Scratch {
    unsigned int cnt[2 * 32];
    unsigned long long rpack[S_ / 2];
    unsigned long long gpack[S_ / 2];
    uint4 time[NCTA * 2];
    float4 carry[16 * 512];
    uint4 hid[2 * F_];
    uint4 h[8 * 4 * 256 * 64];
};
__device__ __align__(128) Scratch g_scratch;
#define STAMPW(cond, w) do {} while (0)
#define LATE(i, tt) do {} while (0)
#define LANDED(i) do {} while (0)
#define GSTAMP(cond, w) do {} while (0)
#define STAMPIF(cond, i) STAMPW(cond, 72 + (i))
#define STAMP(i) STAMPW(1, 72 + (i))
#define KSTAMP(i) STAMPW((threadIdx.x & 127) == 0, i)

struct Params {
    const __nv_bfloat16 *x, *b_re, *b_im;
    int by_smid;
    int swapped;
    const __nv_bfloat16 *lam_re, *lam_im, *c_re, *c_im, *log_dt, *dskip, *w_r, *gate_w;
    float* out;
    Scratch* s;
};

__device__ __forceinline__ uint32_t smem_u32(const void* p) { return (uint32_t)__cvta_generic_to_shared(p); }
__device__ __forceinline__ void mbar_init(uint32_t bar, uint32_t cnt) { asm volatile("mbarrier.init.shared::cta.b64 [%0], %1;" ::"r"(bar), "r"(cnt) : "memory"); }
__device__ __forceinline__ void mbar_expect_tx(uint32_t bar, uint32_t bytes) { asm volatile("mbarrier.arrive.expect_tx.shared::cta.b64 _, [%0], %1;" ::"r"(bar), "r"(bytes) : "memory"); }
__device__ __forceinline__ void mbar_arrive(uint32_t bar) { asm volatile("mbarrier.arrive.shared::cta.b64 _, [%0];" ::"r"(bar) : "memory"); }
__device__ __forceinline__ void mbar_wait(uint32_t bar, uint32_t parity = 0) {
    asm volatile("{ .reg .pred p; .reg .u32 n;\n"
                 "mbarrier.try_wait.parity.shared::cta.b64 p, [%0], %1;\n"
                 "@p bra.uni DONE;\n"
                 "mov.u32 n, 0;\n"
                 "AGAIN: mbarrier.try_wait.parity.shared::cta.b64 p, [%0], %1;\n"
                 "@p bra.uni DONE;\n"
                 "add.u32 n, n, 1;\n"
                 "setp.lt.u32 p, n, %2;\n"
                 "@p bra.uni AGAIN;\n"
                 "trap;\n"
                 "DONE: }" ::"r"(bar), "r"(parity), "n"(SPIN_LIMIT) : "memory");
}
__device__ __forceinline__ bool elect_one() {
    uint32_t pred;
    asm volatile("{ .reg .pred P; elect.sync _|P, 0xffffffff; selp.b32 %0, 1, 0, P; }" : "=r"(pred));
    return pred;
}
__device__ __forceinline__ void named_bar(int id, int n) { asm volatile("bar.sync %0, %1;" ::"r"(id), "r"(n) : "memory"); }

#define ONE "{ .reg .pred e; elect.sync _|e, 0xffffffff;\n@e "
template <int N> __device__ __forceinline__ void mbar_init_n(uint32_t bar, uint32_t cnt) {
    if (elect_one()) {
#pragma unroll
        for (int i = 0; i < N; i++) mbar_init(bar + 8 * i, cnt);
        asm volatile("fence.mbarrier_init.release.cluster;" ::: "memory");
    }
    __syncwarp();
}
__device__ __forceinline__ void bulk_load(uint32_t dst, const void* src, uint32_t bytes, uint32_t bar) {
    asm volatile(ONE "cp.async.bulk.shared::cluster.global.mbarrier::complete_tx::bytes [%0], [%1], %2, [%3]; }" ::"r"(dst), "l"(src), "r"(bytes), "r"(bar) : "memory");
}
__device__ __forceinline__ void sts128(uint32_t a, uint32_t x, uint32_t y, uint32_t z, uint32_t w) {
    asm volatile("st.shared.v4.u32 [%0], {%1,%2,%3,%4};" ::"r"(a), "r"(x), "r"(y), "r"(z), "r"(w) : "memory");
}
__device__ __forceinline__ uint2 lds64(uint32_t a) {
    uint2 v;
    asm volatile("ld.shared.v2.u32 {%0,%1}, [%2];" : "=r"(v.x), "=r"(v.y) : "r"(a) : "memory");
    return v;
}
__device__ __forceinline__ uint32_t clk32() { uint32_t c; asm volatile("mov.u32 %0, %%clock;" : "=r"(c)); return c; }
__device__ __forceinline__ void gap() { asm volatile("pmevent 1;" ::: "memory"); }
__device__ __forceinline__ void pace_until(uint32_t t) { while ((int)(clk32() - t) < 0) {} }
#define SLEEP_MARGIN 200
__device__ __forceinline__ void sleep_until(uint32_t t) {
    while ((int)(clk32() + SLEEP_MARGIN - t) < 0) __nanosleep(40);
    pace_until(t);
}
__device__ __forceinline__ void tma2(uint32_t dst, const CUtensorMap* m, int c0, int c1, uint32_t bar, uint64_t pol) {
    asm volatile(ONE "cp.async.bulk.tensor.2d.shared::cluster.global.mbarrier::complete_tx::bytes.L2::cache_hint [%0], [%1, {%3, %4}], [%2], %5; }"
                 ::"r"(dst), "l"(m), "r"(bar), "r"(c0), "r"(c1), "l"(pol) : "memory");
}
__device__ __forceinline__ void tma3(uint32_t dst, const CUtensorMap* m, int c0, int c1, uint32_t bar) {
    asm volatile(ONE "cp.async.bulk.tensor.3d.shared::cluster.global.mbarrier::complete_tx::bytes [%0], [%1, {%3, %4, %5}], [%2]; }"
                 ::"r"(dst), "l"(m), "r"(bar), "r"(c0), "r"(c1), "r"(0) : "memory");
}
__device__ __forceinline__ void tma4(uint32_t dst, const CUtensorMap* m, int c0, int c3, uint32_t bar) {
    asm volatile(ONE "cp.async.bulk.tensor.4d.shared::cluster.global.mbarrier::complete_tx::bytes [%0], [%1, {%3, %5, %5, %4}], [%2]; }"
                 ::"r"(dst), "l"(m), "r"(bar), "r"(c0), "r"(c3), "r"(0) : "memory");
}
__device__ __forceinline__ void tma5(uint32_t dst, const CUtensorMap* m, int c0, int c4, uint32_t bar) {
    asm volatile(ONE "cp.async.bulk.tensor.5d.shared::cluster.global.mbarrier::complete_tx::bytes [%0], [%1, {%3, %5, %5, %5, %4}], [%2]; }"
                 ::"r"(dst), "l"(m), "r"(bar), "r"(c0), "r"(c4), "r"(0) : "memory");
}
__device__ __forceinline__ void tma5b(uint32_t dst, const CUtensorMap* m, int c0, int c3, uint32_t bar) {
    asm volatile(ONE "cp.async.bulk.tensor.5d.shared::cluster.global.mbarrier::complete_tx::bytes [%0], [%1, {%3, %5, %5, %4, %5}], [%2]; }"
                 ::"r"(dst), "l"(m), "r"(bar), "r"(c0), "r"(c3), "r"(0) : "memory");
}
__device__ __forceinline__ void prefetch_l2(const void* p) {
    asm volatile("cp.async.ca.shared.global.L2::256B [%0], [%1], 4;" ::"r"(sb + OFF_EPOCH + 12), "l"(p) : "memory");
}

__device__ __forceinline__ uint32_t lds32(uint32_t a) {
    uint32_t v;
    asm volatile("ld.volatile.shared.u32 %0, [%1];" : "=r"(v) : "r"(a) : "memory");
    return v;
}
__device__ __forceinline__ uint32_t uni(uint32_t v) { return __shfl_sync(0xffffffffu, v, 0); }   __device__ __forceinline__ uint32_t ld_acquire(const unsigned int* p) {
    uint32_t v;
    asm volatile("ld.acquire.gpu.global.u32 %0, [%1];" : "=r"(v) : "l"(p) : "memory");
    return v;
}
__device__ __forceinline__ void red_release(unsigned int* p) { asm volatile("red.release.gpu.global.add.u32 [%0], 1;" ::"l"(p) : "memory"); }
__device__ __forceinline__ void wait_count(const unsigned int* p, uint32_t target) {
#pragma unroll 1
    for (uint32_t it = 0; it < SPIN_LIMIT; ++it)
        if ((int)(ld_acquire(p) - target) >= 0) return;
    __trap();
}
__device__ __forceinline__ void wait_count_slow(const unsigned int* p, uint32_t target) {
#pragma unroll 1
    for (uint32_t it = 0; it < SPIN_LIMIT; ++it) {
        if ((int)(ld_acquire(p) - target) >= 0) return;
        __nanosleep(200);
    }
    __trap();
}
__device__ __forceinline__ unsigned long long ld_relaxed1(const void* p) {
    unsigned long long v;
    asm volatile("ld.relaxed.gpu.global.b64 %0, [%1];" : "=l"(v) : "l"(p) : "memory");
    return v;
}
__device__ __forceinline__ ulonglong2 ld_relaxed2(const void* p) {
    ulonglong2 v;
    asm volatile("ld.relaxed.gpu.global.v2.b64 {%0, %1}, [%2];" : "=l"(v.x), "=l"(v.y) : "l"(p) : "memory");
    return v;
}
__device__ __forceinline__ void ld_cell(uint32_t (&v)[4], const void* p, bool on = true) {
    asm volatile("{ .reg .pred p; .reg .b64 l, h; .reg .b128 t; setp.ne.u32 p, %5, 0; mov.b64 l, {%0, %1}; mov.b64 h, {%2, %3}; mov.b128 t, {l, h};\n"
                 "@p ld.relaxed.gpu.global.b128 t, [%4]; mov.b128 {l, h}, t; mov.b64 {%0, %1}, l; mov.b64 {%2, %3}, h; }"
                 : "+r"(v[0]), "+r"(v[1]), "+r"(v[2]), "+r"(v[3]) : "l"(p), "r"((uint32_t)on) : "memory");
}
__device__ __forceinline__ void st_cell(void* p, uint32_t a, uint32_t b, uint32_t c, uint32_t d, bool on) {
    asm volatile("{ .reg .pred p; .reg .b64 l, h; .reg .b128 t; setp.ne.u32 p, %5, 0; mov.b64 l, {%1, %2}; mov.b64 h, {%3, %4}; mov.b128 t, {l, h};\n"
                 "@p st.relaxed.gpu.global.b128 [%0], t; }" ::"l"(p), "r"(a), "r"(b), "r"(c), "r"(d), "r"((uint32_t)on) : "memory");
}

__device__ __forceinline__ uint64_t make_desc(uint32_t addr, uint32_t sbo = 1024) {
    return (uint64_t)((addr & 0x3FFFF) >> 4) | ((uint64_t)1 << 16) | ((uint64_t)(sbo >> 4) << 32) | ((uint64_t)1 << 62);
}
__device__ __forceinline__ void wgmma_fence() { asm volatile("wgmma.fence.sync.aligned;" ::: "memory"); }
__device__ __forceinline__ void wgmma_commit() { asm volatile("wgmma.commit_group.sync.aligned;" ::: "memory"); }
template <int N> __device__ __forceinline__ void wgmma_wait() { asm volatile("wgmma.wait_group.sync.aligned %0;" ::"n"(N) : "memory"); }

#define R8(d, i) "+f"(d[i]), "+f"(d[i + 1]), "+f"(d[i + 2]), "+f"(d[i + 3]), "+f"(d[i + 4]), "+f"(d[i + 5]), "+f"(d[i + 6]), "+f"(d[i + 7])
#define R64(d) R8(d, 0), R8(d, 8), R8(d, 16), R8(d, 24), R8(d, 32), R8(d, 40), R8(d, 48), R8(d, 56)
template <int TA>
__device__ __forceinline__ void wgmma_n128(float (&d)[64], uint64_t da, uint64_t db, int scale_d = 1) {
    asm volatile("{ .reg .pred p; setp.ne.b32 p, %66, 0;\n"
                 "wgmma.mma_async.sync.aligned.m64n128k16.f32.bf16.bf16 "
                 "{%0,%1,%2,%3,%4,%5,%6,%7,%8,%9,%10,%11,%12,%13,%14,%15,%16,%17,%18,%19,%20,%21,%22,%23,%24,%25,%26,%27,%28,%29,%30,%31,"
                 "%32,%33,%34,%35,%36,%37,%38,%39,%40,%41,%42,%43,%44,%45,%46,%47,%48,%49,%50,%51,%52,%53,%54,%55,%56,%57,%58,%59,%60,%61,%62,%63}, "
                 "%64, %65, p, 1, 1, %67, 0; }"
                 : R64(d)
                 : "l"(da), "l"(db), "r"(scale_d), "n"(TA));
}
__device__ __forceinline__ void pin4(float (&d)[4]) { asm volatile("" : "+f"(d[0]), "+f"(d[1]), "+f"(d[2]), "+f"(d[3])::"memory"); }
__device__ __forceinline__ void pin64(float (&d)[64]) { asm volatile("" : R64(d)::"memory"); }

template <int TA, int TB = 0>
__device__ __forceinline__ void wgmma_n8(float (&d)[4], uint64_t da, uint64_t db, int scale_d = 1) {
    asm volatile("{ .reg .pred p; setp.ne.b32 p, %7, 0;\n"
                 "wgmma.mma_async.sync.aligned.m64n8k16.f32.bf16.bf16 {%0,%1,%2,%3}, %4, %5, p, 1, 1, %6, %8; }"
                 : "+f"(d[0]), "+f"(d[1]), "+f"(d[2]), "+f"(d[3])
                 : "l"(da), "l"(db), "n"(TA), "r"(scale_d), "n"(TB));
}

__device__ __forceinline__ float bf_lo(uint32_t u) { return __uint_as_float(u << 16); }
__device__ __forceinline__ float bf_hi(uint32_t u) { return __uint_as_float(u & 0xFFFF0000u); }
__device__ __forceinline__ float rbf(float v) { return __bfloat162float(__float2bfloat16_rn(v)); }
__device__ __forceinline__ uint32_t pack_bf(float lo, float hi) {
    uint32_t r;
    asm("cvt.rn.bf16x2.f32 %0, %1, %2;" : "=r"(r) : "f"(hi), "f"(lo));
    return r;
}
__device__ __forceinline__ uint32_t mul_bf2(uint32_t a, uint32_t b) {
    __nv_bfloat162 r = __hmul2(*reinterpret_cast<__nv_bfloat162*>(&a), *reinterpret_cast<__nv_bfloat162*>(&b));
    return *reinterpret_cast<uint32_t*>(&r);
}
__device__ __forceinline__ uint32_t fma_bf2(uint32_t a, uint32_t b, uint32_t c) {
    uint32_t r;
    asm("fma.rn.bf16x2 %0, %1, %2, %3;" : "=r"(r) : "r"(a), "r"(b), "r"(c));
    return r;
}
__device__ __forceinline__ float2 cmul(float2 a, float2 b) { return make_float2(a.x * b.x - a.y * b.y, a.x * b.y + a.y * b.x); }
__device__ __forceinline__ float2 cfma(float2 a, float2 b, float2 c) {
    return make_float2(fmaf(a.x, b.x, fmaf(-a.y, b.y, c.x)), fmaf(a.x, b.y, fmaf(a.y, b.x, c.y)));
}
__device__ __forceinline__ float sigmoidf_(float v) { return __fdividef(1.0f, 1.0f + expf(-v)); }

__device__ __forceinline__ void bulk_prefetch(const void* src, uint32_t bytes) {
    asm volatile(ONE "cp.async.bulk.prefetch.L2.global [%0], %1; }" ::"l"(src), "r"(bytes) : "memory");
}
__device__ __forceinline__ void bulk_store(void* dst, uint32_t src, uint32_t bytes) {
    asm volatile(ONE "cp.async.bulk.global.shared::cta.bulk_group [%0], [%1], %2; }" ::"l"(dst), "r"(src), "r"(bytes) : "memory");
}
__device__ __forceinline__ float4 lds128f(uint32_t a) {
    float4 v;
    asm volatile("ld.shared.v4.f32 {%0,%1,%2,%3}, [%4];" : "=f"(v.x), "=f"(v.y), "=f"(v.z), "=f"(v.w) : "r"(a) : "memory");
    return v;
}
__device__ __forceinline__ void stsm4(uint32_t a, uint32_t x, uint32_t y, uint32_t z, uint32_t w) {
    asm volatile("stmatrix.sync.aligned.m8n8.x4.shared.b16 [%0], {%1,%2,%3,%4};" ::"r"(a), "r"(x), "r"(y), "r"(z), "r"(w) : "memory");
}
__device__ __forceinline__ uint4 ldsm4(uint32_t a) {
    uint4 v;
    asm volatile("ldmatrix.sync.aligned.m8n8.x4.shared.b16 {%0,%1,%2,%3}, [%4];" : "=r"(v.x), "=r"(v.y), "=r"(v.z), "=r"(v.w) : "r"(a) : "memory");
    return v;
}
__device__ __forceinline__ void stg4_unless(float* p, float a, float b, float c, float d, uint32_t skip) {
    asm volatile("{ .reg .pred p; setp.eq.u32 p, %5, 0; @p st.global.v4.f32 [%0], {%1,%2,%3,%4}; }" ::"l"(p), "f"(a), "f"(b), "f"(c), "f"(d), "r"(skip) : "memory");
}
__device__ __forceinline__ void red4(float* p, float a, float b, float c, float d) {
    asm volatile("red.global.add.v4.f32 [%0], {%1,%2,%3,%4};" ::"l"(p), "f"(a), "f"(b), "f"(c), "f"(d) : "memory");
}

#define TT0 3100
#define PER 520
#define PCUT 40
#define PFIN 340
#define PF0 1300
#define PFX_PACE 400
#define PFB_PACE 900
#define PFV 6
#define PFT 0
#define PF1 700
#define T2 400
#define P2 550
#define G0 800
#define R0 2300
#define R_PACE 350
#define W_SHIFT 250
#define PROMO CU_TENSOR_MAP_L2_PROMOTION_L2_256B
#define POLL_S 20
#define ST_TOL 100
#define ST_SHIFT 300
#define CLK_NS 420
#define MARGIN 100
#define BP1 7
#define NDUMP 8
#define DWAIT 1
#define HG0 900
constexpr uint32_t duration(int i) { return PER + (i >= RE0 && i < RE0 + 4 ? 72 : 0) + (i >= GU0 && i < GU0 + 32 ? 36 : 0); }
constexpr uint32_t cmax(uint32_t a, uint32_t b) { return a > b ? a : b; }
constexpr uint32_t issue_time(int i) {
    return i <= NST ? TT0 : i < XE ? issue_time(i - 1) + duration(i - NST) - (i >= FIN - 1 ? PCUT : 0) : issue_time(XE - 1) + cmax((i - XE + 1) * PFIN, (i - XE) * 512);
}
template <int I> struct Sched { static constexpr uint32_t t = issue_time(I); };
template <int LO, int HI, class F>
__device__ __forceinline__ void for_entries(uint32_t base, F body) {
    constexpr uint32_t per = Sched<LO + 1>::t - Sched<LO>::t;
    static_assert(Sched<HI - 1>::t - Sched<LO>::t == (HI - 1 - LO) * per, "period");
    uint32_t tt = base + Sched<LO>::t;
#pragma unroll 1
    for (int i = LO; i < HI; i++) {
        body(i, tt);
        tt += per;
    }
}

struct Ring { uint32_t prev; int slot; };
struct NoHook { __device__ void operator()() const {} };
template <int TA, int SM, class H = NoHook>
__device__ __forceinline__ void run_entries(Ring& r, int lo, int hi, float (&accA)[64], float (&accB)[64], float (&small)[4],
                                            bool fresh = false, bool sfresh = false, H released = H()) {
    const uint64_t d0 = make_desc(sb);
    const bool leader = (threadIdx.x & 31) == 0;
#pragma unroll 1
    for (int i = lo; i < hi; i++) {
        const uint32_t bar = sb + OFF_FULL + 8 * i;
        const uint64_t da = d0 + (uint64_t)(r.slot * (SLOT >> 4));
        const int n = i - (SM == 1 ? RE0 : GU0);
        const uint64_t dw = d0 + (uint64_t)((OFF_W >> 4) + (SM == 1 ? n * 512 : (n & 7) * 256));
        const uint64_t dt8 = d0 + (uint64_t)((OFF_XS >> 4) + (SM == 1 ? n * 64 : (n >> 1) * 64 + (n & 1) * 4));
        r.slot = r.slot == NST - 1 ? 0 : r.slot + 1;
        mbar_wait(bar);
        KSTAMP(i);
        wgmma_fence();
#pragma unroll
        for (int kk = 0; kk < 4; kk++) {
            wgmma_n128<TA>(accA, da + kk * (TA ? 128 : 2), da + 1024 + kk * 2, kk > 0 || !fresh);
            if (SM == 1) wgmma_n8<0>(small, dw + kk * 2, dt8 + kk * 2, kk > 0 || !sfresh);
            if (SM == 2 && (kk & 1)) wgmma_n8<1>(small, dw + (kk >> 1) * 128, dt8 + (kk >> 1) * 2, kk > 1 || !sfresh);
            wgmma_n128<TA>(accB, da + 512 + kk * (TA ? 128 : 2), da + 1024 + kk * 2, kk > 0 || !fresh);
            if (kk == 1) {
                wgmma_commit();
                wgmma_wait<1>();
                if (leader) mbar_arrive(r.prev);
                released();
            }
        }
        wgmma_commit();
        r.prev = bar + (OFF_EMPTY - OFF_FULL);
        fresh = sfresh = false;
    }
}
template <int HALF, int I>
__device__ __forceinline__ void run_small(float (&acc)[64]) {
    const uint64_t da = make_desc(sb) + (slot_off(I) >> 4);
    KSTAMP(I + HALF * (NENT - FIN));
    wgmma_fence();
#pragma unroll
    for (int kk = 0; kk < 4; kk++) wgmma_n128<1>(acc, da + HALF * 512 + kk * 128, da + 1024 + kk * 2, kk > 0 || !(HALF && I == FIN));
    wgmma_commit();
}
template <int V> struct Int { __host__ __device__ constexpr operator int() const { return V; } };
template <int N, class F> __device__ __forceinline__ void static_for(F f) {
    if constexpr (N > 0) { static_for<N - 1>(f); f(Int<N - 1>()); }
}

__global__ void __launch_bounds__(384, 1)
fused_kernel(const __grid_constant__ Params prm, const __grid_constant__ CUtensorMap mX, const __grid_constant__ CUtensorMap mB, const __grid_constant__ CUtensorMap mCre,
             const __grid_constant__ CUtensorMap mCim, const __grid_constant__ CUtensorMap mWg, const __grid_constant__ CUtensorMap mWu,
             const __grid_constant__ CUtensorMap mWd, const __grid_constant__ CUtensorMap mXr, const __grid_constant__ CUtensorMap mXe) {
    extern __shared__ __align__(1024) uint8_t smem[];
    const uint32_t cstart = clk32();
    const int tid = threadIdx.x, lane = tid & 31;
    uint32_t smid;
    asm volatile("mov.u32 %0, %%smid;" : "=r"(smid));
    {
        const uint32_t b = blockIdx.x & 127, r = tid - PFT, o = (r >> 1) * 2048 + (r & 1) * 128;
#define PFS "@q prefetch.global.L2 [%1]; @p prefetch.global.L2 [%0]; @q prefetch.global.L2 [%2];"
        asm volatile("{ .reg .pred p, q; setp.lt.u32 p, %3, 32; setp.lt.u32 q, %3, 8;\n" PFS " }"
                     ::"l"((const char*)prm.x + (b * 32768 + o)), "l"((const char*)prm.b_re + (b * 8192 + o)), "l"((const char*)prm.b_im + (b * 8192 + o)), "r"(r),
                     "r"(sb + OFF_EPOCH + 12) : "memory");
        gap();
        STAMPIF(tid == PFT, 33);
    }
    const int warp = __shfl_sync(0xffffffffu, tid >> 5, 0);
    int cta;
    asm("{ .reg .pred p; .reg .u32 s, a, b, u, q;\n"
                 "mov.u32 s, %3;\n"
                 "and.b32 a, s, 14; shl.b32 a, a, 2; shr.u32 b, s, 4; add.u32 a, a, b;\n"
                 "sub.u32 u, s, 64; shr.u32 u, u, 1; mul.lo.u32 q, u, 37; shr.u32 q, q, 8; shl.b32 u, u, 3; mad.lo.u32 u, q, -55, u; add.u32 u, u, 12;\n"
                 "setp.lt.u32 p, s, 64; selp.u32 a, a, u, p; and.b32 b, s, 1; mad.lo.u32 a, a, 2, b;\n"
                 "setp.lt.u32 p, s, 124; selp.u32 b, 8, -116, p; add.u32 b, b, s; setp.lt.u32 p, s, 120; selp.u32 a, a, b, p;\n"
                 "setp.ne.u32 p, %2, 0; selp.u32 %0, a, %1, p; }" : "=r"(cta) : "r"(blockIdx.x), "r"(prm.by_smid), "r"(smid));
    const int chunk = (cta >> 5) * 4 + ((cta >> 2) & 3);
    const int dt = ((cta >> 4) & 1) * 4 + (cta & 3);
    asm volatile("{ .reg .pred e, p; elect.sync _|e, 0xffffffff; setp.eq.and.u32 p, %0, 5, e;\n"
                 "@p mbarrier.init.shared::cta.b64 [%1], 1; @p mbarrier.init.shared::cta.b64 [%1 + 8], 1;\n"
                 "fence.mbarrier_init.release.cluster; }" ::"r"(warp), "r"(sb + OFF_FULL) : "memory");
    if (warp == 5 && cta < NCTA) {
        tma5b(sb, &mB, 0, dt * 4, sb + OFF_FULL);
        tma4(sb + 2 * ABYTES, &mX, 0, chunk * 64, sb + OFF_FULL);
        STAMP(31);
        tma5b(sb + SLOT, &mB, 64, dt * 4, sb + OFF_FULL + 8);
        tma4(sb + SLOT + 2 * ABYTES, &mX, 64, chunk * 64, sb + OFF_FULL + 8);
    }
    if (cta >= NCTA) {
        if (smem_u32(smem) != sb) __trap();
        if (tid == 0) wait_count_slow(&prm.s->cnt[0], (atomicAdd(&prm.s->cnt[0], 1u) / NGRID + 1) * NGRID);
        return;
    }
    const bool has_gu = cta >= 16;
    constexpr uint32_t full = sb + OFF_FULL, empty = sb + OFF_EMPTY;
    constexpr uint32_t raw = full + 8 * 32;
    constexpr uint32_t bar_xs = full + 8 * 98, bar_dn = full + 8 * 99, bar_xb = full + 8 * 100, bar_xa = full + 8 * 101,
        bar_retry = full + 8 * 102, bar_out = full + 8 * 104;
    constexpr uint32_t bar_base = empty - 64, bar_init3 = empty - 56, bar_rdone = empty - 48, bar_order0 = empty - 40, bar_init2 = empty - 32,
        bar_vec = empty - 24, bar_epoch = empty - 16, bar_dummy = empty - 8, bar_xs0 = empty + 8 * 69,
        bar_zero = empty + 8 * 70, bar_xafree = empty + 8 * 71, bar_order2 = empty + 8 * 72, bar_order3 = empty + 8 * 73, bar_fp = empty + 8 * 74,
        bar_hs = empty + 8 * 75, bar_accb = empty + 8 * 76, bar_xbfree = empty + 8 * 78, bar_fold = empty + 8 * 79, bar_st = empty + 8 * 80,
        bar_order1 = empty + 8 * 67, bar_cand = empty + 8 * 68;

    if (warp == 5) {
        if (lane < 2) mbar_expect_tx(full + 8 * lane, SLOT);
        __syncwarp();
        named_bar(0, 256);
#pragma unroll 1
        for (int i = 2; i < NST; i++) {
            pace_until(cstart + T2 + i * P2);
            tma5b(sb + i * SLOT, &mB, i * 64, dt * 4, full + 8 * i);
            tma4(sb + i * SLOT + 2 * ABYTES, &mX, i * 64, chunk * 64, full + 8 * i);
            STAMPIF(i == 4, 1);
        }
    } else if (warp == 4) {
        mbar_init_n<12>(bar_init2, 4);
        asm volatile("bar.arrive 0, 256;" ::: "memory");
        mbar_init_n<4>(bar_base, 4);
        mbar_init_n<8>(empty + 64, 4);
        *reinterpret_cast<uint2*>(smem + OFF_KEYS + 16) = make_uint2(0, 0);
        asm volatile("bar.arrive 1, 64;" ::: "memory");
        asm volatile("bar.arrive 5, 96;" ::: "memory");
        asm volatile("bar.arrive 6, 96;" ::: "memory");
        mbar_init_n<32>(full + 256, 3);
        if (lane < 2) mbar_arrive(bar_init2);
    } else if ((warp >> 1) == 3) {
        if (warp == 6) {
            mbar_init_n<8>(full + 16, 1);
            if (lane >= 2 && lane < 10) mbar_expect_tx(full + 8 * lane, lane >= RE0 && lane < RE0 + 4 ? SLOT + ABYTES : SLOT);
            __syncwarp();
            asm volatile("bar.arrive 0, 256;" ::: "memory");
        }
        const char* pf0 = (warp & 1) ? (const char*)((cta & 64) ? prm.b_im : prm.b_re) + (cta & 63) * 16384 : (const char*)prm.x + cta * 32768;
        pace_until(cstart + PF1);
        asm volatile("prefetch.global.L2 [%0];" ::"l"(pf0 + (lane & (30 >> (warp & 1) & 30)) * 1024 + (lane & 1) * 128 + 256));
        const int i0 = warp == 6 ? 10 : 21;
        mbar_init_n<11>(full + 8 * i0, 1);
        if (lane >= i0 && lane < i0 + 11) mbar_expect_tx(full + 8 * lane, lane >= GU0 && has_gu ? SLOT + WBYTES : SLOT);
        mbar_init_n<24>(full + 512 + 192 * (warp & 1), 1);
        named_bar(5, 96);
        if (lane == 0) mbar_arrive(bar_init2);
        STAMP(21);
    }
    __syncwarp();

    if (warp >= 8) {
        asm volatile("setmaxnreg.dec.sync.aligned.u32 72;");
        const uint32_t c0 = cstart;
        uint64_t stream;
        asm volatile("createpolicy.fractional.L2::evict_first.b64 %0, 1.0;" : "=l"(stream));
        const CUtensorMap* mw = (cta & 1) ? &mWu : &mWg;
        const int dc = (cta & 15) * 64, dr = (cta >> 4) * 448;
        auto gutile = [&](int i) {
            const int n = i + 3 - GU0;
            if (has_gu) tma2(sb + OFF_W + (n & 7) * WBYTES, mw, (cta >> 1) * 64 - 512, n * 32, full + 8 * (i + 3), stream);
        };
        if (warp == 8) {
            named_bar(0, 256);
            asm volatile("prefetch.tensormap [%0];" ::"l"(&mXr));
#pragma unroll 1
            for (int u = 0; u < 2; u++) {
                sleep_until(c0 + R0 + u * R_PACE);
                tma3(sb + OFF_W + u * ABYTES, &mXr, u * 256, cta * 16, full + 8 * (RE0 + u));
            }
            uint32_t dst = sb, base = c0;
            int i = NST;
#pragma unroll 1
            for (int sg = 0; sg < 5; sg++) {
                if (sg == 1) mbar_wait(bar_init2);
                if (sg == 3) {
                    mbar_wait(bar_base);
                    base = uni(lds32(sb + OFF_EPOCH + 8));
                }
                const int end = (0x20611349 >> (6 * sg)) & 63;
                const uint32_t per = PER + (sg == 1 ? 72 : sg == 4 ? 36 : 0);
                uint32_t tt = base + (sg == 0 ? Sched<NST>::t : sg == 1 ? Sched<9>::t : sg == 2 ? Sched<13>::t : sg == 3 ? Sched<17>::t : Sched<24>::t);
#pragma unroll 1
                for (; i < end; i++) {
                    mbar_wait(empty + 8 * (i - NST));
                    LATE(i, tt);
                    pace_until(tt);
                    tma5b(dst, &mB, (i & 15) * 64, (i >> 4) * 64 + dt * 4, full + 8 * i);
                    tma4(dst + 2 * ABYTES, &mX, (i & 15) * 64, chunk * 64, full + 8 * i);
                    if (i < 7) tma3(sb + OFF_W + (i - 3) * ABYTES, &mXr, (i - 3) * 256, cta * 16, full + 8 * (i + 1));
                    dst = dst == sb + (NST - 1) * SLOT ? sb : dst + SLOT;
                    tt += per;
                }
            }
            const char* hsrc = reinterpret_cast<const char*>(prm.s->h) + (size_t)chunk * 524288;
            auto gemm2 = [&](int i, uint32_t d, int freed, uint32_t tt) {
                if (!(i & 3)) mbar_wait(bar_out + 2 * (i & 28));
                mbar_wait(empty + 8 * freed);
                LATE(i, tt);
                pace_until(tt);
                bulk_load(d, hsrc, 2 * ABYTES, raw + 8 * i);
                tma5(d + 2 * ABYTES, (i & 4) ? &mCim : &mCre, ((i & 3) + ((i >> 1) & 12)) * 64, dt * 8, full + 8 * i);
                hsrc += 2 * ABYTES;
            };
            {
                uint32_t tt = base + Sched<32>::t;
#pragma unroll 1
                for (int u = 0; u < 4; u++) {
                    const CUtensorMap* mc = (u & 1) ? &mCim : &mCre;
                    mbar_wait(bar_out + 8 * u);
#pragma unroll 1
                    for (int col = (u >> 1) * 256; i < 36 + 4 * u; i++, col += 64) {
                        mbar_wait(empty + 8 * (i - NST));
                        LATE(i, tt);
                        pace_until(tt);
                        bulk_load(dst, hsrc, 2 * ABYTES, raw + 8 * i);
                        tma5(dst + 2 * ABYTES, mc, col, dt * 8, full + 8 * i);
                        gutile(i);
                        hsrc += 2 * ABYTES;
                        dst = dst == sb + (NST - 1) * SLOT ? sb : dst + SLOT;
                        tt += PER + 36;
                    }
                }
            }
            for_entries<48, FIN - 1>(base, [&](int i, uint32_t tt) {
                gemm2(i, dst, i - NST, tt);
                const int n = i - GU0 - 29;
                if (n < 0) gutile(i);
                else if ((n & 5) == 1) tma5(sb + OFF_W + (n & 2) * (ABYTES / 2), &mXe, dt * 128 + (n & 2) * 32, chunk * 64, bar_xa);
                else asm volatile(ONE "cp.async.bulk.prefetch.tensor.2d.L2.global [%0, {%1, %2}]; }" ::"l"(&mWd), "r"(dc), "r"(dr + 64 * (n < 4 ? 1 + n / 2 : n - 1)) : "memory");
                dst = dst == sb + (NST - 1) * SLOT ? sb : dst + SLOT;
            });
            static_for<NENT - FIN + 1>([&](auto u) {
                constexpr int i = FIN - 1 + u;
                gemm2(i, sb + slot_off(i), i < XE ? i - NST : i == XE ? 71   : i - NST - 1, base + Sched<i>::t);
            });
            STAMP(4);
        } else if (warp == 9) {
#pragma unroll
            for (int u = 0; u < 8; u++) {
                const int row = (u >> 2) * 4 + (lane >> 3);
                asm volatile("cp.async.cg.shared.global [%0], [%1], 16;" ::"r"(sb + OFF_XS + (u & 3) * 1024 + row * 128 + (((lane & 7) ^ row) << 4)),
                             "l"((const char*)(u < 4 ? prm.w_r : prm.gate_w) + (u & 3) * 512 + lane * 16) : "memory");
            }
            uint32_t ticket = 0;
            if (lane == 0) ticket = atomicAdd(&prm.s->cnt[0], 1u);
            named_bar(1, 64);
            if (lane == 0) *reinterpret_cast<volatile uint32_t*>(smem + OFF_EPOCH) = ticket / NGRID;
            __syncwarp();
            if (lane < 4) mbar_arrive(bar_epoch);
            asm volatile("cp.async.wait_all;" ::: "memory");
            asm volatile("fence.proxy.async.shared::cta;" ::: "memory");
            __syncwarp();
            if (lane < 4) mbar_arrive(bar_vec);
            STAMP(18);
#pragma unroll 1
            for (int i = 4; i < 22; i++) mbar_init_n<4>(empty + 32 * i, 4);
            if (lane < 4) mbar_arrive(bar_init3);
            STAMP(19);
            mbar_wait(bar_cand);
            {
                const uint32_t* list = reinterpret_cast<const uint32_t*>(smem + OFF_LIST);
                const int n = (int)lds32(sb + OFF_KEYS + 16);
#pragma unroll 1
                for (int i0 = 0; i0 < n; i0 += 32) {
                    const uint32_t k = list[i0 + lane];
                    int rank = 0;
#pragma unroll 2
                    for (int o = 0; o < n; o += 4) {
                        const uint4 l4 = *reinterpret_cast<const uint4*>(list + o);
                        rank += (l4.x > k) + (l4.y > k) + (l4.z > k) + (l4.w > k);
                    }
                    if (rank < 8) reinterpret_cast<uint32_t*>(smem + OFF_SEL)[rank] = k;
                }
                __syncwarp();
                STAMP(6);
                const uint32_t key = lds32(sb + OFF_SEL + 4 * (lane & 7)), tok = ~key & 2047u, tag = lds32(sb + OFF_EPOCH) + 1;
                const uint32_t ta = __shfl_sync(0xffffffffu, tok, lane >> 3), tb = __shfl_sync(0xffffffffu, tok, 4 + (lane >> 3));
                const uint32_t da = sb + OFF_XS + (lane >> 3) * 128 + (((lane & 7) ^ (lane >> 3)) << 4), db = (da ^ 64) + 512;
                const char *sa = (const char*)prm.x + ta * 2048 + (lane & 7) * 16, *sc = (const char*)prm.x + tb * 2048 + (lane & 7) * 16;
#pragma unroll
                for (int u = 0; u < 16; u++) {
                    asm volatile("cp.async.cg.shared.global [%0], [%1], 16;" ::"r"(da + u * 1024), "l"(sa + u * 128) : "memory");
                    asm volatile("cp.async.cg.shared.global [%0], [%1], 16;" ::"r"(db + u * 1024), "l"(sc + u * 128) : "memory");
                    if (u == 3) {
                        asm volatile("cp.async.wait_all;" ::: "memory");
                        asm volatile("fence.proxy.async.shared::cta;" ::: "memory");
                        __syncwarp();
                        if (lane < 4) mbar_arrive(bar_xs0);
                        STAMP(17);
                    }
                }
                if ((tok >> 7) == (uint32_t)chunk) {
                    float4* zp = reinterpret_cast<float4*>(prm.out + tok * D_ + dt * 128) + (lane >> 3) * 2;
#pragma unroll
                    for (int u = 0; u < 8; u++) zp[(u >> 1) * 8 + (u & 1)] = make_float4(0.f, 0.f, 0.f, 0.f);
                }
                uint32_t it = 0;
                unsigned long long u;
                do {
                    u = ld_relaxed1(&prm.s->gpack[tok >> 1]);
                    if (++it > SPIN_LIMIT) __trap();
                } while (!__all_sync(0xffffffffu, (uint32_t)(u >> 32) == tag));
                const uint32_t kb = key >> 16;
                const float r = bf_lo((kb & 0x8000u) ? (kb & 0x7FFFu) : (~kb & 0xFFFFu)), gv = (tok & 1) ? bf_hi((uint32_t)u) : bf_lo((uint32_t)u);
                reinterpret_cast<float*>(smem + OFF_FAC)[lane & 7] = rbf(1.0f - gv) * rbf(sigmoidf_(r));
                asm volatile("cp.async.wait_all;" ::: "memory");
                asm volatile("fence.proxy.async.shared::cta;" ::: "memory");
                __syncwarp();
                if (lane == 0) mbar_arrive(bar_xs);
                STAMP(7);
            }
            char* hd = reinterpret_cast<char*>(prm.s->h) + (size_t)chunk * 524288 + (dt >> 1) * 16384 + (dt & 1) * 4096;
            const uint32_t cb = uni(lds32(sb + OFF_EPOCH + 8)) + ST_SHIFT;
            uint32_t tt = cb + Sched<GU0 + 4>::t;
#pragma unroll 1
            for (int np = 0; np < 16; np++) {
                if (!(np & (np & 4 ? 1 : 2))) mbar_wait(bar_st + 4 * (np & 12) + ((np & 3) ? 8 : 0));
                const uint32_t now = clk32() - ST_TOL;
#pragma unroll 1
                while ((int)(tt - now) < 0) tt += PER + 36;
                const uint32_t src = sb + OFF_STG + (np & 3) * 4096;
                pace_until(tt);
                bulk_store(hd, src, 4096);
                asm volatile("cp.async.bulk.commit_group;" ::: "memory");
                if (np & 2) {
                    if (np & 1) asm volatile("cp.async.bulk.wait_group.read 0;" ::: "memory");
                    else asm volatile("cp.async.bulk.wait_group.read 1;" ::: "memory");
                    __syncwarp();
                    if (lane == 0) mbar_arrive(bar_out + 4 * (np & 12) + 8 * (np & 1));
                }
                STAMPIF(np & 2, 8 + ((np >> 1) & 6) + (np & 1));
                hd += (np & 1) ? 65536 - 8192 : 8192;
                tt += PER + 36;
            }
#pragma unroll 1
            for (int u = 0; u < 2; u++) {
                pace_until(tt);
                tma5(sb + OFF_STG + u * ABYTES, &mXe, dt * 128 + u * 64, chunk * 64 + 8, bar_xb);
                tt += PER + 36;
            }
            wait_count(&prm.s->cnt[32], (lds32(sb + OFF_EPOCH) + 1) * NCTA);
            if (lane < 4) mbar_arrive(bar_zero);
            static_for<7>([&](auto u) {
                if (u != 2) mbar_wait(u == 0 ? empty + 8 * (GU0 + 31) : u == 1 ? bar_xbfree : empty + 8 * (FIN - 2 + u));
                if (u < 3) pace_until(cb + Sched<(u < 2 ? 57 + u : NENT - 1)>::t);
                tma2(sb + dn_off(u), &mWd, dc, dr + u * 64, bar_dn, stream);
            });
            STAMP(27);
        } else {
            const char* pf0 = (warp & 1) ? (const char*)((cta & 64) ? prm.b_im : prm.b_re) + (cta & 63) * 16384 : (const char*)prm.x + cta * 32768;
            pf0 += lane * 2048;
#pragma unroll 1
            for (int k = 2; k < 8; k++) {
                sleep_until(c0 + PF0 + (k - 1) * ((warp & 1) ? PFB_PACE : PFX_PACE));
                if (lane < (16 >> (warp & 1))) prefetch_l2(pf0 + k * 256);
            }
            named_bar(6, 96);
            if (warp == 10) {
                const char* pb = (const char*)((cta & 64) ? prm.b_im : prm.b_re) + (cta & 63) * 16384;
                static_for<12>([&](auto k) {
                    sleep_until(c0 + Sched<BP1 + k>::t + ST_SHIFT);
                    bulk_prefetch((k < 4 ? pb + 1048576 : (const char*)(k < 8 ? prm.c_re : prm.c_im) + cta * 16384) + (k & 3) * 4096, 4096);
                    if (k == 4) { mbar_wait(bar_init2); mbar_wait(bar_init3); }
                    if (k >= 4 && lane < 8) mbar_expect_tx(full + 8 * (8 * k + lane), 8 * k + lane < GU0 + 32 && has_gu ? 2 * ABYTES + WBYTES : 2 * ABYTES);
                });
                asm volatile("prefetch.tensormap [%0];" ::"l"(&mCre));
                asm volatile("prefetch.tensormap [%0];" ::"l"(&mCim));
                asm volatile("prefetch.tensormap [%0];" ::"l"(&mWd));
                asm volatile("prefetch.tensormap [%0];" ::"l"(&mXe));
                if (lane < 3) mbar_expect_tx(bar_dn + 8 * lane, lane ? 2 * ABYTES : 7 * ABYTES);
                mbar_wait(bar_xs);
                mbar_wait(bar_st);
                if (lane == 0) red_release(&prm.s->cnt[32]);
                __syncwarp();
                STAMP(22);
            } else {
                asm volatile("prefetch.tensormap [%0];" ::"l"(mw));
                mbar_wait(bar_base);
                const uint32_t cb = uni(lds32(sb + OFF_EPOCH + 8)) + W_SHIFT;
                auto early = [&](int i, uint32_t tt) {
                    mbar_wait(empty + 8 * (i - NST));
                    pace_until(tt);
                    gutile(i);
                };
                for_entries<GU0 - 3, GU0 + 4>(cb, early);
                for_entries<GU0 + 4, 32>(cb, early);
            }
            mbar_wait(bar_epoch);
            const uint32_t t2 = lds32(sb + OFF_EPOCH) + 1, tagw = (t2 & 1) | ((t2 & 2) << 15), half = (warp & 1) * ABYTES;
            const uint32_t lo = half + lane * 32 + (lane & 4) * 4 + (lane >> 3) * 4, retry = bar_retry + (warp & 1) * 8;
            const bool leader = lane == 0;
            uint32_t slot = sb + (32 % NST) * SLOT, rpar = 0;
#pragma unroll 1
            for (int i = 32; i < NENT; i++) {
                const uint32_t src = i == XE ? sb + OFF_W : slot;
                if (i != XE) slot = slot == sb + (NST - 1) * SLOT ? sb : slot + SLOT;
                auto current = [&]() {
                    uint32_t v[8];
#pragma unroll
                    for (int u = 0; u < 8; u++) v[u] = lds32(src + lo + u * 1024);
#pragma unroll
                    for (int u = 0; u < 8; u += 2) asm("lop3.b32 %0, %0, %1, %2, 0x7e;" : "+r"(v[u]) : "r"(v[u + 1]), "r"(tagw));
                    return __all_sync(0xffffffffu, ((v[0] | v[2] | v[4] | v[6]) & 0x00010001u) == 0);
                };
                mbar_wait(raw + 8 * i);
                if (!current()) {
#pragma unroll 1
                    for (uint32_t it = 0;; it++) {
                        if (it > SPIN_LIMIT) __trap();
                        STAMP(16);
                        if (leader) mbar_expect_tx(retry, ABYTES);
                        bulk_load(src + half, reinterpret_cast<const char*>(prm.s->h) + (size_t)chunk * 524288 + (i - 32) * 16384 + half, ABYTES, retry);
                        mbar_wait(retry, rpar);
                        rpar ^= 1;
                        if (current()) break;
                    }
                }
                if (leader) mbar_arrive(full + 8 * i);
            }
        }
    } else {
        asm volatile("setmaxnreg.inc.sync.aligned.u32 216;");
        const int wg = warp >> 2, w = warp & 3, g = lane >> 2, c = lane & 3, at = tid & 127;
        float facc[4];
        float2 a[2], m0[2], a32[2], a128[2];
        auto load_const = [&]() {
            const float2* cp = reinterpret_cast<const float2*>(smem + OFF_CONST) + wg * 64 + w * 8 + g;
#pragma unroll
            for (int h = 0; h < 2; h++) { a[h] = cp[32 * h]; m0[h] = cp[128 + 32 * h]; a32[h] = cp[256 + 32 * h]; a128[h] = cp[384 + 32 * h]; }
        };
        if (wg == 0) {
            named_bar(0, 256);
            STAMPIF(tid == 0, 20);
        } else {
            const int pc = (at >> 5) * 256 + dt * 32 + (at & 31);
            const float lr = __bfloat162float(prm.lam_re[pc]), li = __bfloat162float(prm.lam_im[pc]), ld = __bfloat162float(prm.log_dt[pc]);
            const uint32_t dk = __ldg(reinterpret_cast<const uint32_t*>(prm.dskip + dt * 128) + (at & 63));
#pragma unroll
            for (int i = 0; i < 4; i++) sts128(sb + OFF_LIST + i * 2048 + at * 16, 0u, 0u, 0u, 0u);

            {
                reinterpret_cast<uint32_t*>(smem + OFF_DK)[at & 63] = dk;
                const float dtv = rbf(expf(ld));
                const float er = expf(dtv * lr);
                float sn, cs;
                sincospif(dtv * li * 0.318309886183790672f, &sn, &cs);
                const float ar = er * cs, ai = er * sn;
                const float nr = ar - 1.0f, ni = ai;
                const bool big = fabsf(lr) >= fabsf(li);
                const float t = (big ? li : lr) / (big ? lr : li), dn = big ? lr + li * t : lr * t + li;
                const float cr = (big ? nr + ni * t : nr * t + ni) / dn, ci = (big ? ni - nr * t : ni * t - nr) / dn;
                float2* cp = reinterpret_cast<float2*>(smem + OFF_CONST) + at;
                float2 pw = make_float2(ar, prm.swapped ? ai : -ai);
                cp[0] = pw;
                cp[128] = make_float2(prm.swapped ? -2.f * cr : 2.f * cr, -2.f * ci);
#pragma unroll
                for (int i = 1; i <= 7; i++) {
                    pw = cmul(pw, pw);
                    if (i == 5) cp[256] = pw;
                    if (i == 7) cp[384] = pw;
                }
                __syncwarp();
            }
            named_bar(2, 128);
            load_const();
            mbar_wait(bar_epoch);
            const uint32_t tag = *reinterpret_cast<volatile uint32_t*>(smem + OFF_EPOCH) + 1;
            st_cell(&prm.s->carry[(chunk >> 2) * 2048 + ((w & 1) * 256 + dt * 32 + lane) * 4 + (chunk & 3)], tag + 2, 0, 0, 0, w < 2);
            if (w == 2) st_cell(lane < 4 ? (uint4*)prm.s->rpack + cta * 4 + lane : lane < 8 ? (uint4*)prm.s->gpack + cta * 4 + lane - 4 : prm.s->time + cta * 2 + (lane & 1), 0, 0, 0, 0, lane < 10);
            {
                const uint32_t nt = ((tag & 1) | ((tag & 2) << 15)) ^ 0x00010001u;
                st_cell(prm.s->hid + (cta & 1) * F_ + (cta >> 1) * 64 - 512 + (at & 63), nt, nt, nt, nt, has_gu && w >= 2);
            }
            named_bar(2, 128);
            STAMPIF(lane == 0, 52);
            mbar_wait(bar_rdone);

            const uint32_t tpub = clk32();
            if (w == 2) {
                uint32_t gnow;
                asm volatile("mov.u32 %0, %%globaltimer_lo;" : "=r"(gnow));
                st_cell(prm.s->time + cta * 2, tag, tpub, gnow, 0, lane == 0);
            }
            if (w < 2) {
                const float2* red = reinterpret_cast<const float2*>(smem + OFF_RED) + w * 8 + (lane & 7);
                const float2 r0 = red[0], r1 = red[16], r2 = red[32], r3 = red[48];
                const float v0 = (r0.x + r1.x) + (r2.x + r3.x), v1 = (r0.y + r1.y) + (r2.y + r3.y);
                uint32_t pk2;
                if (w == 0) {
                    pk2 = pack_bf(v0, v1);
                    pk2 ^= (((pk2 >> 15) & 0x00010001u) * 0x7FFFu) ^ 0x80008000u;
                } else pk2 = pack_bf(sigmoidf_(rbf(v0)), sigmoidf_(rbf(v1)));
                if (lane < 8) asm volatile("st.relaxed.gpu.global.b64 [%0], %1;" ::"l"((w ? prm.s->gpack : prm.s->rpack) + cta * 8 + lane), "l"(((unsigned long long)tag << 32) | pk2) : "memory");
                __syncwarp();
            }
            STAMPIF(at == 0, 24);
            uint32_t it = 0, pr[8], g1, tm[4] = {};
            sleep_until(tpub + G0);
            while (true) {
                bool ok = true;
#pragma unroll
                for (int k = 0; k < 4; k++) {
                    const ulonglong2 u = ld_relaxed2(&prm.s->rpack[k * 256 + 2 * at]);
                    ok = ok && (uint32_t)(u.x >> 32) == tag && (uint32_t)(u.y >> 32) == tag;
                    pr[2 * k] = (uint32_t)u.x; pr[2 * k + 1] = (uint32_t)u.y;
                }
                const unsigned long long u1 = ld_relaxed1(&prm.s->gpack[chunk * 64 + (at & 63)]);
                ok = ok && (uint32_t)(u1 >> 32) == tag;
                g1 = (uint32_t)u1;
                ld_cell(tm, prm.s->time + at * 2);
                ok = ok && tm[0] == tag;
                if (__all_sync(0xffffffffu, ok)) break;
                if (++it > SPIN_LIMIT) __trap();
            }
            STAMPIF(lane == 0, 25);
            uint32_t m = __vmaxu2(__vimax3_u16x2(__vimax3_u16x2(pr[0], pr[1], pr[2]), pr[3], pr[4]), __vimax3_u16x2(pr[5], pr[6], pr[7]));
            m = (max(m, m << 16) & 0xFFFF0000u) | (uint32_t)lane;
            const uint32_t m1 = __reduce_max_sync(0xffffffffu, m), m2 = __reduce_max_sync(0xffffffffu, m == m1 ? 0u : m);
            uint32_t* keys = reinterpret_cast<uint32_t*>(smem + OFF_KEYS);
            const uint32_t g0 = uni(tm[2]), glast = g0 + (uint32_t)__reduce_max_sync(0xffffffffu, (int)(tm[2] - g0));
            if (lane == 0) { keys[w] = m2; reinterpret_cast<uint32_t*>(smem + OFF_XS + 1024)[w] = glast; }
            reinterpret_cast<uint2*>(smem + OFF_XS)[at] = make_uint2(tm[1], tm[2]);
            sts128(sb + OFF_XS + 4096 + at * 16, pr[0], pr[1], pr[2], pr[3]);
            sts128(sb + OFF_XS + 6144 + at * 16, pr[4], pr[5], pr[6], pr[7]);
            *reinterpret_cast<uint32_t*>(smem + OFF_G + 4 * (at & 63)) = g1;
            mbar_wait(bar_init3);
            named_bar(2, 128);
            if (w == 3) {
                const uint4 g4 = *reinterpret_cast<const uint4*>(smem + OFF_XS + 1024);
                const uint2* tt = reinterpret_cast<const uint2*>(smem + OFF_XS);
                const uint2 own = tt[cta];
                uint2 ref = tt[cta & ~15];
                if ((uint32_t)(ref.x - own.x - (((int)(ref.y - own.y) * CLK_NS) >> 8) + 400) >= 800u) ref = tt[cta & ~1];
                const int last = max(max((int)(g4.x - ref.y), (int)(g4.y - ref.y)), max((int)(g4.z - ref.y), (int)(g4.w - ref.y)));
                *reinterpret_cast<volatile uint32_t*>(smem + OFF_EPOCH + 8) = ref.x + ((min(last, 4000) * CLK_NS) >> 8) + MARGIN - Sched<RE0 + 8>::t;
                if (lane < 4) mbar_arrive(bar_base);
                STAMP(23);
            }
            __syncwarp();
            const uint4 th4 = *reinterpret_cast<const uint4*>(keys);
            const uint32_t th = (max(min(min(th4.x, th4.y), min(th4.z, th4.w)) >> 16, 1u) - 1u) * 0x00010001u;
            uint32_t mask = 0;
#pragma unroll
            for (int k = 7; k >= 0; k--) mask = mask * 2 + __vminu2(__vmaxu2(pr[k], th) ^ th, 0x00010001u);
            uint32_t pos = 0;
            asm volatile("{ .reg .pred p; setp.ne.u32 p, %2, 0; @p atom.shared.add.u32 %0, [%1], %2; }" : "+r"(pos) : "r"(sb + OFF_KEYS + 16), "r"(__popc(mask)) : "memory");
            while (mask) {
                const int bit = __ffs(mask) - 1, k = bit & 7, hi = bit >> 4;
                mask &= mask - 1;
                const uint32_t sc = *reinterpret_cast<const uint16_t*>(smem + OFF_XS + 4096 + (k >> 2) * 2048 + at * 16 + (k & 3) * 4 + hi * 2);
                *reinterpret_cast<uint32_t*>(smem + OFF_LIST + 4 * pos++) = (sc << 16) | (0x8000u + 2047u - (uint32_t)((k >> 1) * 512 + 4 * at + 2 * (k & 1) + hi));
            }
            __syncwarp();
            if (lane == 0) mbar_arrive(bar_cand);
            STAMPIF(lane == 0, 26);
            mbar_wait(bar_order0);
        }

        float accA[64], accB[64];
        Ring ring = {bar_dummy, wg};
        {
            static_assert(GU0 - 16 == RE0, "segments");
            run_entries<0, 0>(ring, wg * 16, wg * 16 + RE0, accA, accB, facc, true);
            if (wg == 0) {
                float racc[4];
                mbar_wait(bar_vec);
                run_entries<0, 1>(ring, RE0, RE0 + 4, accA, accB, racc, false, true);
                mbar_wait(bar_init2);
                const uint32_t red = sb + OFF_RED + 4 * (w * 32 + (c >> 1) * 16 + g);
                run_entries<0, 0>(ring, RE0 + 4, RE0 + 5, accA, accB, facc, false, false, [&]() {
                    pin4(racc);
                    asm volatile("{ .reg .pred p; setp.ne.u32 p, %3, 0; @p st.shared.f32 [%0], %1; @p st.shared.f32 [%0 + 32], %2; }" ::"r"(red),
                                 "f"((w & 1) ? racc[1] : racc[0]), "f"((w & 1) ? racc[3] : racc[2]), "r"((uint32_t)((c & 1) == (w >> 1))) : "memory");
                    __syncwarp();
                    if (lane == 0) mbar_arrive(bar_rdone);
                    STAMPIF(lane == 0, 5);
                });
                run_entries<0, 0>(ring, RE0 + 5, 16, accA, accB, facc);
                if (lane == 0) mbar_arrive(bar_order0);
                mbar_wait(bar_base);
                load_const();
                named_bar(3, 128);
            } else {
#pragma unroll
                for (int u = 0; u < 2; u++) {
                    mbar_wait(u ? bar_xs : bar_xs0);
                    run_entries<0, 2>(ring, GU0 + 8 * u, GU0 + 8 + 4 * u, accA, accB, facc, false, u == 0);
                }
                if (lane == 0) mbar_arrive(bar_order1);
            }
        }
        const uint32_t tag = *reinterpret_cast<volatile uint32_t*>(smem + OFF_EPOCH) + 1;
        const float2 a64[2] = {cmul(a32[0], a32[0]), cmul(a32[1], a32[1])};
        wgmma_wait<0>();
        pin64(accA); pin64(accB); pin4(facc);
        if (lane == 0) mbar_arrive(ring.prev);
        STAMPIF(at == 0, 28 + wg);
        GSTAMP(tid == 0, 1);

        const int tl = 32 * (g >> 1) + (g & 1) + 4 * w + 16 * wg, t0 = chunk * 128 + tl;
        float* op = prm.out + (size_t)t0 * D_ + dt * 128 + 4 * c;
        uint2 xv[8][2], dk[8];
        uint32_t gp[2], om[2], routed[2];
        auto row_setup = [&]() {
            const uint4 sa = *reinterpret_cast<const uint4*>(smem + OFF_SEL), sc = *reinterpret_cast<const uint4*>(smem + OFF_SEL + 16);
#pragma unroll
            for (int r = 0; r < 2; r++) {
                const uint32_t id = 0x8000u + 2047u - (uint32_t)(t0 + 2 * r);
                routed[r] = (uint16_t)sa.x == id || (uint16_t)sa.y == id || (uint16_t)sa.z == id || (uint16_t)sa.w == id ||
                            (uint16_t)sc.x == id || (uint16_t)sc.y == id || (uint16_t)sc.z == id || (uint16_t)sc.w == id;
                gp[r] = reinterpret_cast<const uint16_t*>(smem + OFF_G)[tl + 2 * r] * 0x00010001u;
                om[r] = pack_bf(1.0f - bf_hi(gp[r]), 1.0f - bf_hi(gp[r]));
            }
#pragma unroll
            for (int j = 0; j < 8; j++) dk[j] = lds64(sb + OFF_DK + 32 * j + 8 * c);
        };
        auto release = [&](uint32_t bar) {
            asm volatile("fence.proxy.async.shared::cta;" ::: "memory");
            __syncwarp();
            if (lane == 0) mbar_arrive(bar);
        };

        {
            const uint32_t t2 = tag & 3u;
            float4* cslot = &prm.s->carry[(wg * 256 + dt * 32 + w * 8 + g) * 4];
            float2 e[2], w0[2];
#pragma unroll
            for (int h = 0; h < 2; h++) {
                float (&acc)[64] = h ? accB : accA;
                const float2 a1 = make_float2(a[h].x, -a[h].y);
                e[h] = make_float2(acc[0], acc[2]);
#pragma unroll
                for (int s = 1; s < 32; s++) {
                    const int i0 = 4 * (s >> 1) + (s & 1);
                    e[h] = cfma(a1, e[h], make_float2(acc[i0], acc[i0 + 2]));
                }
                asm volatile("" : "+f"(e[h].x), "+f"(e[h].y), "+f"(accB[0]), "+f"(accB[2]));
                if (!h) gap();
            }
#pragma unroll
            for (int h = 0; h < 2; h++) {
                e[h] = make_float2(fmaf(m0[h].x, e[h].x, m0[h].y * e[h].y), fmaf(-m0[h].x, e[h].y, m0[h].y * e[h].x));
                float2 y = make_float2(__shfl_up_sync(0xffffffffu, e[h].x, 1, 4), __shfl_up_sync(0xffffffffu, e[h].y, 1, 4));
                if (c >= 1) e[h] = cfma(a32[h], y, e[h]);
                y = make_float2(__shfl_up_sync(0xffffffffu, e[h].x, 2, 4), __shfl_up_sync(0xffffffffu, e[h].y, 2, 4));
                if (c >= 2) e[h] = cfma(a64[h], y, e[h]);
            }
            st_cell(cslot + (chunk >> 2) * 2048 + (chunk & 3), (__float_as_uint(e[0].x) & ~3u) | t2, __float_as_uint(e[0].y), __float_as_uint(e[1].x), __float_as_uint(e[1].y), c == 3);
            gap();
            STAMPIF(lane == 0, 30 + 2 * wg);
            const int j1 = chunk - 1 - c;
            uint32_t v[4][4] = {{t2, 0, 0, 0}, {t2, 0, 0, 0}, {t2, 0, 0, 0}, {t2, 0, 0, 0}};
            auto poll = [&]() {
#pragma unroll
                for (int m = 0; m < 4; m++) ld_cell(v[m], cslot + (j1 >> 2) * 2048 + c - m * 2048, j1 >= 4 * m);
            };
            float2 a512[2], pw128[2], pw32[2];
#pragma unroll
            for (int h = 0; h < 2; h++) {
                float (&acc)[64] = h ? accB : accA;
                w0[h] = make_float2(__shfl_up_sync(0xffffffffu, e[h].x, 1, 4), __shfl_up_sync(0xffffffffu, e[h].y, 1, 4));
                if (c == 0) w0[h] = make_float2(0.f, 0.f);
                const float2 one = make_float2(1.f, 0.f), a256 = cmul(a128[h], a128[h]);
                a512[h] = cmul(a256, a256);
                pw128[h] = cmul((j1 & 1) ? a128[h] : one, (j1 & 2) ? a256 : one);
                pw32[h] = cmul((c & 1) ? a32[h] : one, (c & 2) ? a64[h] : one);
                asm volatile("" : "+f"(a512[h].x), "+f"(a512[h].y), "+f"(pw128[h].x), "+f"(pw128[h].y), "+f"(pw32[h].x), "+f"(pw32[h].y));
                gap();
#pragma unroll
                for (int n = 0; n < 16; n++) {
                    if (16 * h + n == POLL_S) poll();
                    asm volatile("{ .reg .f32 a, b, c, d, n; neg.f32 n, %4; mul.f32 a, %1, %5; mul.f32 b, %0, %5; mul.f32 c, %3, %5; mul.f32 d, %2, %5;\n"
                                 "fma.rn.f32 %0, %0, %4, a; fma.rn.f32 %1, %1, n, b; fma.rn.f32 %2, %2, %4, c; fma.rn.f32 %3, %3, n, d; }"
                                 : "+f"(acc[4 * n]), "+f"(acc[4 * n + 2]), "+f"(acc[4 * n + 1]), "+f"(acc[4 * n + 3]) : "f"(m0[h].x), "f"(m0[h].y));
                    if (n & 1) gap();
                }
            }
            STAMPIF(lane == 0, 34 + 2 * wg);
            {
                uint32_t it = 0;
                while (!__all_sync(0xffffffffu, (((v[0][0] ^ t2) | (v[1][0] ^ t2) | (v[2][0] ^ t2) | (v[3][0] ^ t2)) & 3u) == 0)) {
                    poll();
                    if (++it > SPIN_LIMIT) __trap();
                }
                STAMPIF(lane == 0, 35 + 2 * wg);
#pragma unroll
                for (int h = 0; h < 2; h++) {
                    float2 hin = make_float2(__uint_as_float(v[3][2 * h]), __uint_as_float(v[3][2 * h + 1]));
#pragma unroll
                    for (int m = 2; m >= 0; m--) hin = cfma(a512[h], hin, make_float2(__uint_as_float(v[m][2 * h]), __uint_as_float(v[m][2 * h + 1])));
                    hin = cmul(pw128[h], hin);
                    hin.x += __shfl_xor_sync(0xffffffffu, hin.x, 1); hin.y += __shfl_xor_sync(0xffffffffu, hin.y, 1);
                    hin.x += __shfl_xor_sync(0xffffffffu, hin.x, 2); hin.y += __shfl_xor_sync(0xffffffffu, hin.y, 2);
                    w0[h] = cfma(pw32[h], hin, w0[h]);
                }
            }
            if (wg) mbar_wait(bar_out + 24);
            STAMPIF(lane == 0, 38 + 2 * wg);
            const uint32_t stg = sb + OFF_STG + prm.swapped * 8192 + w * 1024 + (lane & 7) * 128 + (((lane >> 3) ^ (lane & 7)) << 4);
            const uint32_t second = prm.swapped ? -8192 : 8192;
            const uint32_t keep = c == (g >> 1) ? 0xFFFEFFFEu : 0xFFFFFFFFu, tagw = ((t2 & 1) | ((t2 & 2) << 15)) & ~keep;
#pragma unroll
            for (int h = 0; h < 2; h++) {
                float (&acc)[64] = h ? accB : accA;
                uint32_t ra[16], ia[16];
                auto stage = [&](uint32_t (&r)[16], uint32_t base, int j) {
                    stsm4((base ^ ((j & 1) * 64)) + (j >> 1) * 4096, r[4 * j], r[4 * j + 1], r[4 * j + 2], r[4 * j + 3]);
                };
#pragma unroll
                for (int n = 0; n < 16; n++) {
                    const float2 y = cfma(a[h], w0[h], make_float2(acc[4 * n], acc[4 * n + 2]));
                    w0[h] = cfma(a[h], y, make_float2(acc[4 * n + 1], acc[4 * n + 3]));
                    ra[n] = pack_bf(y.x, w0[h].x);
                    ia[n] = pack_bf(y.y, w0[h].y);
                    if (!(n & 1)) { ra[n] = (ra[n] & keep) | tagw; ia[n] = (ia[n] & keep) | tagw; }
                    if (!h && (n & 3) == 3) {
                        if (n == 11) { asm volatile("" : "+r"(ra[n]), "+r"(ia[n])); gap(); release(bar_st + 32 * wg); }
                        stage(ra, stg, n >> 2); stage(ia, stg + second, n >> 2);
                        gap();
                    }
                    if (h && n == 3) { asm volatile("" : "+r"(ra[n]), "+r"(ia[n])); gap(); release(bar_st + 32 * wg + 8); }
                }
                if (h) {
                    STAMPIF(lane == 0, 39 + 2 * wg);
                    mbar_wait(bar_out + 32 * wg);
                    if (prm.swapped) {
#pragma unroll
                        for (int n = 0; n < 16; n++) { const uint32_t t = ra[n]; ra[n] = ia[n]; ia[n] = t; }
                    }
                    const uint32_t st0 = stg - prm.swapped * 8192;
#pragma unroll
                    for (int j = 0; j < 4; j++) stage(ra, st0, j);
                    mbar_wait(bar_xs);
                    row_setup();
                    release(bar_st + 32 * wg + 16);
                    mbar_wait(bar_out + 32 * wg + 8);
#pragma unroll
                    for (int j = 0; j < 4; j++) stage(ia, st0 + 8192, j);
                    release(bar_st + 32 * wg + 24);
                }
                STAMPIF(lane == 0, 42 + 2 * wg + h);
            }
        }

        const uint32_t xr = 2 * (g & 3) + (g >> 2), xa = sb + (wg ? OFF_STG : OFF_W) + (16 * w + xr) * 128 + (((c >> 1) ^ xr) << 4) + (c & 1) * 8;
        auto handover = [&](uint32_t bar) {
            const uint4 z = ldsm4(sb + OFF_KEYS + 16);
            if (lane == 1) mbar_arrive(bar + z.x);
        };
        auto load_x = [&](int j0, int j1) {
#pragma unroll
            for (int j = j0; j < j1; j++)
#pragma unroll
                for (int r = 0; r < 2; r++) xv[j][r] = lds64((xa ^ (32 * (j & 3))) + (j >> 2) * ABYTES + r * 1024);
        };
        auto skip_term = [&](int j0, int j1) {
#pragma unroll
            for (int j = j0; j < j1; j++)
#pragma unroll
                for (int r = 0; r < 2; r++) {
                    xv[j][r].x = mul_bf2(xv[j][r].x, fma_bf2(gp[r], dk[j].x, om[r]));
                    xv[j][r].y = mul_bf2(xv[j][r].y, fma_bf2(gp[r], dk[j].y, om[r]));
                    asm volatile("" : "+r"(xv[j][r].x), "+r"(xv[j][r].y));
                }
        };
        auto finish = [&](float (&acc)[64], int j, bool gaps) {
#pragma unroll
            for (int r = 0; r < 2; r++) {
                const int o = 8 * j + 2 * r;
                const float gv = bf_hi(gp[r]);
                acc[o] = fmaf(gv, acc[o], bf_lo(xv[j][r].x)); acc[o + 1] = fmaf(gv, acc[o + 1], bf_hi(xv[j][r].x));
                acc[o + 4] = fmaf(gv, acc[o + 4], bf_lo(xv[j][r].y)); acc[o + 5] = fmaf(gv, acc[o + 5], bf_hi(xv[j][r].y));
                stg4_unless(op + r * 2 * D_ + 16 * j, acc[o], acc[o + 1], acc[o + 4], acc[o + 5], routed[r]);
                if (gaps) gap();
            }
        };
        auto finish_routed = [&](float (&acc)[64]) {
#pragma unroll
            for (int r = 0; r < 2; r++)
                if (routed[r]) {
#pragma unroll
                    for (int j = 0; j < 8; j++) red4(op + r * 2 * D_ + 16 * j, acc[8 * j + 2 * r], acc[8 * j + 2 * r + 1], acc[8 * j + 2 * r + 4], acc[8 * j + 2 * r + 5]);
                }
            __syncwarp();
        };
        const uint32_t xbuf = sb + slot_off(FIN) + w * 2048 + lane * 16;

        if (wg == 1) {
            float outB[64];
            const uint32_t tagw = (tag & 1) | ((tag & 2) << 15);
            mbar_wait(bar_fp);
            {
                const float4 o4 = lds128f(sb + OFF_XS + at * 16);
                const float o[4] = {o4.x, o4.y, o4.z, o4.w};
                float v[4];
#pragma unroll
                for (int u = 0; u < 4; u++) {
                    v[u] = rbf(facc[u] + o[u]);
                    if (!(cta & 1)) v[u] = __fdividef(v[u], 1.0f + __expf(-v[u]));
                }
                uint32_t w0 = pack_bf(v[0], v[1]), w1 = pack_bf(v[2], v[3]), cell[4];
                if (c == (g & 3)) { w0 = (w0 & 0xFFFEFFFEu) | tagw; w1 = (w1 & 0xFFFEFFFEu) | tagw; }
#pragma unroll
                for (int u = 0; u < 4; u++) {
                    const uint32_t s0 = __shfl_sync(0xffffffffu, w0, u, 4), s1 = __shfl_sync(0xffffffffu, w1, u, 4);
                    cell[u] = (c & 1) ? s1 : s0;
                }
                st_cell(prm.s->hid + (cta & 1) * F_ + (cta >> 1) * 64 - 512 + w * 16 + g + 8 * c, cell[0], cell[1], cell[2], cell[3], has_gu && c < 2);
            }
            const uint32_t tpub = clk32();
            STAMPIF(lane == 0, 47);
            mbar_wait(bar_xb);
            load_x(0, 8);
            release(bar_xbfree);
            skip_term(0, 8);
            STAMPIF(lane == 0, 46);
            named_bar(2, 128);
            {
                uint32_t hv[4][4] = {}, hu[4][4] = {}, it = 0;
                sleep_until(tpub + HG0);
                while (true) {
                    uint32_t bad = 0;
#pragma unroll
                    for (int i = 0; i < 4; i++) {
                        const uint4* hp = prm.s->hid + (cta >> 4) * 448 + (i < 3 ? i * 128 + at : 384 + (at & 63));
                        ld_cell(hv[i], hp); ld_cell(hu[i], hp + F_);
                    }
#pragma unroll
                    for (int i = 0; i < 4; i++)
                        bad |= (((c & 2) ? ((c & 1) ? hv[i][3] : hv[i][2]) : ((c & 1) ? hv[i][1] : hv[i][0])) ^ tagw) |
                               (((c & 2) ? ((c & 1) ? hu[i][3] : hu[i][2]) : ((c & 1) ? hu[i][1] : hu[i][0])) ^ tagw);
                    if (__all_sync(0xffffffffu, (bad & 0x00010001u) == 0)) break;
                    if (++it > SPIN_LIMIT) __trap();
                }
                STAMPIF(lane == 0, 48);
#pragma unroll
                for (int i = 0; i < 4; i++)
                    sts128(sb + OFF_XS + 16 * (i < 3 ? i * 128 + at : 384 + (at & 63)), mul_bf2(hv[i][0], hu[i][0]), mul_bf2(hv[i][1], hu[i][1]),
                           mul_bf2(hv[i][2], hu[i][2]), mul_bf2(hv[i][3], hu[i][3]));
                asm volatile("fence.proxy.async.shared::cta;" ::: "memory");
                __syncwarp();
                if (lane == 0) mbar_arrive(bar_hs);
                STAMPIF(lane == 0, 49);
            }
            mbar_wait(bar_order2);
            static_for<NENT - FIN>([&](auto u) {
                run_small<1, FIN + u>(outB);
                if (u == 2) { wgmma_wait<2>(); if (lane == 0) mbar_arrive(bar_fold); }
            });
            if (lane == 0) mbar_arrive(bar_order3);
            wgmma_wait<0>();
            pin64(outB);
            KSTAMP(2 * NENT - FIN);
            STAMPIF(at == 0, 50);
#pragma unroll
            for (int q = 0; q < 2; q++) {
                uint4 pb[8];
                mbar_wait(bar_accb + 8 * q);
#pragma unroll
                for (int v = 0; v < 8; v++) pb[v] = ldsm4(xbuf + (2 * q + (v >> 2)) * ABYTES + (v & 3) * 512);
#pragma unroll
                for (int v = 0; v < 8; v++) {
                    const int o = 32 * q + 4 * v;
                    outB[o] += __uint_as_float(pb[v].x); outB[o + 1] += __uint_as_float(pb[v].y);
                    outB[o + 2] += __uint_as_float(pb[v].z); outB[o + 3] += __uint_as_float(pb[v].w);
                    if (v & 1) finish(outB, 4 * q + (v >> 1), false);
                }
            }
            finish_routed(outB);
            STAMPIF(lane == 0, 51);
        } else {
            float outA[64], outB[64], gacc[4];
            ring.slot = 32 % NST;
            ring.prev = bar_dummy;
            mbar_wait(bar_order1);
            run_entries<1, 2>(ring, 32, GU0 + 32, outA, outB, gacc, true, true);
            run_entries<1, 0>(ring, GU0 + 32, GU0 + 33, outA, outB, gacc, false, false, [&]() {
                pin4(gacc);
                sts128(sb + OFF_XS + at * 16, __float_as_uint(gacc[0]), __float_as_uint(gacc[1]), __float_as_uint(gacc[2]), __float_as_uint(gacc[3]));
                __syncwarp();
                if (lane == 0) mbar_arrive(bar_fp);
            });
            mbar_wait(bar_xa);
            run_entries<1, 0>(ring, GU0 + 33, GU0 + 34, outA, outB, gacc, false, false, [&]() { load_x(0, 2); });
            load_x(2, 4);
            run_entries<1, 0>(ring, GU0 + 34, GU0 + 35, outA, outB, gacc, false, false, [&]() { load_x(4, 6); });
            load_x(6, 8);
            run_entries<1, 0>(ring, GU0 + 35, GU0 + 36, outA, outB, gacc, false, false, [&]() { release(bar_xafree); });
            run_entries<1, 0>(ring, GU0 + 36, FIN, outA, outB, gacc);
            static_for<NENT - FIN>([&](auto u) {
                mbar_wait(full + 8 * (FIN + u));
                run_small<0, FIN + u>(outA);
                if (u == 5 && lane == 0) mbar_arrive(bar_order2);
                wgmma_wait<1>();
                if (lane == 0) mbar_arrive(empty + 8 * (FIN + u - 1));
                if (u < 4) skip_term(2 * u, 2 * u + 2);
            });
            wgmma_wait<0>();
            pin64(outA); pin64(outB);
            STAMPIF(at == 0, 53);
            GSTAMP(at == 0, 2);
            auto dump = [&](int v) {
                if (v == 4) mbar_wait(bar_fold);
                stsm4(xbuf + (v >> 2) * ABYTES + (v & 3) * 512, __float_as_uint(outB[4 * v]), __float_as_uint(outB[4 * v + 1]), __float_as_uint(outB[4 * v + 2]),
                      __float_as_uint(outB[4 * v + 3]));
                if ((v & 7) == 7) handover(bar_accb + (v & 8));
            };
            mbar_wait(empty + 8 * FIN);
#pragma unroll
            for (int j = 0; j < 8; j++) {
                finish(outA, j, true);
#pragma unroll
                for (int v = j * NDUMP / 8; v < (j + 1) * NDUMP / 8; v++) dump(v);
            }
            STAMPIF(lane == 0, 54);
            if (DWAIT) mbar_wait(bar_order3);
#pragma unroll
            for (int v = NDUMP; v < 16; v++) dump(v);
            STAMPIF(lane == 0, 55);
            finish_routed(outA);
            const uint2 sk = lds64(sb + OFF_SEL + 8 * c), fk = lds64(sb + OFF_FAC + 8 * c);
            float* y0 = prm.out + (~sk.x & 2047u) * D_ + (cta & 15) * 64 + w * 16 + g;
            float* y1 = prm.out + (~sk.y & 2047u) * D_ + (cta & 15) * 64 + w * 16 + g;
            float yacc[4];
            const uint64_t dw = make_desc(sb), dh = (uint64_t)(((sb + OFF_XS) & 0x3FFFF) >> 4) | ((uint64_t)8 << 16) | ((uint64_t)8 << 32);
            mbar_wait(bar_hs);
            mbar_wait(bar_zero);
            mbar_wait(bar_dn);
            mbar_wait(bar_order3);
            STAMPIF(at == 0, 2);
            wgmma_fence();
#pragma unroll
            for (int n = 0; n < 28; n++) wgmma_n8<1, 1>(yacc, dw + (dn_off(n >> 2) >> 4) + (n & 3) * 128, dh + n * 16, n > 0);
            wgmma_commit();
            wgmma_wait<0>();
            pin4(yacc);
            atomicAdd(y0, yacc[0] * __uint_as_float(fk.x)); atomicAdd(y1, yacc[1] * __uint_as_float(fk.y));
            atomicAdd(y0 + 8, yacc[2] * __uint_as_float(fk.x)); atomicAdd(y1 + 8, yacc[3] * __uint_as_float(fk.y));
            STAMPIF(lane == 0, 3);
        }
    }
}

typedef CUresult (*EncodeFn)(CUtensorMap*, CUtensorMapDataType, cuuint32_t, void*, const cuuint64_t*, const cuuint64_t*, const cuuint32_t*,
                             const cuuint32_t*, CUtensorMapInterleave, CUtensorMapSwizzle, CUtensorMapL2promotion, CUtensorMapFloatOOBfill);

bool encode(EncodeFn fn, CUtensorMap* m, const void* ptr, int rank, const cuuint64_t* dims, const cuuint64_t* strides, const cuuint32_t* box,
            CUtensorMapSwizzle sw = CU_TENSOR_MAP_SWIZZLE_128B, CUtensorMapL2promotion promo = CU_TENSOR_MAP_L2_PROMOTION_NONE) {
    const cuuint32_t es[5] = {1, 1, 1, 1, 1};
    return fn(m, CU_TENSOR_MAP_DATA_TYPE_BFLOAT16, rank, const_cast<void*>(ptr), dims, strides, box, es, CU_TENSOR_MAP_INTERLEAVE_NONE,
              sw, promo, CU_TENSOR_MAP_FLOAT_OOB_FILL_NONE) == CUDA_SUCCESS;
}

}

extern "C" void kernel_launch(void* const* d_in, const int* in_sizes, int n_in, void* d_out, int out_size) {
    (void)in_sizes; (void)n_in; (void)out_size;
    Params prm;
    prm.x = (const __nv_bfloat16*)d_in[0];
    prm.lam_re = (const __nv_bfloat16*)d_in[1];
    prm.lam_im = (const __nv_bfloat16*)d_in[2];
    prm.b_re = (const __nv_bfloat16*)d_in[3];
    prm.b_im = (const __nv_bfloat16*)d_in[4];
    prm.c_re = (const __nv_bfloat16*)d_in[5];
    prm.c_im = (const __nv_bfloat16*)d_in[6];
    prm.log_dt = (const __nv_bfloat16*)d_in[7];
    prm.dskip = (const __nv_bfloat16*)d_in[8];
    prm.w_r = (const __nv_bfloat16*)d_in[10];
    prm.gate_w = (const __nv_bfloat16*)d_in[14];
    prm.out = (float*)d_out;
    cudaGetSymbolAddress((void**)&prm.s, g_scratch);
    int dev = 0, sms = 0;
    cudaGetDevice(&dev);
    cudaDeviceGetAttribute(&sms, cudaDevAttrMultiProcessorCount, dev);
    prm.by_smid = sms == NGRID;
    prm.swapped = prm.b_im < prm.b_re;

    void* fnp = nullptr;
    cudaDriverEntryPointQueryResult qr;
    cudaGetDriverEntryPoint("cuTensorMapEncodeTiled", &fnp, cudaEnableDefault, &qr);
    EncodeFn fn = (EncodeFn)fnp;
    cudaFuncSetAttribute(fused_kernel, cudaFuncAttributeMaxDynamicSharedMemorySize, SMEM_BYTES);

    CUtensorMap mX, mB, mCre, mCim, mWg, mWu, mWd, mXr, mXe;
    const cuuint64_t row = 2048;
    {
        const cuuint64_t dims[4] = {1024, 2, 4, 976}, st[3] = {row, 32 * row, 2 * row};
        const cuuint32_t box[4] = {64, 2, 4, 16};
        encode(fn, &mX, prm.x, 4, dims, st, box, CU_TENSOR_MAP_SWIZZLE_128B, PROMO);
    }
    {
        const char *lo = (const char*)(prm.swapped ? prm.b_im : prm.b_re), *hi = (const char*)(prm.swapped ? prm.b_re : prm.b_im);
        const cuuint64_t dims[5] = {1024, 8, 2, 96, 2}, st[4] = {row, (cuuint64_t)(hi - lo), 8 * row, 256 * row};
        const cuuint32_t box[5] = {64, 8, 2, 4, 2};
        encode(fn, &mB, lo, 5, dims, st, box, CU_TENSOR_MAP_SWIZZLE_128B, PROMO);
    }
    {
        const cuuint64_t dims[5] = {1024, 2, 4, 2, 64}, st[4] = {row, 4 * row, 2 * row, 16 * row};
        const cuuint32_t box[5] = {64, 2, 4, 2, 8};
        encode(fn, &mCre, prm.c_re, 5, dims, st, box);
        encode(fn, &mCim, prm.c_im, 5, dims, st, box);
    }
    {
        const cuuint64_t dims[2] = {F_, D_}, st[1] = {F_ * 2}, dimsd[2] = {D_, F_}, std_[1] = {row};
        const cuuint32_t box[2] = {64, 32}, boxd[2] = {64, 64};
        encode(fn, &mWg, d_in[11], 2, dims, st, box, CU_TENSOR_MAP_SWIZZLE_128B, CU_TENSOR_MAP_L2_PROMOTION_NONE);
        encode(fn, &mWu, d_in[12], 2, dims, st, box, CU_TENSOR_MAP_SWIZZLE_128B, CU_TENSOR_MAP_L2_PROMOTION_NONE);
        encode(fn, &mWd, d_in[13], 2, dimsd, std_, boxd, CU_TENSOR_MAP_SWIZZLE_128B, CU_TENSOR_MAP_L2_PROMOTION_NONE);
    }
    {
        const cuuint64_t dims[3] = {D_ - 192, S_, 4}, st[2] = {row, 128};
        const cuuint32_t box[3] = {64, 16, 4};
        encode(fn, &mXr, prm.x, 3, dims, st, box, CU_TENSOR_MAP_SWIZZLE_128B, CU_TENSOR_MAP_L2_PROMOTION_NONE);
    }
    {
        const cuuint64_t dims[5] = {D_, 2, 2, 2, 976}, st[4] = {64 * row, row, 32 * row, 2 * row};
        const cuuint32_t box[5] = {64, 2, 2, 2, 8};
        encode(fn, &mXe, prm.x, 5, dims, st, box);
    }
    fused_kernel<<<NGRID, 384, SMEM_BYTES, cudaStreamPerThread>>>(prm, mX, mB, mCre, mCim, mWg, mWu, mWd, mXr, mXe);
}
```

```cpp
#include <cuda_runtime.h>
#include <cuda_bf16.h>
#include <cuda.h>
#include <stdint.h>

namespace {

constexpr int S_ = 2048, D_ = 1024, F_ = 3584;
constexpr int NCTA = 128, NGRID = 132;
constexpr int NENT = 64, FIN = 58, XE = 60;
constexpr int NST = 5;
constexpr int RE0 = 4;
constexpr int GU0 = 20;
constexpr uint32_t SLOT = 32768, ABYTES = 8192, WBYTES = 4096;
constexpr uint32_t OFF_XS = NST * SLOT;
constexpr uint32_t OFF_LIST = OFF_XS + 8192;
constexpr uint32_t OFF_W = OFF_XS + 16384;
constexpr uint32_t OFF_STG = OFF_W + 32768;
__host__ __device__ constexpr uint32_t slot_off(int i) { return i < XE ? (i % NST) * SLOT : i == XE ? OFF_W : ((i - 1) % NST) * SLOT; }
__host__ __device__ constexpr uint32_t dn_off(int u) { return u == 0 ? OFF_XS + ABYTES : u < 3 ? OFF_STG + (u - 1) * ABYTES : slot_off(FIN - 2 + u); }
constexpr uint32_t OFF_CONST = OFF_STG;
constexpr uint32_t OFF_RED = OFF_STG + 4096;
constexpr uint32_t OFF_FULL = OFF_STG + 16384;
constexpr uint32_t OFF_EMPTY = OFF_FULL + 120 * 8;
constexpr uint32_t OFF_G = OFF_EMPTY + 88 * 8;
constexpr uint32_t OFF_DK = OFF_G + 256;
constexpr uint32_t OFF_KEYS = OFF_DK + 256;
constexpr uint32_t OFF_SEL = OFF_KEYS + 32;
constexpr uint32_t OFF_FAC = OFF_SEL + 32;
constexpr uint32_t OFF_EPOCH = OFF_FAC + 32;
constexpr uint32_t OFF_PROF = OFF_EPOCH + 16;
constexpr uint32_t SMEM_BYTES = OFF_PROF + 768;
static_assert(SMEM_BYTES <= 232448, "smem");

constexpr uint32_t sb = 1024;
constexpr uint32_t SPIN_LIMIT = 1u << 18;

struct Scratch {
    unsigned int cnt[2 * 32];
    unsigned long long rpack[S_ / 2];
    unsigned long long gpack[S_ / 2];
    uint4 time[NCTA * 2];
    float4 carry[16 * 512];
    uint4 hid[2 * F_];
    uint4 h[8 * 4 * 256 * 64];
};
__device__ __align__(128) Scratch g_scratch;
#define STAMPW(cond, w) do {} while (0)
#define LATE(i, tt) do {} while (0)
#define LANDED(i) do {} while (0)
#define GSTAMP(cond, w) do {} while (0)
#define STAMPIF(cond, i) STAMPW(cond, 72 + (i))
#define STAMP(i) STAMPW(1, 72 + (i))
#define KSTAMP(i) STAMPW((threadIdx.x & 127) == 0, i)

struct Params {
    const __nv_bfloat16 *x, *b_re, *b_im;
    int by_smid;
    int swapped;
    const __nv_bfloat16 *lam_re, *lam_im, *c_re, *c_im, *log_dt, *dskip, *w_r, *gate_w;
    float* out;
    Scratch* s;
};

__device__ __forceinline__ uint32_t smem_u32(const void* p) { return (uint32_t)__cvta_generic_to_shared(p); }
__device__ __forceinline__ void mbar_init(uint32_t bar, uint32_t cnt) { asm volatile("mbarrier.init.shared::cta.b64 [%0], %1;" ::"r"(bar), "r"(cnt) : "memory"); }
__device__ __forceinline__ void mbar_expect_tx(uint32_t bar, uint32_t bytes) { asm volatile("mbarrier.arrive.expect_tx.shared::cta.b64 _, [%0], %1;" ::"r"(bar), "r"(bytes) : "memory"); }
__device__ __forceinline__ void mbar_arrive(uint32_t bar) { asm volatile("mbarrier.arrive.shared::cta.b64 _, [%0];" ::"r"(bar) : "memory"); }
__device__ __forceinline__ void mbar_wait(uint32_t bar, uint32_t parity = 0) {
    asm volatile("{ .reg .pred p; .reg .u32 n;\n"
                 "mbarrier.try_wait.parity.shared::cta.b64 p, [%0], %1;\n"
                 "@p bra.uni DONE;\n"
                 "mov.u32 n, 0;\n"
                 "AGAIN: mbarrier.try_wait.parity.shared::cta.b64 p, [%0], %1;\n"
                 "@p bra.uni DONE;\n"
                 "add.u32 n, n, 1;\n"
                 "setp.lt.u32 p, n, %2;\n"
                 "@p bra.uni AGAIN;\n"
                 "trap;\n"
                 "DONE: }" ::"r"(bar), "r"(parity), "n"(SPIN_LIMIT) : "memory");
}
__device__ __forceinline__ bool elect_one() {
    uint32_t pred;
    asm volatile("{ .reg .pred P; elect.sync _|P, 0xffffffff; selp.b32 %0, 1, 0, P; }" : "=r"(pred));
    return pred;
}
__device__ __forceinline__ void named_bar(int id, int n) { asm volatile("bar.sync %0, %1;" ::"r"(id), "r"(n) : "memory"); }

#define ONE "{ .reg .pred e; elect.sync _|e, 0xffffffff;\n@e "
template <int N> __device__ __forceinline__ void mbar_init_n(uint32_t bar, uint32_t cnt) {
    if (elect_one()) {
#pragma unroll
        for (int i = 0; i < N; i++) mbar_init(bar + 8 * i, cnt);
        asm volatile("fence.mbarrier_init.release.cluster;" ::: "memory");
    }
    __syncwarp();
}
__device__ __forceinline__ void bulk_load(uint32_t dst, const void* src, uint32_t bytes, uint32_t bar) {
    asm volatile(ONE "cp.async.bulk.shared::cluster.global.mbarrier::complete_tx::bytes [%0], [%1], %2, [%3]; }" ::"r"(dst), "l"(src), "r"(bytes), "r"(bar) : "memory");
}
__device__ __forceinline__ void sts128(uint32_t a, uint32_t x, uint32_t y, uint32_t z, uint32_t w) {
    asm volatile("st.shared.v4.u32 [%0], {%1,%2,%3,%4};" ::"r"(a), "r"(x), "r"(y), "r"(z), "r"(w) : "memory");
}
__device__ __forceinline__ uint2 lds64(uint32_t a) {
    uint2 v;
    asm volatile("ld.shared.v2.u32 {%0,%1}, [%2];" : "=r"(v.x), "=r"(v.y) : "r"(a) : "memory");
    return v;
}
__device__ __forceinline__ uint32_t clk32() { uint32_t c; asm volatile("mov.u32 %0, %%clock;" : "=r"(c)); return c; }
__device__ __forceinline__ void gap() { asm volatile("pmevent 1;" ::: "memory"); }
__device__ __forceinline__ void pace_until(uint32_t t) { while ((int)(clk32() - t) < 0) {} }
#define SLEEP_MARGIN 200
__device__ __forceinline__ void sleep_until(uint32_t t) {
    while ((int)(clk32() + SLEEP_MARGIN - t) < 0) __nanosleep(40);
    pace_until(t);
}
__device__ __forceinline__ void tma2(uint32_t dst, const CUtensorMap* m, int c0, int c1, uint32_t bar, uint64_t pol) {
    asm volatile(ONE "cp.async.bulk.tensor.2d.shared::cluster.global.mbarrier::complete_tx::bytes.L2::cache_hint [%0], [%1, {%3, %4}], [%2], %5; }"
                 ::"r"(dst), "l"(m), "r"(bar), "r"(c0), "r"(c1), "l"(pol) : "memory");
}
__device__ __forceinline__ void tma3(uint32_t dst, const CUtensorMap* m, int c0, int c1, uint32_t bar) {
    asm volatile(ONE "cp.async.bulk.tensor.3d.shared::cluster.global.mbarrier::complete_tx::bytes [%0], [%1, {%3, %4, %5}], [%2]; }"
                 ::"r"(dst), "l"(m), "r"(bar), "r"(c0), "r"(c1), "r"(0) : "memory");
}
__device__ __forceinline__ void tma4(uint32_t dst, const CUtensorMap* m, int c0, int c3, uint32_t bar) {
    asm volatile(ONE "cp.async.bulk.tensor.4d.shared::cluster.global.mbarrier::complete_tx::bytes [%0], [%1, {%3, %5, %5, %4}], [%2]; }"
                 ::"r"(dst), "l"(m), "r"(bar), "r"(c0), "r"(c3), "r"(0) : "memory");
}
__device__ __forceinline__ void tma5(uint32_t dst, const CUtensorMap* m, int c0, int c4, uint32_t bar) {
    asm volatile(ONE "cp.async.bulk.tensor.5d.shared::cluster.global.mbarrier::complete_tx::bytes [%0], [%1, {%3, %5, %5, %5, %4}], [%2]; }"
                 ::"r"(dst), "l"(m), "r"(bar), "r"(c0), "r"(c4), "r"(0) : "memory");
}
__device__ __forceinline__ void tma5b(uint32_t dst, const CUtensorMap* m, int c0, int c3, uint32_t bar) {
    asm volatile(ONE "cp.async.bulk.tensor.5d.shared::cluster.global.mbarrier::complete_tx::bytes [%0], [%1, {%3, %5, %5, %4, %5}], [%2]; }"
                 ::"r"(dst), "l"(m), "r"(bar), "r"(c0), "r"(c3), "r"(0) : "memory");
}
__device__ __forceinline__ void prefetch_l2(const void* p) {
    asm volatile("cp.async.ca.shared.global.L2::256B [%0], [%1], 4;" ::"r"(sb + OFF_EPOCH + 12), "l"(p) : "memory");
}

__device__ __forceinline__ uint32_t lds32(uint32_t a) {
    uint32_t v;
    asm volatile("ld.volatile.shared.u32 %0, [%1];" : "=r"(v) : "r"(a) : "memory");
    return v;
}
__device__ __forceinline__ uint32_t uni(uint32_t v) { return __shfl_sync(0xffffffffu, v, 0); }   __device__ __forceinline__ uint32_t ld_acquire(const unsigned int* p) {
    uint32_t v;
    asm volatile("ld.acquire.gpu.global.u32 %0, [%1];" : "=r"(v) : "l"(p) : "memory");
    return v;
}
__device__ __forceinline__ void red_release(unsigned int* p) { asm volatile("red.release.gpu.global.add.u32 [%0], 1;" ::"l"(p) : "memory"); }
__device__ __forceinline__ void wait_count(const unsigned int* p, uint32_t target) {
#pragma unroll 1
    for (uint32_t it = 0; it < SPIN_LIMIT; ++it)
        if ((int)(ld_acquire(p) - target) >= 0) return;
    __trap();
}
__device__ __forceinline__ void wait_count_slow(const unsigned int* p, uint32_t target) {
#pragma unroll 1
    for (uint32_t it = 0; it < SPIN_LIMIT; ++it) {
        if ((int)(ld_acquire(p) - target) >= 0) return;
        __nanosleep(200);
    }
    __trap();
}
__device__ __forceinline__ unsigned long long ld_relaxed1(const void* p) {
    unsigned long long v;
    asm volatile("ld.relaxed.gpu.global.b64 %0, [%1];" : "=l"(v) : "l"(p) : "memory");
    return v;
}
__device__ __forceinline__ ulonglong2 ld_relaxed2(const void* p) {
    ulonglong2 v;
    asm volatile("ld.relaxed.gpu.global.v2.b64 {%0, %1}, [%2];" : "=l"(v.x), "=l"(v.y) : "l"(p) : "memory");
    return v;
}
__device__ __forceinline__ void ld_cell(uint32_t (&v)[4], const void* p, bool on = true) {
    asm volatile("{ .reg .pred p; .reg .b64 l, h; .reg .b128 t; setp.ne.u32 p, %5, 0; mov.b64 l, {%0, %1}; mov.b64 h, {%2, %3}; mov.b128 t, {l, h};\n"
                 "@p ld.relaxed.gpu.global.b128 t, [%4]; mov.b128 {l, h}, t; mov.b64 {%0, %1}, l; mov.b64 {%2, %3}, h; }"
                 : "+r"(v[0]), "+r"(v[1]), "+r"(v[2]), "+r"(v[3]) : "l"(p), "r"((uint32_t)on) : "memory");
}
__device__ __forceinline__ void st_cell(void* p, uint32_t a, uint32_t b, uint32_t c, uint32_t d, bool on) {
    asm volatile("{ .reg .pred p; .reg .b64 l, h; .reg .b128 t; setp.ne.u32 p, %5, 0; mov.b64 l, {%1, %2}; mov.b64 h, {%3, %4}; mov.b128 t, {l, h};\n"
                 "@p st.relaxed.gpu.global.b128 [%0], t; }" ::"l"(p), "r"(a), "r"(b), "r"(c), "r"(d), "r"((uint32_t)on) : "memory");
}

__device__ __forceinline__ uint64_t make_desc(uint32_t addr, uint32_t sbo = 1024) {
    return (uint64_t)((addr & 0x3FFFF) >> 4) | ((uint64_t)1 << 16) | ((uint64_t)(sbo >> 4) << 32) | ((uint64_t)1 << 62);
}
__device__ __forceinline__ void wgmma_fence() { asm volatile("wgmma.fence.sync.aligned;" ::: "memory"); }
__device__ __forceinline__ void wgmma_commit() { asm volatile("wgmma.commit_group.sync.aligned;" ::: "memory"); }
template <int N> __device__ __forceinline__ void wgmma_wait() { asm volatile("wgmma.wait_group.sync.aligned %0;" ::"n"(N) : "memory"); }

#define R8(d, i) "+f"(d[i]), "+f"(d[i + 1]), "+f"(d[i + 2]), "+f"(d[i + 3]), "+f"(d[i + 4]), "+f"(d[i + 5]), "+f"(d[i + 6]), "+f"(d[i + 7])
#define R64(d) R8(d, 0), R8(d, 8), R8(d, 16), R8(d, 24), R8(d, 32), R8(d, 40), R8(d, 48), R8(d, 56)
template <int TA>
__device__ __forceinline__ void wgmma_n128(float (&d)[64], uint64_t da, uint64_t db, int scale_d = 1) {
    asm volatile("{ .reg .pred p; setp.ne.b32 p, %66, 0;\n"
                 "wgmma.mma_async.sync.aligned.m64n128k16.f32.bf16.bf16 "
                 "{%0,%1,%2,%3,%4,%5,%6,%7,%8,%9,%10,%11,%12,%13,%14,%15,%16,%17,%18,%19,%20,%21,%22,%23,%24,%25,%26,%27,%28,%29,%30,%31,"
                 "%32,%33,%34,%35,%36,%37,%38,%39,%40,%41,%42,%43,%44,%45,%46,%47,%48,%49,%50,%51,%52,%53,%54,%55,%56,%57,%58,%59,%60,%61,%62,%63}, "
                 "%64, %65, p, 1, 1, %67, 0; }"
                 : R64(d)
                 : "l"(da), "l"(db), "r"(scale_d), "n"(TA));
}
__device__ __forceinline__ void pin4(float (&d)[4]) { asm volatile("" : "+f"(d[0]), "+f"(d[1]), "+f"(d[2]), "+f"(d[3])::"memory"); }
__device__ __forceinline__ void pin64(float (&d)[64]) { asm volatile("" : R64(d)::"memory"); }

template <int TA, int TB = 0>
__device__ __forceinline__ void wgmma_n8(float (&d)[4], uint64_t da, uint64_t db, int scale_d = 1) {
    asm volatile("{ .reg .pred p; setp.ne.b32 p, %7, 0;\n"
                 "wgmma.mma_async.sync.aligned.m64n8k16.f32.bf16.bf16 {%0,%1,%2,%3}, %4, %5, p, 1, 1, %6, %8; }"
                 : "+f"(d[0]), "+f"(d[1]), "+f"(d[2]), "+f"(d[3])
                 : "l"(da), "l"(db), "n"(TA), "r"(scale_d), "n"(TB));
}

__device__ __forceinline__ float bf_lo(uint32_t u) { return __uint_as_float(u << 16); }
__device__ __forceinline__ float bf_hi(uint32_t u) { return __uint_as_float(u & 0xFFFF0000u); }
__device__ __forceinline__ float rbf(float v) { return __bfloat162float(__float2bfloat16_rn(v)); }
__device__ __forceinline__ uint32_t pack_bf(float lo, float hi) {
    uint32_t r;
    asm("cvt.rn.bf16x2.f32 %0, %1, %2;" : "=r"(r) : "f"(hi), "f"(lo));
    return r;
}
__device__ __forceinline__ uint32_t mul_bf2(uint32_t a, uint32_t b) {
    __nv_bfloat162 r = __hmul2(*reinterpret_cast<__nv_bfloat162*>(&a), *reinterpret_cast<__nv_bfloat162*>(&b));
    return *reinterpret_cast<uint32_t*>(&r);
}
__device__ __forceinline__ uint32_t fma_bf2(uint32_t a, uint32_t b, uint32_t c) {
    uint32_t r;
    asm("fma.rn.bf16x2 %0, %1, %2, %3;" : "=r"(r) : "r"(a), "r"(b), "r"(c));
    return r;
}
__device__ __forceinline__ float2 cmul(float2 a, float2 b) { return make_float2(a.x * b.x - a.y * b.y, a.x * b.y + a.y * b.x); }
__device__ __forceinline__ float2 cfma(float2 a, float2 b, float2 c) {
    return make_float2(fmaf(a.x, b.x, fmaf(-a.y, b.y, c.x)), fmaf(a.x, b.y, fmaf(a.y, b.x, c.y)));
}
__device__ __forceinline__ float sigmoidf_(float v) { return __fdividef(1.0f, 1.0f + expf(-v)); }

__device__ __forceinline__ void bulk_prefetch(const void* src, uint32_t bytes) {
    asm volatile(ONE "cp.async.bulk.prefetch.L2.global [%0], %1; }" ::"l"(src), "r"(bytes) : "memory");
}
__device__ __forceinline__ void bulk_store(void* dst, uint32_t src, uint32_t bytes) {
    asm volatile(ONE "cp.async.bulk.global.shared::cta.bulk_group [%0], [%1], %2; }" ::"l"(dst), "r"(src), "r"(bytes) : "memory");
}
__device__ __forceinline__ float4 lds128f(uint32_t a) {
    float4 v;
    asm volatile("ld.shared.v4.f32 {%0,%1,%2,%3}, [%4];" : "=f"(v.x), "=f"(v.y), "=f"(v.z), "=f"(v.w) : "r"(a) : "memory");
    return v;
}
__device__ __forceinline__ void stsm4(uint32_t a, uint32_t x, uint32_t y, uint32_t z, uint32_t w) {
    asm volatile("stmatrix.sync.aligned.m8n8.x4.shared.b16 [%0], {%1,%2,%3,%4};" ::"r"(a), "r"(x), "r"(y), "r"(z), "r"(w) : "memory");
}
__device__ __forceinline__ uint4 ldsm4(uint32_t a) {
    uint4 v;
    asm volatile("ldmatrix.sync.aligned.m8n8.x4.shared.b16 {%0,%1,%2,%3}, [%4];" : "=r"(v.x), "=r"(v.y), "=r"(v.z), "=r"(v.w) : "r"(a) : "memory");
    return v;
}
__device__ __forceinline__ void stg4_unless(float* p, float a, float b, float c, float d, uint32_t skip) {
    asm volatile("{ .reg .pred p; setp.eq.u32 p, %5, 0; @p st.global.v4.f32 [%0], {%1,%2,%3,%4}; }" ::"l"(p), "f"(a), "f"(b), "f"(c), "f"(d), "r"(skip) : "memory");
}
__device__ __forceinline__ void red4(float* p, float a, float b, float c, float d) {
    asm volatile("red.global.add.v4.f32 [%0], {%1,%2,%3,%4};" ::"l"(p), "f"(a), "f"(b), "f"(c), "f"(d) : "memory");
}

#define TT0 3100
#define PER 520
#define PCUT 40
#define PFIN 340
#define PF0 1300
#define PFX_PACE 400
#define PFB_PACE 900
#define PFV 6
#define PFT 0
#define PF1 700
#define T2 400
#define P2 550
#define G0 800
#define R0 2300
#define R_PACE 350
#define W_SHIFT 250
#define PROMO CU_TENSOR_MAP_L2_PROMOTION_L2_256B
#define POLL_S 20
#define ST_TOL 100
#define ST_SHIFT 300
#define CLK_NS 420
#define MARGIN 100
#define BP1 7
#define NDUMP 8
#define DWAIT 0
#define DNE 2
#define XFIRST 0
#define HG0 900
constexpr uint32_t duration(int i) { return PER + (i >= RE0 && i < RE0 + 4 ? 72 : 0) + (i >= GU0 && i < GU0 + 32 ? 36 : 0); }
constexpr uint32_t cmax(uint32_t a, uint32_t b) { return a > b ? a : b; }
constexpr uint32_t issue_time(int i) {
    return i <= NST ? TT0 : i < XE ? issue_time(i - 1) + duration(i - NST) - (i >= FIN - 1 ? PCUT : 0) : issue_time(XE - 1) + cmax((i - XE + 1) * PFIN, (i - XE) * 512);
}
template <int I> struct Sched { static constexpr uint32_t t = issue_time(I); };
template <int LO, int HI, class F>
__device__ __forceinline__ void for_entries(uint32_t base, F body) {
    constexpr uint32_t per = Sched<LO + 1>::t - Sched<LO>::t;
    static_assert(Sched<HI - 1>::t - Sched<LO>::t == (HI - 1 - LO) * per, "period");
    uint32_t tt = base + Sched<LO>::t;
#pragma unroll 1
    for (int i = LO; i < HI; i++) {
        body(i, tt);
        tt += per;
    }
}

struct Ring { uint32_t prev; int slot; };
struct NoHook { __device__ void operator()() const {} };
template <int TA, int SM, class H = NoHook>
__device__ __forceinline__ void run_entries(Ring& r, int lo, int hi, float (&accA)[64], float (&accB)[64], float (&small)[4],
                                            bool fresh = false, bool sfresh = false, H released = H()) {
    const uint64_t d0 = make_desc(sb);
    const bool leader = (threadIdx.x & 31) == 0;
#pragma unroll 1
    for (int i = lo; i < hi; i++) {
        const uint32_t bar = sb + OFF_FULL + 8 * i;
        const uint64_t da = d0 + (uint64_t)(r.slot * (SLOT >> 4));
        const int n = i - (SM == 1 ? RE0 : GU0);
        const uint64_t dw = d0 + (uint64_t)((OFF_W >> 4) + (SM == 1 ? n * 512 : (n & 7) * 256));
        const uint64_t dt8 = d0 + (uint64_t)((OFF_XS >> 4) + (SM == 1 ? n * 64 : (n >> 1) * 64 + (n & 1) * 4));
        r.slot = r.slot == NST - 1 ? 0 : r.slot + 1;
        mbar_wait(bar);
        KSTAMP(i);
        wgmma_fence();
#pragma unroll
        for (int kk = 0; kk < 4; kk++) {
            wgmma_n128<TA>(accA, da + kk * (TA ? 128 : 2), da + 1024 + kk * 2, kk > 0 || !fresh);
            if (SM == 1) wgmma_n8<0>(small, dw + kk * 2, dt8 + kk * 2, kk > 0 || !sfresh);
            if (SM == 2 && (kk & 1)) wgmma_n8<1>(small, dw + (kk >> 1) * 128, dt8 + (kk >> 1) * 2, kk > 1 || !sfresh);
            wgmma_n128<TA>(accB, da + 512 + kk * (TA ? 128 : 2), da + 1024 + kk * 2, kk > 0 || !fresh);
            if (kk == 1) {
                wgmma_commit();
                wgmma_wait<1>();
                if (leader) mbar_arrive(r.prev);
                released();
            }
        }
        wgmma_commit();
        r.prev = bar + (OFF_EMPTY - OFF_FULL);
        fresh = sfresh = false;
    }
}
template <int HALF, int I>
__device__ __forceinline__ void run_small(float (&acc)[64]) {
    const uint64_t da = make_desc(sb) + (slot_off(I) >> 4);
    KSTAMP(I + HALF * (NENT - FIN));
    wgmma_fence();
#pragma unroll
    for (int kk = 0; kk < 4; kk++) wgmma_n128<1>(acc, da + HALF * 512 + kk * 128, da + 1024 + kk * 2, kk > 0 || !(HALF && I == FIN));
    wgmma_commit();
}
template <int V> struct Int { __host__ __device__ constexpr operator int() const { return V; } };
template <int N, class F> __device__ __forceinline__ void static_for(F f) {
    if constexpr (N > 0) { static_for<N - 1>(f); f(Int<N - 1>()); }
}

__global__ void __launch_bounds__(384, 1)
fused_kernel(const __grid_constant__ Params prm, const __grid_constant__ CUtensorMap mX, const __grid_constant__ CUtensorMap mB, const __grid_constant__ CUtensorMap mCre,
             const __grid_constant__ CUtensorMap mCim, const __grid_constant__ CUtensorMap mWg, const __grid_constant__ CUtensorMap mWu,
             const __grid_constant__ CUtensorMap mWd, const __grid_constant__ CUtensorMap mXr, const __grid_constant__ CUtensorMap mXe) {
    extern __shared__ __align__(1024) uint8_t smem[];
    const uint32_t cstart = clk32();
    const int tid = threadIdx.x, lane = tid & 31;
    uint32_t smid;
    asm volatile("mov.u32 %0, %%smid;" : "=r"(smid));
    {
        const uint32_t b = blockIdx.x & 127, r = tid - PFT, o = (r >> 1) * 2048 + (r & 1) * 128;
#define PFS "@q prefetch.global.L2 [%1]; @p prefetch.global.L2 [%0]; @q prefetch.global.L2 [%2];"
        asm volatile("{ .reg .pred p, q; setp.lt.u32 p, %3, 32; setp.lt.u32 q, %3, 8;\n" PFS " }"
                     ::"l"((const char*)prm.x + (b * 32768 + o)), "l"((const char*)prm.b_re + (b * 8192 + o)), "l"((const char*)prm.b_im + (b * 8192 + o)), "r"(r),
                     "r"(sb + OFF_EPOCH + 12) : "memory");
        gap();
        STAMPIF(tid == PFT, 33);
    }
    const int warp = __shfl_sync(0xffffffffu, tid >> 5, 0);
    int cta;
    asm("{ .reg .pred p; .reg .u32 s, a, b, u, q;\n"
                 "mov.u32 s, %3;\n"
                 "and.b32 a, s, 14; shl.b32 a, a, 2; shr.u32 b, s, 4; add.u32 a, a, b;\n"
                 "sub.u32 u, s, 64; shr.u32 u, u, 1; mul.lo.u32 q, u, 37; shr.u32 q, q, 8; shl.b32 u, u, 3; mad.lo.u32 u, q, -55, u; add.u32 u, u, 12;\n"
                 "setp.lt.u32 p, s, 64; selp.u32 a, a, u, p; and.b32 b, s, 1; mad.lo.u32 a, a, 2, b;\n"
                 "setp.lt.u32 p, s, 124; selp.u32 b, 8, -116, p; add.u32 b, b, s; setp.lt.u32 p, s, 120; selp.u32 a, a, b, p;\n"
                 "setp.ne.u32 p, %2, 0; selp.u32 %0, a, %1, p; }" : "=r"(cta) : "r"(blockIdx.x), "r"(prm.by_smid), "r"(smid));
    const int chunk = (cta >> 5) * 4 + ((cta >> 2) & 3);
    const int dt = ((cta >> 4) & 1) * 4 + (cta & 3);
    asm volatile("{ .reg .pred e, p; elect.sync _|e, 0xffffffff; setp.eq.and.u32 p, %0, 5, e;\n"
                 "@p mbarrier.init.shared::cta.b64 [%1], 1; @p mbarrier.init.shared::cta.b64 [%1 + 8], 1;\n"
                 "fence.mbarrier_init.release.cluster; }" ::"r"(warp), "r"(sb + OFF_FULL) : "memory");
    if (warp == 5 && cta < NCTA) {
        tma5b(sb, &mB, 0, dt * 4, sb + OFF_FULL);
        tma4(sb + 2 * ABYTES, &mX, 0, chunk * 64, sb + OFF_FULL);
        STAMP(31);
        tma5b(sb + SLOT, &mB, 64, dt * 4, sb + OFF_FULL + 8);
        tma4(sb + SLOT + 2 * ABYTES, &mX, 64, chunk * 64, sb + OFF_FULL + 8);
    }
    if (cta >= NCTA) {
        if (smem_u32(smem) != sb) __trap();
        if (tid == 0) wait_count_slow(&prm.s->cnt[0], (atomicAdd(&prm.s->cnt[0], 1u) / NGRID + 1) * NGRID);
        return;
    }
    const bool has_gu = cta >= 16;
    constexpr uint32_t full = sb + OFF_FULL, empty = sb + OFF_EMPTY;
    constexpr uint32_t raw = full + 8 * 32;
    constexpr uint32_t bar_xs = full + 8 * 98, bar_dn = full + 8 * 99, bar_xb = full + 8 * 100, bar_xa = full + 8 * 101,
        bar_retry = full + 8 * 102, bar_out = full + 8 * 104;
    constexpr uint32_t bar_base = empty - 64, bar_init3 = empty - 56, bar_rdone = empty - 48, bar_order0 = empty - 40, bar_init2 = empty - 32,
        bar_vec = empty - 24, bar_epoch = empty - 16, bar_dummy = empty - 8, bar_xs0 = empty + 8 * 69,
        bar_zero = empty + 8 * 70, bar_xafree = empty + 8 * 71, bar_order2 = empty + 8 * 72, bar_order3 = empty + 8 * 73, bar_fp = empty + 8 * 74,
        bar_hs = empty + 8 * 75, bar_accb = empty + 8 * 76, bar_xbfree = empty + 8 * 78, bar_fold = empty + 8 * 79, bar_st = empty + 8 * 80,
        bar_order1 = empty + 8 * 67, bar_cand = empty + 8 * 68;

    if (warp == 5) {
        if (lane < 2) mbar_expect_tx(full + 8 * lane, SLOT);
        __syncwarp();
        named_bar(0, 256);
#pragma unroll 1
        for (int i = 2; i < NST; i++) {
            pace_until(cstart + T2 + i * P2);
            tma5b(sb + i * SLOT, &mB, i * 64, dt * 4, full + 8 * i);
            tma4(sb + i * SLOT + 2 * ABYTES, &mX, i * 64, chunk * 64, full + 8 * i);
            STAMPIF(i == 4, 1);
        }
    } else if (warp == 4) {
        mbar_init_n<12>(bar_init2, 4);
        asm volatile("bar.arrive 0, 256;" ::: "memory");
        mbar_init_n<4>(bar_base, 4);
        mbar_init_n<8>(empty + 64, 4);
        *reinterpret_cast<uint2*>(smem + OFF_KEYS + 16) = make_uint2(0, 0);
        asm volatile("bar.arrive 1, 64;" ::: "memory");
        asm volatile("bar.arrive 5, 96;" ::: "memory");
        asm volatile("bar.arrive 6, 96;" ::: "memory");
        mbar_init_n<32>(full + 256, 3);
        if (lane < 2) mbar_arrive(bar_init2);
    } else if ((warp >> 1) == 3) {
        if (warp == 6) {
            mbar_init_n<8>(full + 16, 1);
            if (lane >= 2 && lane < 10) mbar_expect_tx(full + 8 * lane, lane >= RE0 && lane < RE0 + 4 ? SLOT + ABYTES : SLOT);
            __syncwarp();
            asm volatile("bar.arrive 0, 256;" ::: "memory");
        }
        const char* pf0 = (warp & 1) ? (const char*)((cta & 64) ? prm.b_im : prm.b_re) + (cta & 63) * 16384 : (const char*)prm.x + cta * 32768;
        pace_until(cstart + PF1);
        asm volatile("prefetch.global.L2 [%0];" ::"l"(pf0 + (lane & (30 >> (warp & 1) & 30)) * 1024 + (lane & 1) * 128 + 256));
        const int i0 = warp == 6 ? 10 : 21;
        mbar_init_n<11>(full + 8 * i0, 1);
        if (lane >= i0 && lane < i0 + 11) mbar_expect_tx(full + 8 * lane, lane >= GU0 && has_gu ? SLOT + WBYTES : SLOT);
        mbar_init_n<24>(full + 512 + 192 * (warp & 1), 1);
        named_bar(5, 96);
        if (lane == 0) mbar_arrive(bar_init2);
        STAMP(21);
    }
    __syncwarp();

    if (warp >= 8) {
        asm volatile("setmaxnreg.dec.sync.aligned.u32 72;");
        const uint32_t c0 = cstart;
        uint64_t stream;
        asm volatile("createpolicy.fractional.L2::evict_first.b64 %0, 1.0;" : "=l"(stream));
        const CUtensorMap* mw = (cta & 1) ? &mWu : &mWg;
        const int dc = (cta & 15) * 64, dr = (cta >> 4) * 448;
        auto gutile = [&](int i) {
            const int n = i + 3 - GU0;
            if (has_gu) tma2(sb + OFF_W + (n & 7) * WBYTES, mw, (cta >> 1) * 64 - 512, n * 32, full + 8 * (i + 3), stream);
        };
        if (warp == 8) {
            named_bar(0, 256);
            asm volatile("prefetch.tensormap [%0];" ::"l"(&mXr));
#pragma unroll 1
            for (int u = 0; u < 2; u++) {
                sleep_until(c0 + R0 + u * R_PACE);
                tma3(sb + OFF_W + u * ABYTES, &mXr, u * 256, cta * 16, full + 8 * (RE0 + u));
            }
            uint32_t dst = sb, base = c0;
            int i = NST;
#pragma unroll 1
            for (int sg = 0; sg < 5; sg++) {
                if (sg == 1) mbar_wait(bar_init2);
                if (sg == 3) {
                    mbar_wait(bar_base);
                    base = uni(lds32(sb + OFF_EPOCH + 8));
                }
                const int end = (0x20611349 >> (6 * sg)) & 63;
                const uint32_t per = PER + (sg == 1 ? 72 : sg == 4 ? 36 : 0);
                uint32_t tt = base + (sg == 0 ? Sched<NST>::t : sg == 1 ? Sched<9>::t : sg == 2 ? Sched<13>::t : sg == 3 ? Sched<17>::t : Sched<24>::t);
#pragma unroll 1
                for (; i < end; i++) {
                    mbar_wait(empty + 8 * (i - NST));
                    LATE(i, tt);
                    pace_until(tt);
                    tma5b(dst, &mB, (i & 15) * 64, (i >> 4) * 64 + dt * 4, full + 8 * i);
                    tma4(dst + 2 * ABYTES, &mX, (i & 15) * 64, chunk * 64, full + 8 * i);
                    if (i < 7) tma3(sb + OFF_W + (i - 3) * ABYTES, &mXr, (i - 3) * 256, cta * 16, full + 8 * (i + 1));
                    dst = dst == sb + (NST - 1) * SLOT ? sb : dst + SLOT;
                    tt += per;
                }
            }
            const char* hsrc = reinterpret_cast<const char*>(prm.s->h) + (size_t)chunk * 524288;
            auto gemm2 = [&](int i, uint32_t d, int freed, uint32_t tt) {
                if (!(i & 3)) mbar_wait(bar_out + 2 * (i & 28));
                mbar_wait(empty + 8 * freed);
                LATE(i, tt);
                pace_until(tt);
                bulk_load(d, hsrc, 2 * ABYTES, raw + 8 * i);
                tma5(d + 2 * ABYTES, (i & 4) ? &mCim : &mCre, ((i & 3) + ((i >> 1) & 12)) * 64, dt * 8, full + 8 * i);
                hsrc += 2 * ABYTES;
            };
            {
                uint32_t tt = base + Sched<32>::t;
#pragma unroll 1
                for (int u = 0; u < 4; u++) {
                    const CUtensorMap* mc = (u & 1) ? &mCim : &mCre;
                    mbar_wait(bar_out + 8 * u);
#pragma unroll 1
                    for (int col = (u >> 1) * 256; i < 36 + 4 * u; i++, col += 64) {
                        mbar_wait(empty + 8 * (i - NST));
                        LATE(i, tt);
                        pace_until(tt);
                        bulk_load(dst, hsrc, 2 * ABYTES, raw + 8 * i);
                        tma5(dst + 2 * ABYTES, mc, col, dt * 8, full + 8 * i);
                        gutile(i);
                        hsrc += 2 * ABYTES;
                        dst = dst == sb + (NST - 1) * SLOT ? sb : dst + SLOT;
                        tt += PER + 36;
                    }
                }
            }
            for_entries<48, FIN - 1>(base, [&](int i, uint32_t tt) {
                gemm2(i, dst, i - NST, tt);
                const int n = i - GU0 - 29;
                if (n < 0) gutile(i);
                else if ((n & 5) == 1) tma5(sb + OFF_W + (n & 2) * (ABYTES / 2), &mXe, dt * 128 + (n & 2) * 32, chunk * 64, bar_xa);
                else asm volatile(ONE "cp.async.bulk.prefetch.tensor.2d.L2.global [%0, {%1, %2}]; }" ::"l"(&mWd), "r"(dc), "r"(dr + 64 * (n < 4 ? 1 + n / 2 : n - 1)) : "memory");
                dst = dst == sb + (NST - 1) * SLOT ? sb : dst + SLOT;
            });
            static_for<NENT - FIN + 1>([&](auto u) {
                constexpr int i = FIN - 1 + u;
                gemm2(i, sb + slot_off(i), i < XE ? i - NST : i == XE ? 71   : i - NST - 1, base + Sched<i>::t);
            });
            STAMP(4);
        } else if (warp == 9) {
#pragma unroll
            for (int u = 0; u < 8; u++) {
                const int row = (u >> 2) * 4 + (lane >> 3);
                asm volatile("cp.async.cg.shared.global [%0], [%1], 16;" ::"r"(sb + OFF_XS + (u & 3) * 1024 + row * 128 + (((lane & 7) ^ row) << 4)),
                             "l"((const char*)(u < 4 ? prm.w_r : prm.gate_w) + (u & 3) * 512 + lane * 16) : "memory");
            }
            uint32_t ticket = 0;
            if (lane == 0) ticket = atomicAdd(&prm.s->cnt[0], 1u);
            named_bar(1, 64);
            if (lane == 0) *reinterpret_cast<volatile uint32_t*>(smem + OFF_EPOCH) = ticket / NGRID;
            __syncwarp();
            if (lane < 4) mbar_arrive(bar_epoch);
            asm volatile("cp.async.wait_all;" ::: "memory");
            asm volatile("fence.proxy.async.shared::cta;" ::: "memory");
            __syncwarp();
            if (lane < 4) mbar_arrive(bar_vec);
            STAMP(18);
#pragma unroll 1
            for (int i = 4; i < 22; i++) mbar_init_n<4>(empty + 32 * i, 4);
            if (lane < 4) mbar_arrive(bar_init3);
            STAMP(19);
            mbar_wait(bar_cand);
            {
                const uint32_t* list = reinterpret_cast<const uint32_t*>(smem + OFF_LIST);
                const int n = (int)lds32(sb + OFF_KEYS + 16);
#pragma unroll 1
                for (int i0 = 0; i0 < n; i0 += 32) {
                    const uint32_t k = list[i0 + lane];
                    int rank = 0;
#pragma unroll 2
                    for (int o = 0; o < n; o += 4) {
                        const uint4 l4 = *reinterpret_cast<const uint4*>(list + o);
                        rank += (l4.x > k) + (l4.y > k) + (l4.z > k) + (l4.w > k);
                    }
                    if (rank < 8) reinterpret_cast<uint32_t*>(smem + OFF_SEL)[rank] = k;
                }
                __syncwarp();
                STAMP(6);
                const uint32_t key = lds32(sb + OFF_SEL + 4 * (lane & 7)), tok = ~key & 2047u, tag = lds32(sb + OFF_EPOCH) + 1;
                const uint32_t ta = __shfl_sync(0xffffffffu, tok, lane >> 3), tb = __shfl_sync(0xffffffffu, tok, 4 + (lane >> 3));
                const uint32_t da = sb + OFF_XS + (lane >> 3) * 128 + (((lane & 7) ^ (lane >> 3)) << 4), db = (da ^ 64) + 512;
                const char *sa = (const char*)prm.x + ta * 2048 + (lane & 7) * 16, *sc = (const char*)prm.x + tb * 2048 + (lane & 7) * 16;
#pragma unroll
                for (int u = 0; u < 16; u++) {
                    asm volatile("cp.async.cg.shared.global [%0], [%1], 16;" ::"r"(da + u * 1024), "l"(sa + u * 128) : "memory");
                    asm volatile("cp.async.cg.shared.global [%0], [%1], 16;" ::"r"(db + u * 1024), "l"(sc + u * 128) : "memory");
                    if (u == 3) {
                        asm volatile("cp.async.wait_all;" ::: "memory");
                        asm volatile("fence.proxy.async.shared::cta;" ::: "memory");
                        __syncwarp();
                        if (lane < 4) mbar_arrive(bar_xs0);
                        STAMP(17);
                    }
                }
                if ((tok >> 7) == (uint32_t)chunk) {
                    float4* zp = reinterpret_cast<float4*>(prm.out + tok * D_ + dt * 128) + (lane >> 3) * 2;
#pragma unroll
                    for (int u = 0; u < 8; u++) zp[(u >> 1) * 8 + (u & 1)] = make_float4(0.f, 0.f, 0.f, 0.f);
                }
                uint32_t it = 0;
                unsigned long long u;
                do {
                    u = ld_relaxed1(&prm.s->gpack[tok >> 1]);
                    if (++it > SPIN_LIMIT) __trap();
                } while (!__all_sync(0xffffffffu, (uint32_t)(u >> 32) == tag));
                const uint32_t kb = key >> 16;
                const float r = bf_lo((kb & 0x8000u) ? (kb & 0x7FFFu) : (~kb & 0xFFFFu)), gv = (tok & 1) ? bf_hi((uint32_t)u) : bf_lo((uint32_t)u);
                reinterpret_cast<float*>(smem + OFF_FAC)[lane & 7] = rbf(1.0f - gv) * rbf(sigmoidf_(r));
                asm volatile("cp.async.wait_all;" ::: "memory");
                asm volatile("fence.proxy.async.shared::cta;" ::: "memory");
                __syncwarp();
                if (lane == 0) mbar_arrive(bar_xs);
                STAMP(7);
            }
            char* hd = reinterpret_cast<char*>(prm.s->h) + (size_t)chunk * 524288 + (dt >> 1) * 16384 + (dt & 1) * 4096;
            const uint32_t cb = uni(lds32(sb + OFF_EPOCH + 8)) + ST_SHIFT;
            uint32_t tt = cb + Sched<GU0 + 4>::t;
#pragma unroll 1
            for (int np = 0; np < 16; np++) {
                if (!(np & (np & 4 ? 1 : 2))) mbar_wait(bar_st + 4 * (np & 12) + ((np & 3) ? 8 : 0));
                const uint32_t now = clk32() - ST_TOL;
#pragma unroll 1
                while ((int)(tt - now) < 0) tt += PER + 36;
                const uint32_t src = sb + OFF_STG + (np & 3) * 4096;
                pace_until(tt);
                bulk_store(hd, src, 4096);
                asm volatile("cp.async.bulk.commit_group;" ::: "memory");
                if (np & 2) {
                    if (np & 1) asm volatile("cp.async.bulk.wait_group.read 0;" ::: "memory");
                    else asm volatile("cp.async.bulk.wait_group.read 1;" ::: "memory");
                    __syncwarp();
                    if (lane == 0) mbar_arrive(bar_out + 4 * (np & 12) + 8 * (np & 1));
                }
                STAMPIF(np & 2, 8 + ((np >> 1) & 6) + (np & 1));
                hd += (np & 1) ? 65536 - 8192 : 8192;
                tt += PER + 36;
            }
#pragma unroll 1
            for (int u = 0; u < 2; u++) {
                pace_until(tt);
                tma5(sb + OFF_STG + u * ABYTES, &mXe, dt * 128 + u * 64, chunk * 64 + 8, bar_xb);
                tt += PER + 36;
            }
            wait_count(&prm.s->cnt[32], (lds32(sb + OFF_EPOCH) + 1) * NCTA);
            if (lane < 4) mbar_arrive(bar_zero);
            static_for<7>([&](auto u) {
                if (u != 2) mbar_wait(u == 0 ? empty + 8 * (GU0 + 31) : u == 1 ? bar_xbfree : empty + 8 * (FIN - 2 + u));
                if (u < 3) sleep_until(cb + Sched<(u < DNE ? 57 + u : NENT - 1)>::t);
                tma2(sb + dn_off(u), &mWd, dc, dr + u * 64, bar_dn, stream);
            });
            STAMP(27);
        } else {
            const char* pf0 = (warp & 1) ? (const char*)((cta & 64) ? prm.b_im : prm.b_re) + (cta & 63) * 16384 : (const char*)prm.x + cta * 32768;
            pf0 += lane * 2048;
#pragma unroll 1
            for (int k = 2; k < 8; k++) {
                sleep_until(c0 + PF0 + (k - 1) * ((warp & 1) ? PFB_PACE : PFX_PACE));
                if (lane < (16 >> (warp & 1))) prefetch_l2(pf0 + k * 256);
            }
            named_bar(6, 96);
            if (warp == 10) {
                const char* pb = (const char*)((cta & 64) ? prm.b_im : prm.b_re) + (cta & 63) * 16384;
                static_for<12>([&](auto k) {
                    sleep_until(c0 + Sched<BP1 + k>::t + ST_SHIFT);
                    bulk_prefetch((k < 4 ? pb + 1048576 : (const char*)(k < 8 ? prm.c_re : prm.c_im) + cta * 16384) + (k & 3) * 4096, 4096);
                    if (k == 4) { mbar_wait(bar_init2); mbar_wait(bar_init3); }
                    if (k >= 4 && lane < 8) mbar_expect_tx(full + 8 * (8 * k + lane), 8 * k + lane < GU0 + 32 && has_gu ? 2 * ABYTES + WBYTES : 2 * ABYTES);
                });
                asm volatile("prefetch.tensormap [%0];" ::"l"(&mCre));
                asm volatile("prefetch.tensormap [%0];" ::"l"(&mCim));
                asm volatile("prefetch.tensormap [%0];" ::"l"(&mWd));
                asm volatile("prefetch.tensormap [%0];" ::"l"(&mXe));
                if (lane < 3) mbar_expect_tx(bar_dn + 8 * lane, lane ? 2 * ABYTES : 7 * ABYTES);
                mbar_wait(bar_xs);
                mbar_wait(bar_st);
                if (lane == 0) red_release(&prm.s->cnt[32]);
                __syncwarp();
                STAMP(22);
            } else {
                asm volatile("prefetch.tensormap [%0];" ::"l"(mw));
                mbar_wait(bar_base);
                const uint32_t cb = uni(lds32(sb + OFF_EPOCH + 8)) + W_SHIFT;
                auto early = [&](int i, uint32_t tt) {
                    mbar_wait(empty + 8 * (i - NST));
                    pace_until(tt);
                    gutile(i);
                };
                for_entries<GU0 - 3, GU0 + 4>(cb, early);
                for_entries<GU0 + 4, 32>(cb, early);
            }
            mbar_wait(bar_epoch);
            const uint32_t t2 = lds32(sb + OFF_EPOCH) + 1, tagw = (t2 & 1) | ((t2 & 2) << 15), half = (warp & 1) * ABYTES;
            const uint32_t lo = half + lane * 32 + (lane & 4) * 4 + (lane >> 3) * 4, retry = bar_retry + (warp & 1) * 8;
            const bool leader = lane == 0;
            uint32_t slot = sb + (32 % NST) * SLOT, rpar = 0;
#pragma unroll 1
            for (int i = 32; i < NENT; i++) {
                const uint32_t src = i == XE ? sb + OFF_W : slot;
                if (i != XE) slot = slot == sb + (NST - 1) * SLOT ? sb : slot + SLOT;
                auto current = [&]() {
                    uint32_t v[8];
#pragma unroll
                    for (int u = 0; u < 8; u++) v[u] = lds32(src + lo + u * 1024);
#pragma unroll
                    for (int u = 0; u < 8; u += 2) asm("lop3.b32 %0, %0, %1, %2, 0x7e;" : "+r"(v[u]) : "r"(v[u + 1]), "r"(tagw));
                    return __all_sync(0xffffffffu, ((v[0] | v[2] | v[4] | v[6]) & 0x00010001u) == 0);
                };
                mbar_wait(raw + 8 * i);
                if (!current()) {
#pragma unroll 1
                    for (uint32_t it = 0;; it++) {
                        if (it > SPIN_LIMIT) __trap();
                        STAMP(16);
                        if (leader) mbar_expect_tx(retry, ABYTES);
                        bulk_load(src + half, reinterpret_cast<const char*>(prm.s->h) + (size_t)chunk * 524288 + (i - 32) * 16384 + half, ABYTES, retry);
                        mbar_wait(retry, rpar);
                        rpar ^= 1;
                        if (current()) break;
                    }
                }
                if (leader) mbar_arrive(full + 8 * i);
            }
        }
    } else {
        asm volatile("setmaxnreg.inc.sync.aligned.u32 216;");
        const int wg = warp >> 2, w = warp & 3, g = lane >> 2, c = lane & 3, at = tid & 127;
        float facc[4];
        float2 a[2], m0[2], a32[2], a128[2];
        auto load_const = [&]() {
            const float2* cp = reinterpret_cast<const float2*>(smem + OFF_CONST) + wg * 64 + w * 8 + g;
#pragma unroll
            for (int h = 0; h < 2; h++) { a[h] = cp[32 * h]; m0[h] = cp[128 + 32 * h]; a32[h] = cp[256 + 32 * h]; a128[h] = cp[384 + 32 * h]; }
        };
        if (wg == 0) {
            named_bar(0, 256);
            STAMPIF(tid == 0, 20);
        } else {
            const int pc = (at >> 5) * 256 + dt * 32 + (at & 31);
            const float lr = __bfloat162float(prm.lam_re[pc]), li = __bfloat162float(prm.lam_im[pc]), ld = __bfloat162float(prm.log_dt[pc]);
            const uint32_t dk = __ldg(reinterpret_cast<const uint32_t*>(prm.dskip + dt * 128) + (at & 63));
#pragma unroll
            for (int i = 0; i < 4; i++) sts128(sb + OFF_LIST + i * 2048 + at * 16, 0u, 0u, 0u, 0u);

            {
                reinterpret_cast<uint32_t*>(smem + OFF_DK)[at & 63] = dk;
                const float dtv = rbf(expf(ld));
                const float er = expf(dtv * lr);
                float sn, cs;
                sincospif(dtv * li * 0.318309886183790672f, &sn, &cs);
                const float ar = er * cs, ai = er * sn;
                const float nr = ar - 1.0f, ni = ai;
                const bool big = fabsf(lr) >= fabsf(li);
                const float t = (big ? li : lr) / (big ? lr : li), dn = big ? lr + li * t : lr * t + li;
                const float cr = (big ? nr + ni * t : nr * t + ni) / dn, ci = (big ? ni - nr * t : ni * t - nr) / dn;
                float2* cp = reinterpret_cast<float2*>(smem + OFF_CONST) + at;
                float2 pw = make_float2(ar, prm.swapped ? ai : -ai);
                cp[0] = pw;
                cp[128] = make_float2(prm.swapped ? -2.f * cr : 2.f * cr, -2.f * ci);
#pragma unroll
                for (int i = 1; i <= 7; i++) {
                    pw = cmul(pw, pw);
                    if (i == 5) cp[256] = pw;
                    if (i == 7) cp[384] = pw;
                }
                __syncwarp();
            }
            named_bar(2, 128);
            load_const();
            mbar_wait(bar_epoch);
            const uint32_t tag = *reinterpret_cast<volatile uint32_t*>(smem + OFF_EPOCH) + 1;
            st_cell(&prm.s->carry[(chunk >> 2) * 2048 + ((w & 1) * 256 + dt * 32 + lane) * 4 + (chunk & 3)], tag + 2, 0, 0, 0, w < 2);
            if (w == 2) st_cell(lane < 4 ? (uint4*)prm.s->rpack + cta * 4 + lane : lane < 8 ? (uint4*)prm.s->gpack + cta * 4 + lane - 4 : prm.s->time + cta * 2 + (lane & 1), 0, 0, 0, 0, lane < 10);
            {
                const uint32_t nt = ((tag & 1) | ((tag & 2) << 15)) ^ 0x00010001u;
                st_cell(prm.s->hid + (cta & 1) * F_ + (cta >> 1) * 64 - 512 + (at & 63), nt, nt, nt, nt, has_gu && w >= 2);
            }
            named_bar(2, 128);
            STAMPIF(lane == 0, 52);
            mbar_wait(bar_rdone);

            const uint32_t tpub = clk32();
            if (w == 2) {
                uint32_t gnow;
                asm volatile("mov.u32 %0, %%globaltimer_lo;" : "=r"(gnow));
                st_cell(prm.s->time + cta * 2, tag, tpub, gnow, 0, lane == 0);
            }
            if (w < 2) {
                const float2* red = reinterpret_cast<const float2*>(smem + OFF_RED) + w * 8 + (lane & 7);
                const float2 r0 = red[0], r1 = red[16], r2 = red[32], r3 = red[48];
                const float v0 = (r0.x + r1.x) + (r2.x + r3.x), v1 = (r0.y + r1.y) + (r2.y + r3.y);
                uint32_t pk2;
                if (w == 0) {
                    pk2 = pack_bf(v0, v1);
                    pk2 ^= (((pk2 >> 15) & 0x00010001u) * 0x7FFFu) ^ 0x80008000u;
                } else pk2 = pack_bf(sigmoidf_(rbf(v0)), sigmoidf_(rbf(v1)));
                if (lane < 8) asm volatile("st.relaxed.gpu.global.b64 [%0], %1;" ::"l"((w ? prm.s->gpack : prm.s->rpack) + cta * 8 + lane), "l"(((unsigned long long)tag << 32) | pk2) : "memory");
                __syncwarp();
            }
            STAMPIF(at == 0, 24);
            uint32_t it = 0, pr[8], g1, tm[4] = {};
            sleep_until(tpub + G0);
            while (true) {
                bool ok = true;
#pragma unroll
                for (int k = 0; k < 4; k++) {
                    const ulonglong2 u = ld_relaxed2(&prm.s->rpack[k * 256 + 2 * at]);
                    ok = ok && (uint32_t)(u.x >> 32) == tag && (uint32_t)(u.y >> 32) == tag;
                    pr[2 * k] = (uint32_t)u.x; pr[2 * k + 1] = (uint32_t)u.y;
                }
                const unsigned long long u1 = ld_relaxed1(&prm.s->gpack[chunk * 64 + (at & 63)]);
                ok = ok && (uint32_t)(u1 >> 32) == tag;
                g1 = (uint32_t)u1;
                ld_cell(tm, prm.s->time + at * 2);
                ok = ok && tm[0] == tag;
                if (__all_sync(0xffffffffu, ok)) break;
                if (++it > SPIN_LIMIT) __trap();
            }
            STAMPIF(lane == 0, 25);
            uint32_t m = __vmaxu2(__vimax3_u16x2(__vimax3_u16x2(pr[0], pr[1], pr[2]), pr[3], pr[4]), __vimax3_u16x2(pr[5], pr[6], pr[7]));
            m = (max(m, m << 16) & 0xFFFF0000u) | (uint32_t)lane;
            const uint32_t m1 = __reduce_max_sync(0xffffffffu, m), m2 = __reduce_max_sync(0xffffffffu, m == m1 ? 0u : m);
            uint32_t* keys = reinterpret_cast<uint32_t*>(smem + OFF_KEYS);
            const uint32_t g0 = uni(tm[2]), glast = g0 + (uint32_t)__reduce_max_sync(0xffffffffu, (int)(tm[2] - g0));
            if (lane == 0) { keys[w] = m2; reinterpret_cast<uint32_t*>(smem + OFF_XS + 1024)[w] = glast; }
            reinterpret_cast<uint2*>(smem + OFF_XS)[at] = make_uint2(tm[1], tm[2]);
            sts128(sb + OFF_XS + 4096 + at * 16, pr[0], pr[1], pr[2], pr[3]);
            sts128(sb + OFF_XS + 6144 + at * 16, pr[4], pr[5], pr[6], pr[7]);
            *reinterpret_cast<uint32_t*>(smem + OFF_G + 4 * (at & 63)) = g1;
            mbar_wait(bar_init3);
            named_bar(2, 128);
            if (w == 3) {
                const uint4 g4 = *reinterpret_cast<const uint4*>(smem + OFF_XS + 1024);
                const uint2* tt = reinterpret_cast<const uint2*>(smem + OFF_XS);
                const uint2 own = tt[cta];
                uint2 ref = tt[cta & ~15];
                if ((uint32_t)(ref.x - own.x - (((int)(ref.y - own.y) * CLK_NS) >> 8) + 400) >= 800u) ref = tt[cta & ~1];
                const int last = max(max((int)(g4.x - ref.y), (int)(g4.y - ref.y)), max((int)(g4.z - ref.y), (int)(g4.w - ref.y)));
                *reinterpret_cast<volatile uint32_t*>(smem + OFF_EPOCH + 8) = ref.x + ((min(last, 4000) * CLK_NS) >> 8) + MARGIN - Sched<RE0 + 8>::t;
                if (lane < 4) mbar_arrive(bar_base);
                STAMP(23);
            }
            __syncwarp();
            const uint4 th4 = *reinterpret_cast<const uint4*>(keys);
            const uint32_t th = (max(min(min(th4.x, th4.y), min(th4.z, th4.w)) >> 16, 1u) - 1u) * 0x00010001u;
            uint32_t mask = 0;
#pragma unroll
            for (int k = 7; k >= 0; k--) mask = mask * 2 + __vminu2(__vmaxu2(pr[k], th) ^ th, 0x00010001u);
            uint32_t pos = 0;
            asm volatile("{ .reg .pred p; setp.ne.u32 p, %2, 0; @p atom.shared.add.u32 %0, [%1], %2; }" : "+r"(pos) : "r"(sb + OFF_KEYS + 16), "r"(__popc(mask)) : "memory");
            while (mask) {
                const int bit = __ffs(mask) - 1, k = bit & 7, hi = bit >> 4;
                mask &= mask - 1;
                const uint32_t sc = *reinterpret_cast<const uint16_t*>(smem + OFF_XS + 4096 + (k >> 2) * 2048 + at * 16 + (k & 3) * 4 + hi * 2);
                *reinterpret_cast<uint32_t*>(smem + OFF_LIST + 4 * pos++) = (sc << 16) | (0x8000u + 2047u - (uint32_t)((k >> 1) * 512 + 4 * at + 2 * (k & 1) + hi));
            }
            __syncwarp();
            if (lane == 0) mbar_arrive(bar_cand);
            STAMPIF(lane == 0, 26);
            mbar_wait(bar_order0);
        }

        float accA[64], accB[64];
        Ring ring = {bar_dummy, wg};
        {
            static_assert(GU0 - 16 == RE0, "segments");
            run_entries<0, 0>(ring, wg * 16, wg * 16 + RE0, accA, accB, facc, true);
            if (wg == 0) {
                float racc[4];
                mbar_wait(bar_vec);
                run_entries<0, 1>(ring, RE0, RE0 + 4, accA, accB, racc, false, true);
                mbar_wait(bar_init2);
                const uint32_t red = sb + OFF_RED + 4 * (w * 32 + (c >> 1) * 16 + g);
                run_entries<0, 0>(ring, RE0 + 4, RE0 + 5, accA, accB, facc, false, false, [&]() {
                    pin4(racc);
                    asm volatile("{ .reg .pred p; setp.ne.u32 p, %3, 0; @p st.shared.f32 [%0], %1; @p st.shared.f32 [%0 + 32], %2; }" ::"r"(red),
                                 "f"((w & 1) ? racc[1] : racc[0]), "f"((w & 1) ? racc[3] : racc[2]), "r"((uint32_t)((c & 1) == (w >> 1))) : "memory");
                    __syncwarp();
                    if (lane == 0) mbar_arrive(bar_rdone);
                    STAMPIF(lane == 0, 5);
                });
                run_entries<0, 0>(ring, RE0 + 5, 16, accA, accB, facc);
                if (lane == 0) mbar_arrive(bar_order0);
                mbar_wait(bar_base);
                load_const();
                named_bar(3, 128);
            } else {
#pragma unroll
                for (int u = 0; u < 2; u++) {
                    mbar_wait(u ? bar_xs : bar_xs0);
                    run_entries<0, 2>(ring, GU0 + 8 * u, GU0 + 8 + 4 * u, accA, accB, facc, false, u == 0);
                }
                if (lane == 0) mbar_arrive(bar_order1);
            }
        }
        const uint32_t tag = *reinterpret_cast<volatile uint32_t*>(smem + OFF_EPOCH) + 1;
        const float2 a64[2] = {cmul(a32[0], a32[0]), cmul(a32[1], a32[1])};
        wgmma_wait<0>();
        pin64(accA); pin64(accB); pin4(facc);
        if (lane == 0) mbar_arrive(ring.prev);
        STAMPIF(at == 0, 28 + wg);
        GSTAMP(tid == 0, 1);

        const int tl = 32 * (g >> 1) + (g & 1) + 4 * w + 16 * wg, t0 = chunk * 128 + tl;
        float* op = prm.out + (size_t)t0 * D_ + dt * 128 + 4 * c;
        uint2 xv[8][2], dk[8];
        uint32_t gp[2], om[2], routed[2];
        auto row_setup = [&]() {
            const uint4 sa = *reinterpret_cast<const uint4*>(smem + OFF_SEL), sc = *reinterpret_cast<const uint4*>(smem + OFF_SEL + 16);
#pragma unroll
            for (int r = 0; r < 2; r++) {
                const uint32_t id = 0x8000u + 2047u - (uint32_t)(t0 + 2 * r);
                routed[r] = (uint16_t)sa.x == id || (uint16_t)sa.y == id || (uint16_t)sa.z == id || (uint16_t)sa.w == id ||
                            (uint16_t)sc.x == id || (uint16_t)sc.y == id || (uint16_t)sc.z == id || (uint16_t)sc.w == id;
                gp[r] = reinterpret_cast<const uint16_t*>(smem + OFF_G)[tl + 2 * r] * 0x00010001u;
                om[r] = pack_bf(1.0f - bf_hi(gp[r]), 1.0f - bf_hi(gp[r]));
            }
#pragma unroll
            for (int j = 0; j < 8; j++) dk[j] = lds64(sb + OFF_DK + 32 * j + 8 * c);
        };
        auto release = [&](uint32_t bar) {
            asm volatile("fence.proxy.async.shared::cta;" ::: "memory");
            __syncwarp();
            if (lane == 0) mbar_arrive(bar);
        };

        {
            const uint32_t t2 = tag & 3u;
            float4* cslot = &prm.s->carry[(wg * 256 + dt * 32 + w * 8 + g) * 4];
            float2 e[2], w0[2];
#pragma unroll
            for (int h = 0; h < 2; h++) {
                float (&acc)[64] = h ? accB : accA;
                const float2 a1 = make_float2(a[h].x, -a[h].y);
                e[h] = make_float2(acc[0], acc[2]);
#pragma unroll
                for (int s = 1; s < 32; s++) {
                    const int i0 = 4 * (s >> 1) + (s & 1);
                    e[h] = cfma(a1, e[h], make_float2(acc[i0], acc[i0 + 2]));
                }
                asm volatile("" : "+f"(e[h].x), "+f"(e[h].y), "+f"(accB[0]), "+f"(accB[2]));
                if (!h) gap();
            }
#pragma unroll
            for (int h = 0; h < 2; h++) {
                e[h] = make_float2(fmaf(m0[h].x, e[h].x, m0[h].y * e[h].y), fmaf(-m0[h].x, e[h].y, m0[h].y * e[h].x));
                float2 y = make_float2(__shfl_up_sync(0xffffffffu, e[h].x, 1, 4), __shfl_up_sync(0xffffffffu, e[h].y, 1, 4));
                if (c >= 1) e[h] = cfma(a32[h], y, e[h]);
                y = make_float2(__shfl_up_sync(0xffffffffu, e[h].x, 2, 4), __shfl_up_sync(0xffffffffu, e[h].y, 2, 4));
                if (c >= 2) e[h] = cfma(a64[h], y, e[h]);
            }
            st_cell(cslot + (chunk >> 2) * 2048 + (chunk & 3), (__float_as_uint(e[0].x) & ~3u) | t2, __float_as_uint(e[0].y), __float_as_uint(e[1].x), __float_as_uint(e[1].y), c == 3);
            gap();
            STAMPIF(lane == 0, 30 + 2 * wg);
            const int j1 = chunk - 1 - c;
            uint32_t v[4][4] = {{t2, 0, 0, 0}, {t2, 0, 0, 0}, {t2, 0, 0, 0}, {t2, 0, 0, 0}};
            auto poll = [&]() {
#pragma unroll
                for (int m = 0; m < 4; m++) ld_cell(v[m], cslot + (j1 >> 2) * 2048 + c - m * 2048, j1 >= 4 * m);
            };
            float2 a512[2], pw128[2], pw32[2];
#pragma unroll
            for (int h = 0; h < 2; h++) {
                float (&acc)[64] = h ? accB : accA;
                w0[h] = make_float2(__shfl_up_sync(0xffffffffu, e[h].x, 1, 4), __shfl_up_sync(0xffffffffu, e[h].y, 1, 4));
                if (c == 0) w0[h] = make_float2(0.f, 0.f);
                const float2 one = make_float2(1.f, 0.f), a256 = cmul(a128[h], a128[h]);
                a512[h] = cmul(a256, a256);
                pw128[h] = cmul((j1 & 1) ? a128[h] : one, (j1 & 2) ? a256 : one);
                pw32[h] = cmul((c & 1) ? a32[h] : one, (c & 2) ? a64[h] : one);
                asm volatile("" : "+f"(a512[h].x), "+f"(a512[h].y), "+f"(pw128[h].x), "+f"(pw128[h].y), "+f"(pw32[h].x), "+f"(pw32[h].y));
                gap();
#pragma unroll
                for (int n = 0; n < 16; n++) {
                    if (16 * h + n == POLL_S) poll();
                    asm volatile("{ .reg .f32 a, b, c, d, n; neg.f32 n, %4; mul.f32 a, %1, %5; mul.f32 b, %0, %5; mul.f32 c, %3, %5; mul.f32 d, %2, %5;\n"
                                 "fma.rn.f32 %0, %0, %4, a; fma.rn.f32 %1, %1, n, b; fma.rn.f32 %2, %2, %4, c; fma.rn.f32 %3, %3, n, d; }"
                                 : "+f"(acc[4 * n]), "+f"(acc[4 * n + 2]), "+f"(acc[4 * n + 1]), "+f"(acc[4 * n + 3]) : "f"(m0[h].x), "f"(m0[h].y));
                    if (n & 1) gap();
                }
            }
            STAMPIF(lane == 0, 34 + 2 * wg);
            {
                uint32_t it = 0;
                while (!__all_sync(0xffffffffu, (((v[0][0] ^ t2) | (v[1][0] ^ t2) | (v[2][0] ^ t2) | (v[3][0] ^ t2)) & 3u) == 0)) {
                    poll();
                    if (++it > SPIN_LIMIT) __trap();
                }
                STAMPIF(lane == 0, 35 + 2 * wg);
#pragma unroll
                for (int h = 0; h < 2; h++) {
                    float2 hin = make_float2(__uint_as_float(v[3][2 * h]), __uint_as_float(v[3][2 * h + 1]));
#pragma unroll
                    for (int m = 2; m >= 0; m--) hin = cfma(a512[h], hin, make_float2(__uint_as_float(v[m][2 * h]), __uint_as_float(v[m][2 * h + 1])));
                    hin = cmul(pw128[h], hin);
                    hin.x += __shfl_xor_sync(0xffffffffu, hin.x, 1); hin.y += __shfl_xor_sync(0xffffffffu, hin.y, 1);
                    hin.x += __shfl_xor_sync(0xffffffffu, hin.x, 2); hin.y += __shfl_xor_sync(0xffffffffu, hin.y, 2);
                    w0[h] = cfma(pw32[h], hin, w0[h]);
                }
            }
            if (wg) mbar_wait(bar_out + 24);
            STAMPIF(lane == 0, 38 + 2 * wg);
            const uint32_t stg = sb + OFF_STG + prm.swapped * 8192 + w * 1024 + (lane & 7) * 128 + (((lane >> 3) ^ (lane & 7)) << 4);
            const uint32_t second = prm.swapped ? -8192 : 8192;
            const uint32_t keep = c == (g >> 1) ? 0xFFFEFFFEu : 0xFFFFFFFFu, tagw = ((t2 & 1) | ((t2 & 2) << 15)) & ~keep;
#pragma unroll
            for (int h = 0; h < 2; h++) {
                float (&acc)[64] = h ? accB : accA;
                uint32_t ra[16], ia[16];
                auto stage = [&](uint32_t (&r)[16], uint32_t base, int j) {
                    stsm4((base ^ ((j & 1) * 64)) + (j >> 1) * 4096, r[4 * j], r[4 * j + 1], r[4 * j + 2], r[4 * j + 3]);
                };
#pragma unroll
                for (int n = 0; n < 16; n++) {
                    const float2 y = cfma(a[h], w0[h], make_float2(acc[4 * n], acc[4 * n + 2]));
                    w0[h] = cfma(a[h], y, make_float2(acc[4 * n + 1], acc[4 * n + 3]));
                    ra[n] = pack_bf(y.x, w0[h].x);
                    ia[n] = pack_bf(y.y, w0[h].y);
                    if (!(n & 1)) { ra[n] = (ra[n] & keep) | tagw; ia[n] = (ia[n] & keep) | tagw; }
                    if (!h && (n & 3) == 3) {
                        if (n == 11) { asm volatile("" : "+r"(ra[n]), "+r"(ia[n])); gap(); release(bar_st + 32 * wg); }
                        stage(ra, stg, n >> 2); stage(ia, stg + second, n >> 2);
                        gap();
                    }
                    if (h && n == 3) { asm volatile("" : "+r"(ra[n]), "+r"(ia[n])); gap(); release(bar_st + 32 * wg + 8); }
                }
                if (h) {
                    STAMPIF(lane == 0, 39 + 2 * wg);
                    mbar_wait(bar_out + 32 * wg);
                    if (prm.swapped) {
#pragma unroll
                        for (int n = 0; n < 16; n++) { const uint32_t t = ra[n]; ra[n] = ia[n]; ia[n] = t; }
                    }
                    const uint32_t st0 = stg - prm.swapped * 8192;
#pragma unroll
                    for (int j = 0; j < 4; j++) stage(ra, st0, j);
                    mbar_wait(bar_xs);
                    row_setup();
                    release(bar_st + 32 * wg + 16);
                    mbar_wait(bar_out + 32 * wg + 8);
#pragma unroll
                    for (int j = 0; j < 4; j++) stage(ia, st0 + 8192, j);
                    release(bar_st + 32 * wg + 24);
                }
                STAMPIF(lane == 0, 42 + 2 * wg + h);
            }
        }

        const uint32_t xr = 2 * (g & 3) + (g >> 2), xa = sb + (wg ? OFF_STG : OFF_W) + (16 * w + xr) * 128 + (((c >> 1) ^ xr) << 4) + (c & 1) * 8;
        auto handover = [&](uint32_t bar) {
            const uint4 z = ldsm4(sb + OFF_KEYS + 16);
            if (lane == 1) mbar_arrive(bar + z.x);
        };
        auto load_x = [&](int j0, int j1) {
#pragma unroll
            for (int j = j0; j < j1; j++)
#pragma unroll
                for (int r = 0; r < 2; r++) xv[j][r] = lds64((xa ^ (32 * (j & 3))) + (j >> 2) * ABYTES + r * 1024);
        };
        auto skip_term = [&](int j0, int j1) {
#pragma unroll
            for (int j = j0; j < j1; j++)
#pragma unroll
                for (int r = 0; r < 2; r++) {
                    xv[j][r].x = mul_bf2(xv[j][r].x, fma_bf2(gp[r], dk[j].x, om[r]));
                    xv[j][r].y = mul_bf2(xv[j][r].y, fma_bf2(gp[r], dk[j].y, om[r]));
                    asm volatile("" : "+r"(xv[j][r].x), "+r"(xv[j][r].y));
                }
        };
        auto finish = [&](float (&acc)[64], int j, bool gaps) {
#pragma unroll
            for (int r = 0; r < 2; r++) {
                const int o = 8 * j + 2 * r;
                const float gv = bf_hi(gp[r]);
                acc[o] = fmaf(gv, acc[o], bf_lo(xv[j][r].x)); acc[o + 1] = fmaf(gv, acc[o + 1], bf_hi(xv[j][r].x));
                acc[o + 4] = fmaf(gv, acc[o + 4], bf_lo(xv[j][r].y)); acc[o + 5] = fmaf(gv, acc[o + 5], bf_hi(xv[j][r].y));
                stg4_unless(op + r * 2 * D_ + 16 * j, acc[o], acc[o + 1], acc[o + 4], acc[o + 5], routed[r]);
                if (gaps) gap();
            }
        };
        auto finish_routed = [&](float (&acc)[64]) {
#pragma unroll
            for (int r = 0; r < 2; r++)
                if (routed[r]) {
#pragma unroll
                    for (int j = 0; j < 8; j++) red4(op + r * 2 * D_ + 16 * j, acc[8 * j + 2 * r], acc[8 * j + 2 * r + 1], acc[8 * j + 2 * r + 4], acc[8 * j + 2 * r + 5]);
                }
            __syncwarp();
        };
        const uint32_t xbuf = sb + slot_off(FIN) + w * 2048 + lane * 16;

        if (wg == 1) {
            float outB[64];
            const uint32_t tagw = (tag & 1) | ((tag & 2) << 15);
            mbar_wait(bar_fp);
            {
                const float4 o4 = lds128f(sb + OFF_XS + at * 16);
                const float o[4] = {o4.x, o4.y, o4.z, o4.w};
                float v[4];
#pragma unroll
                for (int u = 0; u < 4; u++) {
                    v[u] = rbf(facc[u] + o[u]);
                    if (!(cta & 1)) v[u] = __fdividef(v[u], 1.0f + __expf(-v[u]));
                }
                uint32_t w0 = pack_bf(v[0], v[1]), w1 = pack_bf(v[2], v[3]), cell[4];
                if (c == (g & 3)) { w0 = (w0 & 0xFFFEFFFEu) | tagw; w1 = (w1 & 0xFFFEFFFEu) | tagw; }
#pragma unroll
                for (int u = 0; u < 4; u++) {
                    const uint32_t s0 = __shfl_sync(0xffffffffu, w0, u, 4), s1 = __shfl_sync(0xffffffffu, w1, u, 4);
                    cell[u] = (c & 1) ? s1 : s0;
                }
                st_cell(prm.s->hid + (cta & 1) * F_ + (cta >> 1) * 64 - 512 + w * 16 + g + 8 * c, cell[0], cell[1], cell[2], cell[3], has_gu && c < 2);
            }
            const uint32_t tpub = clk32();
            STAMPIF(lane == 0, 47);
            mbar_wait(bar_xb);
            load_x(0, 8);
            release(bar_xbfree);
            skip_term(0, 8);
            STAMPIF(lane == 0, 46);
            named_bar(2, 128);
            {
                uint32_t hv[4][4] = {}, hu[4][4] = {}, it = 0;
                sleep_until(tpub + HG0);
                while (true) {
                    uint32_t bad = 0;
#pragma unroll
                    for (int i = 0; i < 4; i++) {
                        const uint4* hp = prm.s->hid + (cta >> 4) * 448 + (i < 3 ? i * 128 + at : 384 + (at & 63));
                        ld_cell(hv[i], hp); ld_cell(hu[i], hp + F_);
                    }
#pragma unroll
                    for (int i = 0; i < 4; i++)
                        bad |= (((c & 2) ? ((c & 1) ? hv[i][3] : hv[i][2]) : ((c & 1) ? hv[i][1] : hv[i][0])) ^ tagw) |
                               (((c & 2) ? ((c & 1) ? hu[i][3] : hu[i][2]) : ((c & 1) ? hu[i][1] : hu[i][0])) ^ tagw);
                    if (__all_sync(0xffffffffu, (bad & 0x00010001u) == 0)) break;
                    if (++it > SPIN_LIMIT) __trap();
                }
                STAMPIF(lane == 0, 48);
#pragma unroll
                for (int i = 0; i < 4; i++)
                    sts128(sb + OFF_XS + 16 * (i < 3 ? i * 128 + at : 384 + (at & 63)), mul_bf2(hv[i][0], hu[i][0]), mul_bf2(hv[i][1], hu[i][1]),
                           mul_bf2(hv[i][2], hu[i][2]), mul_bf2(hv[i][3], hu[i][3]));
                asm volatile("fence.proxy.async.shared::cta;" ::: "memory");
                __syncwarp();
                if (lane == 0) mbar_arrive(bar_hs);
                STAMPIF(lane == 0, 49);
            }
            mbar_wait(bar_order2);
            static_for<NENT - FIN>([&](auto u) {
                run_small<1, FIN + u>(outB);
                if (u == 2) { wgmma_wait<2>(); if (lane == 0) mbar_arrive(bar_fold); }
            });
            if (lane == 0) mbar_arrive(bar_order3);
            wgmma_wait<0>();
            pin64(outB);
            KSTAMP(2 * NENT - FIN);
            STAMPIF(at == 0, 50);
#pragma unroll
            for (int q = 0; q < 2; q++) {
                uint4 pb[8];
                mbar_wait(bar_accb + 8 * q);
#pragma unroll
                for (int v = 0; v < 8; v++) pb[v] = ldsm4(xbuf + (2 * q + (v >> 2)) * ABYTES + (v & 3) * 512);
#pragma unroll
                for (int v = 0; v < 8; v++) {
                    const int o = 32 * q + 4 * v;
                    outB[o] += __uint_as_float(pb[v].x); outB[o + 1] += __uint_as_float(pb[v].y);
                    outB[o + 2] += __uint_as_float(pb[v].z); outB[o + 3] += __uint_as_float(pb[v].w);
                    if (v & 1) finish(outB, 4 * q + (v >> 1), false);
                }
            }
            finish_routed(outB);
            STAMPIF(lane == 0, 51);
        } else {
            float outA[64], outB[64], gacc[4];
            ring.slot = 32 % NST;
            ring.prev = bar_dummy;
            mbar_wait(bar_order1);
            run_entries<1, 2>(ring, 32, GU0 + 32, outA, outB, gacc, true, true);
            run_entries<1, 0>(ring, GU0 + 32, GU0 + 33, outA, outB, gacc, false, false, [&]() {
                pin4(gacc);
                sts128(sb + OFF_XS + at * 16, __float_as_uint(gacc[0]), __float_as_uint(gacc[1]), __float_as_uint(gacc[2]), __float_as_uint(gacc[3]));
                __syncwarp();
                if (lane == 0) mbar_arrive(bar_fp);
            });
            mbar_wait(bar_xa);
            run_entries<1, 0>(ring, GU0 + 33, GU0 + 34, outA, outB, gacc, false, false, [&]() { load_x(0, 2); });
            load_x(2, 4);
            run_entries<1, 0>(ring, GU0 + 34, GU0 + 35, outA, outB, gacc, false, false, [&]() { load_x(4, 6); });
            load_x(6, 8);
            run_entries<1, 0>(ring, GU0 + 35, GU0 + 36, outA, outB, gacc, false, false, [&]() { release(bar_xafree); });
            run_entries<1, 0>(ring, GU0 + 36, FIN, outA, outB, gacc);
            static_for<NENT - FIN>([&](auto u) {
                mbar_wait(full + 8 * (FIN + u));
                run_small<0, FIN + u>(outA);
                if (u == 5 && lane == 0) mbar_arrive(bar_order2);
                wgmma_wait<1>();
                if (lane == 0) mbar_arrive(empty + 8 * (FIN + u - 1));
                if (u < 4) skip_term(2 * u, 2 * u + 2);
            });
            wgmma_wait<0>();
            pin64(outA); pin64(outB);
            STAMPIF(at == 0, 53);
            GSTAMP(at == 0, 2);
            auto dump = [&](int v) {
                if (v == 4) mbar_wait(bar_fold);
                stsm4(xbuf + (v >> 2) * ABYTES + (v & 3) * 512, __float_as_uint(outB[4 * v]), __float_as_uint(outB[4 * v + 1]), __float_as_uint(outB[4 * v + 2]),
                      __float_as_uint(outB[4 * v + 3]));
                if ((v & 7) == 7) handover(bar_accb + (v & 8));
            };
            mbar_wait(empty + 8 * FIN);
#pragma unroll
            for (int j = 0; j < 8; j++) {
                finish(outA, j, true);
#pragma unroll
                for (int v = j * NDUMP / 8; v < (j + 1) * NDUMP / 8; v++) dump(v);
            }
            STAMPIF(lane == 0, 54);
            if (DWAIT) mbar_wait(bar_order3);
#pragma unroll
            for (int v = NDUMP; v < 16; v++) dump(v);
            STAMPIF(lane == 0, 55);
            finish_routed(outA);
            const uint2 sk = lds64(sb + OFF_SEL + 8 * c), fk = lds64(sb + OFF_FAC + 8 * c);
            float* y0 = prm.out + (~sk.x & 2047u) * D_ + (cta & 15) * 64 + w * 16 + g;
            float* y1 = prm.out + (~sk.y & 2047u) * D_ + (cta & 15) * 64 + w * 16 + g;
            float yacc[4];
            const uint64_t dw = make_desc(sb), dh = (uint64_t)(((sb + OFF_XS) & 0x3FFFF) >> 4) | ((uint64_t)8 << 16) | ((uint64_t)8 << 32);
            mbar_wait(bar_hs);
            mbar_wait(bar_zero);
            mbar_wait(bar_dn);
            mbar_wait(bar_order3);
            STAMPIF(at == 0, 2);
            wgmma_fence();
#pragma unroll
            for (int n = 0; n < 28; n++) wgmma_n8<1, 1>(yacc, dw + (dn_off(n >> 2) >> 4) + (n & 3) * 128, dh + n * 16, n > 0);
            wgmma_commit();
            wgmma_wait<0>();
            pin4(yacc);
            atomicAdd(y0, yacc[0] * __uint_as_float(fk.x)); atomicAdd(y1, yacc[1] * __uint_as_float(fk.y));
            atomicAdd(y0 + 8, yacc[2] * __uint_as_float(fk.x)); atomicAdd(y1 + 8, yacc[3] * __uint_as_float(fk.y));
            STAMPIF(lane == 0, 3);
        }
    }
}

typedef CUresult (*EncodeFn)(CUtensorMap*, CUtensorMapDataType, cuuint32_t, void*, const cuuint64_t*, const cuuint64_t*, const cuuint32_t*,
                             const cuuint32_t*, CUtensorMapInterleave, CUtensorMapSwizzle, CUtensorMapL2promotion, CUtensorMapFloatOOBfill);

bool encode(EncodeFn fn, CUtensorMap* m, const void* ptr, int rank, const cuuint64_t* dims, const cuuint64_t* strides, const cuuint32_t* box,
            CUtensorMapSwizzle sw = CU_TENSOR_MAP_SWIZZLE_128B, CUtensorMapL2promotion promo = CU_TENSOR_MAP_L2_PROMOTION_NONE) {
    const cuuint32_t es[5] = {1, 1, 1, 1, 1};
    return fn(m, CU_TENSOR_MAP_DATA_TYPE_BFLOAT16, rank, const_cast<void*>(ptr), dims, strides, box, es, CU_TENSOR_MAP_INTERLEAVE_NONE,
              sw, promo, CU_TENSOR_MAP_FLOAT_OOB_FILL_NONE) == CUDA_SUCCESS;
}

}

extern "C" void kernel_launch(void* const* d_in, const int* in_sizes, int n_in, void* d_out, int out_size) {
    (void)in_sizes; (void)n_in; (void)out_size;
    Params prm;
    prm.x = (const __nv_bfloat16*)d_in[0];
    prm.lam_re = (const __nv_bfloat16*)d_in[1];
    prm.lam_im = (const __nv_bfloat16*)d_in[2];
    prm.b_re = (const __nv_bfloat16*)d_in[3];
    prm.b_im = (const __nv_bfloat16*)d_in[4];
    prm.c_re = (const __nv_bfloat16*)d_in[5];
    prm.c_im = (const __nv_bfloat16*)d_in[6];
    prm.log_dt = (const __nv_bfloat16*)d_in[7];
    prm.dskip = (const __nv_bfloat16*)d_in[8];
    prm.w_r = (const __nv_bfloat16*)d_in[10];
    prm.gate_w = (const __nv_bfloat16*)d_in[14];
    prm.out = (float*)d_out;
    cudaGetSymbolAddress((void**)&prm.s, g_scratch);
    int dev = 0, sms = 0;
    cudaGetDevice(&dev);
    cudaDeviceGetAttribute(&sms, cudaDevAttrMultiProcessorCount, dev);
    prm.by_smid = sms == NGRID;
    prm.swapped = prm.b_im < prm.b_re;

    void* fnp = nullptr;
    cudaDriverEntryPointQueryResult qr;
    cudaGetDriverEntryPoint("cuTensorMapEncodeTiled", &fnp, cudaEnableDefault, &qr);
    EncodeFn fn = (EncodeFn)fnp;
    cudaFuncSetAttribute(fused_kernel, cudaFuncAttributeMaxDynamicSharedMemorySize, SMEM_BYTES);

    CUtensorMap mX, mB, mCre, mCim, mWg, mWu, mWd, mXr, mXe;
    const cuuint64_t row = 2048;
    {
        const cuuint64_t dims[4] = {1024, 2, 4, 976}, st[3] = {row, 32 * row, 2 * row};
        const cuuint32_t box[4] = {64, 2, 4, 16};
        encode(fn, &mX, prm.x, 4, dims, st, box, CU_TENSOR_MAP_SWIZZLE_128B, PROMO);
    }
    {
        const char *lo = (const char*)(prm.swapped ? prm.b_im : prm.b_re), *hi = (const char*)(prm.swapped ? prm.b_re : prm.b_im);
        const cuuint64_t dims[5] = {1024, 8, 2, 96, 2}, st[4] = {row, (cuuint64_t)(hi - lo), 8 * row, 256 * row};
        const cuuint32_t box[5] = {64, 8, 2, 4, 2};
        encode(fn, &mB, lo, 5, dims, st, box, CU_TENSOR_MAP_SWIZZLE_128B, PROMO);
    }
    {
        const cuuint64_t dims[5] = {1024, 2, 4, 2, 64}, st[4] = {row, 4 * row, 2 * row, 16 * row};
        const cuuint32_t box[5] = {64, 2, 4, 2, 8};
        encode(fn, &mCre, prm.c_re, 5, dims, st, box);
        encode(fn, &mCim, prm.c_im, 5, dims, st, box);
    }
    {
        const cuuint64_t dims[2] = {F_, D_}, st[1] = {F_ * 2}, dimsd[2] = {D_, F_}, std_[1] = {row};
        const cuuint32_t box[2] = {64, 32}, boxd[2] = {64, 64};
        encode(fn, &mWg, d_in[11], 2, dims, st, box, CU_TENSOR_MAP_SWIZZLE_128B, CU_TENSOR_MAP_L2_PROMOTION_NONE);
        encode(fn, &mWu, d_in[12], 2, dims, st, box, CU_TENSOR_MAP_SWIZZLE_128B, CU_TENSOR_MAP_L2_PROMOTION_NONE);
        encode(fn, &mWd, d_in[13], 2, dimsd, std_, boxd, CU_TENSOR_MAP_SWIZZLE_128B, CU_TENSOR_MAP_L2_PROMOTION_NONE);
    }
    {
        const cuuint64_t dims[3] = {D_ - 192, S_, 4}, st[2] = {row, 128};
        const cuuint32_t box[3] = {64, 16, 4};
        encode(fn, &mXr, prm.x, 3, dims, st, box, CU_TENSOR_MAP_SWIZZLE_128B, CU_TENSOR_MAP_L2_PROMOTION_NONE);
    }
    {
        const cuuint64_t dims[5] = {D_, 2, 2, 2, 976}, st[4] = {64 * row, row, 32 * row, 2 * row};
        const cuuint32_t box[5] = {64, 2, 2, 2, 8};
        encode(fn, &mXe, prm.x, 5, dims, st, box);
    }
    fused_kernel<<<NGRID, 384, SMEM_BYTES, cudaStreamPerThread>>>(prm, mX, mB, mCre, mCim, mWg, mWu, mWd, mXr, mXe);
}
```

```cpp
#include <cuda_runtime.h>
#include <cuda_bf16.h>
#include <cuda.h>
#include <stdint.h>

namespace {

constexpr int S_ = 2048, D_ = 1024, F_ = 3584;
constexpr int NCTA = 128, NGRID = 132;
#define XE_ 58
#define GU0_ 18
constexpr int NENT = 64, FIN = 58, XE = XE_;
constexpr int NST = 5;
constexpr int RE0 = 4;
constexpr int GU0 = GU0_;
constexpr uint32_t SLOT = 32768, ABYTES = 8192, WBYTES = 4096;
constexpr uint32_t OFF_XS = NST * SLOT;
constexpr uint32_t OFF_LIST = OFF_XS + 8192;
constexpr uint32_t OFF_W = OFF_XS + 16384;
constexpr uint32_t OFF_STG = OFF_W + 32768;
__host__ __device__ constexpr uint32_t slot_off(int i) { return i < XE ? (i % NST) * SLOT : i == XE ? OFF_W : ((i - 1) % NST) * SLOT; }
__host__ __device__ constexpr uint32_t dn_off(int u) { return u < 2 ? OFF_STG + u * ABYTES : u == 2 ? OFF_XS + ABYTES : slot_off(FIN - 2 + u); }
constexpr uint32_t OFF_CONST = OFF_STG;
constexpr uint32_t OFF_RED = OFF_STG + 4096;
constexpr uint32_t OFF_FULL = OFF_STG + 16384;
constexpr uint32_t OFF_EMPTY = OFF_FULL + 120 * 8;
constexpr uint32_t OFF_G = OFF_EMPTY + 88 * 8;
constexpr uint32_t OFF_DK = OFF_G + 256;
constexpr uint32_t OFF_KEYS = OFF_DK + 256;
constexpr uint32_t OFF_SEL = OFF_KEYS + 32;
constexpr uint32_t OFF_FAC = OFF_SEL + 32;
constexpr uint32_t OFF_EPOCH = OFF_FAC + 32;
constexpr uint32_t OFF_PROF = OFF_EPOCH + 16;
constexpr uint32_t SMEM_BYTES = OFF_PROF + 768;
static_assert(SMEM_BYTES <= 232448, "smem");

constexpr uint32_t sb = 1024;
constexpr uint32_t SPIN_LIMIT = 1u << 18;

struct Scratch {
    unsigned int cnt[2 * 32];
    unsigned long long rpack[S_ / 2];
    unsigned long long gpack[S_ / 2];
    uint4 time[NCTA];
    float2 carry[16 * 1024];
    uint4 hid[2 * F_];
    uint4 h[8 * 4 * 256 * 64];
};
__device__ __align__(128) Scratch g_scratch;
#define STAMPW(cond, w) do {} while (0)
#define LATE(i, tt) do {} while (0)
#define LANDED(i) do {} while (0)
#define GSTAMP(cond, w) do {} while (0)
#define STAMPIF(cond, i) STAMPW(cond, 72 + (i))
#define STAMP(i) STAMPW(1, 72 + (i))
#define KSTAMP(i) STAMPW((threadIdx.x & 127) == 0, i)

struct Params {
    const __nv_bfloat16 *x, *b_re, *b_im;
    int by_smid;
    int swapped;
    const __nv_bfloat16 *lam_re, *lam_im, *c_re, *c_im, *log_dt, *dskip, *w_r, *gate_w;
    float* out;
    Scratch* s;
};

__device__ __forceinline__ uint32_t smem_u32(const void* p) { return (uint32_t)__cvta_generic_to_shared(p); }
__device__ __forceinline__ void mbar_init(uint32_t bar, uint32_t cnt) { asm volatile("mbarrier.init.shared::cta.b64 [%0], %1;" ::"r"(bar), "r"(cnt) : "memory"); }
__device__ __forceinline__ void mbar_expect_tx(uint32_t bar, uint32_t bytes) { asm volatile("mbarrier.arrive.expect_tx.shared::cta.b64 _, [%0], %1;" ::"r"(bar), "r"(bytes) : "memory"); }
__device__ __forceinline__ void mbar_arrive(uint32_t bar) { asm volatile("mbarrier.arrive.shared::cta.b64 _, [%0];" ::"r"(bar) : "memory"); }
__device__ __forceinline__ void mbar_wait(uint32_t bar, uint32_t parity = 0) {
    asm volatile("{ .reg .pred p; .reg .u32 n;\n"
                 "mbarrier.try_wait.parity.shared::cta.b64 p, [%0], %1;\n"
                 "@p bra.uni DONE;\n"
                 "mov.u32 n, 0;\n"
                 "AGAIN: mbarrier.try_wait.parity.shared::cta.b64 p, [%0], %1;\n"
                 "@p bra.uni DONE;\n"
                 "add.u32 n, n, 1;\n"
                 "setp.lt.u32 p, n, %2;\n"
                 "@p bra.uni AGAIN;\n"
                 "trap;\n"
                 "DONE: }" ::"r"(bar), "r"(parity), "n"(SPIN_LIMIT) : "memory");
}
__device__ __forceinline__ bool elect_one() {
    uint32_t pred;
    asm volatile("{ .reg .pred P; elect.sync _|P, 0xffffffff; selp.b32 %0, 1, 0, P; }" : "=r"(pred));
    return pred;
}
__device__ __forceinline__ void named_bar(int id, int n) { asm volatile("bar.sync %0, %1;" ::"r"(id), "r"(n) : "memory"); }

#define ONE "{ .reg .pred e; elect.sync _|e, 0xffffffff;\n@e "
template <int N> __device__ __forceinline__ void mbar_init_n(uint32_t bar, uint32_t cnt, uint32_t extra = 0) {
    if (elect_one()) {
#pragma unroll
        for (int i = 0; i < N; i++) mbar_init(bar + 8 * i, i == N - 1 ? cnt + extra : cnt);
        asm volatile("fence.mbarrier_init.release.cluster;" ::: "memory");
    }
    __syncwarp();
}
__device__ __forceinline__ void bulk_load(uint32_t dst, const void* src, uint32_t bytes, uint32_t bar) {
    asm volatile(ONE "cp.async.bulk.shared::cluster.global.mbarrier::complete_tx::bytes [%0], [%1], %2, [%3]; }" ::"r"(dst), "l"(src), "r"(bytes), "r"(bar) : "memory");
}
__device__ __forceinline__ void sts128(uint32_t a, uint32_t x, uint32_t y, uint32_t z, uint32_t w) {
    asm volatile("st.shared.v4.u32 [%0], {%1,%2,%3,%4};" ::"r"(a), "r"(x), "r"(y), "r"(z), "r"(w) : "memory");
}
__device__ __forceinline__ uint2 lds64(uint32_t a) {
    uint2 v;
    asm volatile("ld.shared.v2.u32 {%0,%1}, [%2];" : "=r"(v.x), "=r"(v.y) : "r"(a) : "memory");
    return v;
}
__device__ __forceinline__ uint32_t clk32() { uint32_t c; asm volatile("mov.u32 %0, %%clock;" : "=r"(c)); return c; }
__device__ __forceinline__ void gap() { asm volatile("pmevent 1;" ::: "memory"); }
__device__ __forceinline__ void pace_until(uint32_t t) { while ((int)(clk32() - t) < 0) {} }
#define SLEEP_MARGIN 200
__device__ __forceinline__ void sleep_until(uint32_t t) {
    while ((int)(clk32() + SLEEP_MARGIN - t) < 0) __nanosleep(40);
    pace_until(t);
}
__device__ __forceinline__ void tma2(uint32_t dst, const CUtensorMap* m, int c0, int c1, uint32_t bar, uint64_t pol) {
    asm volatile(ONE "cp.async.bulk.tensor.2d.shared::cluster.global.mbarrier::complete_tx::bytes.L2::cache_hint [%0], [%1, {%3, %4}], [%2], %5; }"
                 ::"r"(dst), "l"(m), "r"(bar), "r"(c0), "r"(c1), "l"(pol) : "memory");
}
__device__ __forceinline__ void tma3(uint32_t dst, const CUtensorMap* m, int c0, int c1, uint32_t bar) {
    asm volatile(ONE "cp.async.bulk.tensor.3d.shared::cluster.global.mbarrier::complete_tx::bytes [%0], [%1, {%3, %4, %5}], [%2]; }"
                 ::"r"(dst), "l"(m), "r"(bar), "r"(c0), "r"(c1), "r"(0) : "memory");
}
__device__ __forceinline__ void tma4(uint32_t dst, const CUtensorMap* m, int c0, int c3, uint32_t bar) {
    asm volatile(ONE "cp.async.bulk.tensor.4d.shared::cluster.global.mbarrier::complete_tx::bytes [%0], [%1, {%3, %5, %5, %4}], [%2]; }"
                 ::"r"(dst), "l"(m), "r"(bar), "r"(c0), "r"(c3), "r"(0) : "memory");
}
__device__ __forceinline__ void tma5(uint32_t dst, const CUtensorMap* m, int c0, int c4, uint32_t bar) {
    asm volatile(ONE "cp.async.bulk.tensor.5d.shared::cluster.global.mbarrier::complete_tx::bytes [%0], [%1, {%3, %5, %5, %5, %4}], [%2]; }"
                 ::"r"(dst), "l"(m), "r"(bar), "r"(c0), "r"(c4), "r"(0) : "memory");
}
__device__ __forceinline__ void tma5b(uint32_t dst, const CUtensorMap* m, int c0, int c3, uint32_t bar) {
    asm volatile(ONE "cp.async.bulk.tensor.5d.shared::cluster.global.mbarrier::complete_tx::bytes [%0], [%1, {%3, %5, %5, %4, %5}], [%2]; }"
                 ::"r"(dst), "l"(m), "r"(bar), "r"(c0), "r"(c3), "r"(0) : "memory");
}
__device__ __forceinline__ void prefetch_l2(const void* p) {
    asm volatile("cp.async.ca.shared.global.L2::256B [%0], [%1], 4;" ::"r"(sb + OFF_EPOCH + 12), "l"(p) : "memory");
}

__device__ __forceinline__ uint32_t lds32(uint32_t a) {
    uint32_t v;
    asm volatile("ld.volatile.shared.u32 %0, [%1];" : "=r"(v) : "r"(a) : "memory");
    return v;
}
__device__ __forceinline__ uint32_t uni(uint32_t v) { return __shfl_sync(0xffffffffu, v, 0); }   __device__ __forceinline__ uint32_t ld_acquire(const unsigned int* p) {
    uint32_t v;
    asm volatile("ld.acquire.gpu.global.u32 %0, [%1];" : "=r"(v) : "l"(p) : "memory");
    return v;
}
__device__ __forceinline__ void red_release(unsigned int* p) { asm volatile("red.release.gpu.global.add.u32 [%0], 1;" ::"l"(p) : "memory"); }
__device__ __forceinline__ void wait_count(const unsigned int* p, uint32_t target) {
#pragma unroll 1
    for (uint32_t it = 0; it < SPIN_LIMIT; ++it)
        if ((int)(ld_acquire(p) - target) >= 0) return;
    __trap();
}
__device__ __forceinline__ void wait_count_slow(const unsigned int* p, uint32_t target) {
#pragma unroll 1
    for (uint32_t it = 0; it < SPIN_LIMIT; ++it) {
        if ((int)(ld_acquire(p) - target) >= 0) return;
        __nanosleep(200);
    }
    __trap();
}
__device__ __forceinline__ unsigned long long ld_relaxed1(const void* p) {
    unsigned long long v;
    asm volatile("ld.relaxed.gpu.global.b64 %0, [%1];" : "=l"(v) : "l"(p) : "memory");
    return v;
}
__device__ __forceinline__ ulonglong2 ld_relaxed2(const void* p) {
    ulonglong2 v;
    asm volatile("ld.relaxed.gpu.global.v2.b64 {%0, %1}, [%2];" : "=l"(v.x), "=l"(v.y) : "l"(p) : "memory");
    return v;
}
__device__ __forceinline__ void ld_cell(uint32_t (&v)[4], const void* p, bool on = true) {
    asm volatile("{ .reg .pred p; .reg .b64 l, h; .reg .b128 t; setp.ne.u32 p, %5, 0; mov.b64 l, {%0, %1}; mov.b64 h, {%2, %3}; mov.b128 t, {l, h};\n"
                 "@p ld.relaxed.gpu.global.b128 t, [%4]; mov.b128 {l, h}, t; mov.b64 {%0, %1}, l; mov.b64 {%2, %3}, h; }"
                 : "+r"(v[0]), "+r"(v[1]), "+r"(v[2]), "+r"(v[3]) : "l"(p), "r"((uint32_t)on) : "memory");
}
__device__ __forceinline__ void st_cell(void* p, uint32_t a, uint32_t b, uint32_t c, uint32_t d, bool on) {
    asm volatile("{ .reg .pred p; .reg .b64 l, h; .reg .b128 t; setp.ne.u32 p, %5, 0; mov.b64 l, {%1, %2}; mov.b64 h, {%3, %4}; mov.b128 t, {l, h};\n"
                 "@p st.relaxed.gpu.global.b128 [%0], t; }" ::"l"(p), "r"(a), "r"(b), "r"(c), "r"(d), "r"((uint32_t)on) : "memory");
}

__device__ __forceinline__ uint64_t make_desc(uint32_t addr, uint32_t sbo = 1024) {
    return (uint64_t)((addr & 0x3FFFF) >> 4) | ((uint64_t)1 << 16) | ((uint64_t)(sbo >> 4) << 32) | ((uint64_t)1 << 62);
}
__device__ __forceinline__ void wgmma_fence() { asm volatile("wgmma.fence.sync.aligned;" ::: "memory"); }
__device__ __forceinline__ void wgmma_commit() { asm volatile("wgmma.commit_group.sync.aligned;" ::: "memory"); }
template <int N> __device__ __forceinline__ void wgmma_wait() { asm volatile("wgmma.wait_group.sync.aligned %0;" ::"n"(N) : "memory"); }

#define R8(d, i) "+f"(d[i]), "+f"(d[i + 1]), "+f"(d[i + 2]), "+f"(d[i + 3]), "+f"(d[i + 4]), "+f"(d[i + 5]), "+f"(d[i + 6]), "+f"(d[i + 7])
#define R64(d) R8(d, 0), R8(d, 8), R8(d, 16), R8(d, 24), R8(d, 32), R8(d, 40), R8(d, 48), R8(d, 56)
template <int TA>
__device__ __forceinline__ void wgmma_n128(float (&d)[64], uint64_t da, uint64_t db, int scale_d = 1) {
    asm volatile("{ .reg .pred p; setp.ne.b32 p, %66, 0;\n"
                 "wgmma.mma_async.sync.aligned.m64n128k16.f32.bf16.bf16 "
                 "{%0,%1,%2,%3,%4,%5,%6,%7,%8,%9,%10,%11,%12,%13,%14,%15,%16,%17,%18,%19,%20,%21,%22,%23,%24,%25,%26,%27,%28,%29,%30,%31,"
                 "%32,%33,%34,%35,%36,%37,%38,%39,%40,%41,%42,%43,%44,%45,%46,%47,%48,%49,%50,%51,%52,%53,%54,%55,%56,%57,%58,%59,%60,%61,%62,%63}, "
                 "%64, %65, p, 1, 1, %67, 0; }"
                 : R64(d)
                 : "l"(da), "l"(db), "r"(scale_d), "n"(TA));
}
__device__ __forceinline__ void pin4(float (&d)[4]) { asm volatile("" : "+f"(d[0]), "+f"(d[1]), "+f"(d[2]), "+f"(d[3])::"memory"); }
__device__ __forceinline__ void pin64(float (&d)[64]) { asm volatile("" : R64(d)::"memory"); }

template <int TA, int TB = 0>
__device__ __forceinline__ void wgmma_n8(float (&d)[4], uint64_t da, uint64_t db, int scale_d = 1) {
    asm volatile("{ .reg .pred p; setp.ne.b32 p, %7, 0;\n"
                 "wgmma.mma_async.sync.aligned.m64n8k16.f32.bf16.bf16 {%0,%1,%2,%3}, %4, %5, p, 1, 1, %6, %8; }"
                 : "+f"(d[0]), "+f"(d[1]), "+f"(d[2]), "+f"(d[3])
                 : "l"(da), "l"(db), "n"(TA), "r"(scale_d), "n"(TB));
}

__device__ __forceinline__ float bf_lo(uint32_t u) { return __uint_as_float(u << 16); }
__device__ __forceinline__ float bf_hi(uint32_t u) { return __uint_as_float(u & 0xFFFF0000u); }
__device__ __forceinline__ float rbf(float v) { return __bfloat162float(__float2bfloat16_rn(v)); }
__device__ __forceinline__ uint32_t pack_bf(float lo, float hi) {
    uint32_t r;
    asm("cvt.rn.bf16x2.f32 %0, %1, %2;" : "=r"(r) : "f"(hi), "f"(lo));
    return r;
}
__device__ __forceinline__ uint32_t mul_bf2(uint32_t a, uint32_t b) {
    __nv_bfloat162 r = __hmul2(*reinterpret_cast<__nv_bfloat162*>(&a), *reinterpret_cast<__nv_bfloat162*>(&b));
    return *reinterpret_cast<uint32_t*>(&r);
}
__device__ __forceinline__ uint32_t fma_bf2(uint32_t a, uint32_t b, uint32_t c) {
    uint32_t r;
    asm("fma.rn.bf16x2 %0, %1, %2, %3;" : "=r"(r) : "r"(a), "r"(b), "r"(c));
    return r;
}
__device__ __forceinline__ float2 cmul(float2 a, float2 b) { return make_float2(a.x * b.x - a.y * b.y, a.x * b.y + a.y * b.x); }
__device__ __forceinline__ float2 cfma(float2 a, float2 b, float2 c) {
    return make_float2(fmaf(a.x, b.x, fmaf(-a.y, b.y, c.x)), fmaf(a.x, b.y, fmaf(a.y, b.x, c.y)));
}
__device__ __forceinline__ float sigmoidf_(float v) { return __fdividef(1.0f, 1.0f + expf(-v)); }

__device__ __forceinline__ void bulk_prefetch(const void* src, uint32_t bytes) {
    asm volatile(ONE "cp.async.bulk.prefetch.L2.global [%0], %1; }" ::"l"(src), "r"(bytes) : "memory");
}
__device__ __forceinline__ void bulk_store(void* dst, uint32_t src, uint32_t bytes) {
    asm volatile(ONE "cp.async.bulk.global.shared::cta.bulk_group [%0], [%1], %2; }" ::"l"(dst), "r"(src), "r"(bytes) : "memory");
}
__device__ __forceinline__ uint4 lds128(uint32_t a) {
    uint4 v;
    asm volatile("ld.shared.v4.u32 {%0,%1,%2,%3}, [%4];" : "=r"(v.x), "=r"(v.y), "=r"(v.z), "=r"(v.w) : "r"(a) : "memory");
    return v;
}
__device__ __forceinline__ float4 lds128f(uint32_t a) {
    float4 v;
    asm volatile("ld.shared.v4.f32 {%0,%1,%2,%3}, [%4];" : "=f"(v.x), "=f"(v.y), "=f"(v.z), "=f"(v.w) : "r"(a) : "memory");
    return v;
}
__device__ __forceinline__ void stsm4(uint32_t a, uint32_t x, uint32_t y, uint32_t z, uint32_t w) {
    asm volatile("stmatrix.sync.aligned.m8n8.x4.shared.b16 [%0], {%1,%2,%3,%4};" ::"r"(a), "r"(x), "r"(y), "r"(z), "r"(w) : "memory");
}
__device__ __forceinline__ uint4 ldsm4(uint32_t a) {
    uint4 v;
    asm volatile("ldmatrix.sync.aligned.m8n8.x4.shared.b16 {%0,%1,%2,%3}, [%4];" : "=r"(v.x), "=r"(v.y), "=r"(v.z), "=r"(v.w) : "r"(a) : "memory");
    return v;
}
__device__ __forceinline__ void stg4_unless(float* p, float a, float b, float c, float d, uint32_t skip) {
    asm volatile("{ .reg .pred p; setp.eq.u32 p, %5, 0; @p st.global.v4.f32 [%0], {%1,%2,%3,%4}; }" ::"l"(p), "f"(a), "f"(b), "f"(c), "f"(d), "r"(skip) : "memory");
}
__device__ __forceinline__ void red4(float* p, float a, float b, float c, float d) {
    asm volatile("red.global.add.v4.f32 [%0], {%1,%2,%3,%4};" ::"l"(p), "f"(a), "f"(b), "f"(c), "f"(d) : "memory");
}

#define TT0 3100
#define PER 520
#define PCUT 60
#define PFIN 400
#define PF0 1700
#define PFX_PACE 400
#define PFV 6
#define PFT 0
#define PF1 700
#define T2 400
#define P2 550
#define G0 450
#define R0 2300
#define R_PACE 350
#define W_SHIFT 250
#define PROMO CU_TENSOR_MAP_L2_PROMOTION_L2_256B
#define POLL_S 0
#define ST_TOL 100
#define ST_SHIFT 300
#define CLK_NS 420
#define MARGIN 150
#define BP1 10
#define NDUMP 8
#define DWAIT 0
#define DNL 2
#define AE 6
#define AG0 900
#define AB 16
#define HGE 38
constexpr uint32_t duration(int i) { return PER + (i >= RE0 && i < RE0 + 4 ? 72 : 0) + (i >= GU0 && i < GU0 + 32 ? 36 : 0); }
constexpr uint32_t cmax(uint32_t a, uint32_t b) { return a > b ? a : b; }
constexpr uint32_t issue_time(int i) {
    return i <= NST ? TT0 : i < XE ? issue_time(i - 1) + duration(i - NST) - (i >= XE - 3 && i > GU0 + 36 ? PCUT : 0) : issue_time(XE - 1) + cmax((i - XE + 1) * PFIN, (i - XE) * 512);
}
template <int I> struct Sched { static constexpr uint32_t t = issue_time(I); };
template <int LO, int HI, class F>
__device__ __forceinline__ void for_entries(uint32_t base, F body) {
    constexpr uint32_t per = Sched<LO + 1>::t - Sched<LO>::t;
    static_assert(Sched<HI - 1>::t - Sched<LO>::t == (HI - 1 - LO) * per, "period");
    uint32_t tt = base + Sched<LO>::t;
#pragma unroll 1
    for (int i = LO; i < HI; i++) {
        body(i, tt);
        tt += per;
    }
}

struct Ring { uint32_t prev; int slot; };
struct NoHook { __device__ void operator()() const {} };
template <int TA, int SM, class H = NoHook>
__device__ __forceinline__ void run_entries(Ring& r, int lo, int hi, float (&accA)[64], float (&accB)[64], float (&small)[4],
                                            bool fresh = false, bool sfresh = false, H released = H()) {
    const uint64_t d0 = make_desc(sb);
    const bool leader = (threadIdx.x & 31) == 0;
#pragma unroll 1
    for (int i = lo; i < hi; i++) {
        const uint32_t bar = sb + OFF_FULL + 8 * i;
        const uint64_t da = d0 + (uint64_t)(r.slot * (SLOT >> 4));
        const int n = i - (SM == 1 ? RE0 : GU0);
        const uint64_t dw = d0 + (uint64_t)((OFF_W >> 4) + (SM == 1 ? n * 512 : (n & 7) * 256));
        const uint64_t dt8 = d0 + (uint64_t)((OFF_XS >> 4) + (SM == 1 ? n * 64 : (n >> 1) * 64 + (n & 1) * 4));
        r.slot = r.slot == NST - 1 ? 0 : r.slot + 1;
        mbar_wait(bar);
        KSTAMP(i);
        wgmma_fence();
#pragma unroll
        for (int kk = 0; kk < 4; kk++) {
            wgmma_n128<TA>(accA, da + kk * (TA ? 128 : 2), da + 1024 + kk * 2, kk > 0 || !fresh);
            if (SM == 1) wgmma_n8<0>(small, dw + kk * 2, dt8 + kk * 2, kk > 0 || !sfresh);
            if (SM == 2 && (kk & 1)) wgmma_n8<1>(small, dw + (kk >> 1) * 128, dt8 + (kk >> 1) * 2, kk > 1 || !sfresh);
            wgmma_n128<TA>(accB, da + 512 + kk * (TA ? 128 : 2), da + 1024 + kk * 2, kk > 0 || !fresh);
            if (kk == 1) {
                wgmma_commit();
                wgmma_wait<1>();
                if (leader) mbar_arrive(r.prev);
                released();
            }
        }
        wgmma_commit();
        r.prev = bar + (OFF_EMPTY - OFF_FULL);
        fresh = sfresh = false;
    }
}
template <int HALF, int I>
__device__ __forceinline__ void run_small(float (&acc)[64]) {
    const uint64_t da = make_desc(sb) + (slot_off(I) >> 4);
    KSTAMP(I + HALF * (NENT - FIN));
    wgmma_fence();
#pragma unroll
    for (int kk = 0; kk < 4; kk++) wgmma_n128<1>(acc, da + HALF * 512 + kk * 128, da + 1024 + kk * 2, kk > 0 || !(HALF && I == FIN));
    wgmma_commit();
}
template <int V> struct Int { __host__ __device__ constexpr operator int() const { return V; } };
template <int N, class F> __device__ __forceinline__ void static_for(F f) {
    if constexpr (N > 0) { static_for<N - 1>(f); f(Int<N - 1>()); }
}

__global__ void __launch_bounds__(384, 1)
fused_kernel(const __grid_constant__ Params prm, const __grid_constant__ CUtensorMap mX, const __grid_constant__ CUtensorMap mB, const __grid_constant__ CUtensorMap mCre,
             const __grid_constant__ CUtensorMap mCim, const __grid_constant__ CUtensorMap mWg, const __grid_constant__ CUtensorMap mWu,
             const __grid_constant__ CUtensorMap mWd, const __grid_constant__ CUtensorMap mXr, const __grid_constant__ CUtensorMap mXe) {
    extern __shared__ __align__(1024) uint8_t smem[];
    const uint32_t cstart = clk32();
    const int tid = threadIdx.x, lane = tid & 31;
    uint32_t smid;
    asm volatile("mov.u32 %0, %%smid;" : "=r"(smid));
    {
        const uint32_t b = blockIdx.x & 127, r = tid - PFT, o = (r >> 1) * 2048 + (r & 1) * 128;
#define PFS "@q prefetch.global.L2 [%1]; @p prefetch.global.L2 [%0]; @q prefetch.global.L2 [%2];"
        asm volatile("{ .reg .pred p, q; setp.lt.u32 p, %3, 32; setp.lt.u32 q, %3, 8;\n" PFS " }"
                     ::"l"((const char*)prm.x + (b * 32768 + o)), "l"((const char*)prm.b_re + (b * 8192 + o)), "l"((const char*)prm.b_im + (b * 8192 + o)), "r"(r),
                     "r"(sb + OFF_EPOCH + 12) : "memory");
        gap();
        STAMPIF(tid == PFT, 33);
    }
    const int warp = __shfl_sync(0xffffffffu, tid >> 5, 0);
    int cta;
    asm("{ .reg .pred p; .reg .u32 s, a, b, u, q;\n"
                 "mov.u32 s, %3;\n"
                 "and.b32 a, s, 14; shl.b32 a, a, 2; shr.u32 b, s, 4; add.u32 a, a, b;\n"
                 "sub.u32 u, s, 64; shr.u32 u, u, 1; mul.lo.u32 q, u, 37; shr.u32 q, q, 8; shl.b32 u, u, 3; mad.lo.u32 u, q, -55, u; add.u32 u, u, 12;\n"
                 "setp.lt.u32 p, s, 64; selp.u32 a, a, u, p; and.b32 b, s, 1; mad.lo.u32 a, a, 2, b;\n"
                 "setp.lt.u32 p, s, 124; selp.u32 b, 8, -116, p; add.u32 b, b, s; setp.lt.u32 p, s, 120; selp.u32 a, a, b, p;\n"
                 "setp.ne.u32 p, %2, 0; selp.u32 %0, a, %1, p; }" : "=r"(cta) : "r"(blockIdx.x), "r"(prm.by_smid), "r"(smid));
    const int chunk = (cta >> 5) * 4 + ((cta >> 2) & 3);
    const int dt = ((cta >> 4) & 1) * 4 + (cta & 3);
    asm volatile("{ .reg .pred e, p; elect.sync _|e, 0xffffffff; setp.eq.and.u32 p, %0, 5, e;\n"
                 "@p mbarrier.init.shared::cta.b64 [%1], 1; @p mbarrier.init.shared::cta.b64 [%1 + 8], 1;\n"
                 "fence.mbarrier_init.release.cluster; }" ::"r"(warp), "r"(sb + OFF_FULL) : "memory");
    if (warp == 5 && cta < NCTA) {
        tma5b(sb, &mB, 0, dt * 4, sb + OFF_FULL);
        tma4(sb + 2 * ABYTES, &mX, 0, chunk * 64, sb + OFF_FULL);
        STAMP(31);
        tma5b(sb + SLOT, &mB, 64, dt * 4, sb + OFF_FULL + 8);
        tma4(sb + SLOT + 2 * ABYTES, &mX, 64, chunk * 64, sb + OFF_FULL + 8);
    }
    if (cta >= NCTA) {
        if (smem_u32(smem) != sb) __trap();
        if (tid == 0) wait_count_slow(&prm.s->cnt[0], (atomicAdd(&prm.s->cnt[0], 1u) / NGRID + 1) * NGRID);
        return;
    }
    const bool has_gu = cta >= 16;
    constexpr uint32_t full = sb + OFF_FULL, empty = sb + OFF_EMPTY;
    constexpr uint32_t raw = full + 8 * 32;
    constexpr uint32_t bar_hraw = full + 8 * 97, bar_xs = full + 8 * 98, bar_dn = full + 8 * 99, bar_xb = full + 8 * 100, bar_xa = full + 8 * 101,
        bar_retry = full + 8 * 102, bar_out = full + 8 * 104;
    constexpr uint32_t bar_base = empty - 64, bar_init3 = empty - 56, bar_rdone = empty - 48, bar_order0 = empty - 40, bar_init2 = empty - 32,
        bar_vec = empty - 24, bar_epoch = empty - 16, bar_dummy = empty - 8, bar_xs0 = empty + 8 * 69,
        bar_zero = empty + 8 * 70, bar_xafree = empty + 8 * 71, bar_order2 = empty + 8 * 72, bar_order3 = empty + 8 * 73, bar_fp = empty + 8 * 74,
        bar_hs = empty + 8 * 75, bar_accb = empty + 8 * 76, bar_xbfree = empty + 8 * 78, bar_fold = empty + 8 * 79, bar_st = empty + 8 * 80,
        bar_hpub = empty + 8 * 66, bar_order1 = empty + 8 * 67, bar_cand = empty + 8 * 68;

    auto load_hid = [&]() {
        if (lane == 0) mbar_expect_tx(bar_hraw, 2 * 7168);
        bulk_load(sb + OFF_XS, prm.s->hid + (cta >> 4) * 448, 7168, bar_hraw);
        bulk_load(sb + OFF_XS + ABYTES, prm.s->hid + F_ + (cta >> 4) * 448, 7168, bar_hraw);
    };

    if (warp == 5) {
        if (lane < 2) mbar_expect_tx(full + 8 * lane, SLOT);
        __syncwarp();
        named_bar(0, 256);
#pragma unroll 1
        for (int i = 2; i < NST; i++) {
            pace_until(cstart + T2 + i * P2);
            tma5b(sb + i * SLOT, &mB, i * 64, dt * 4, full + 8 * i);
            tma4(sb + i * SLOT + 2 * ABYTES, &mX, i * 64, chunk * 64, full + 8 * i);
            STAMPIF(i == 4, 1);
        }
    } else if (warp == 4) {
        mbar_init_n<12>(bar_init2, 4);
        asm volatile("bar.arrive 0, 256;" ::: "memory");
        mbar_init_n<4>(bar_base, 4);
        mbar_init_n<8>(empty + 64, 4);
        *reinterpret_cast<uint2*>(smem + OFF_KEYS + 16) = make_uint2(0, 0);
        asm volatile("bar.arrive 1, 64;" ::: "memory");
        asm volatile("bar.arrive 5, 96;" ::: "memory");
        asm volatile("bar.arrive 6, 96;" ::: "memory");
        mbar_init_n<32>(full + 256, 3);
        if (lane < 2) mbar_arrive(bar_init2);
    } else if ((warp >> 1) == 3) {
        if (warp == 6) {
            mbar_init_n<8>(full + 16, 1);
            if (lane >= 2 && lane < 10) mbar_expect_tx(full + 8 * lane, lane >= RE0 && lane < RE0 + 4 ? SLOT + ABYTES : SLOT);
            __syncwarp();
            asm volatile("bar.arrive 0, 256;" ::: "memory");
        }
        const char* pf0 = (warp & 1) ? (const char*)((cta & 64) ? prm.b_im : prm.b_re) + (cta & 63) * 16384 : (const char*)prm.x + cta * 32768;
        pace_until(cstart + PF1);
        asm volatile("prefetch.global.L2 [%0];" ::"l"(pf0 + (lane & (30 >> (warp & 1) & 30)) * 1024 + (lane & 1) * 128 + 256));
        const int i0 = warp == 6 ? 10 : 21;
        mbar_init_n<11>(full + 8 * i0, 1);
        if (lane >= i0 && lane < i0 + 11) mbar_expect_tx(full + 8 * lane, lane >= GU0 && has_gu ? SLOT + WBYTES : SLOT);
        mbar_init_n<24>(full + 512 + 192 * (warp & 1), 1);
        named_bar(5, 96);
        if (lane == 0) mbar_arrive(bar_init2);
        STAMP(21);
    }
    __syncwarp();

    if (warp >= 8) {
        asm volatile("setmaxnreg.dec.sync.aligned.u32 72;");
        const uint32_t c0 = cstart;
        uint64_t stream;
        asm volatile("createpolicy.fractional.L2::evict_first.b64 %0, 1.0;" : "=l"(stream));
        const CUtensorMap* mw = (cta & 1) ? &mWu : &mWg;
        const int dc = (cta & 15) * 64, dr = (cta >> 4) * 448;
        auto gutile = [&](int i) {
            const int n = i + 3 - GU0;
            if (has_gu) tma2(sb + OFF_W + (n & 7) * WBYTES, mw, (cta >> 1) * 64 - 512, n * 32, full + 8 * (i + 3), stream);
        };
        if (warp == 8) {
            named_bar(0, 256);
            asm volatile("prefetch.tensormap [%0];" ::"l"(&mXr));
#pragma unroll 1
            for (int u = 0; u < 2; u++) {
                sleep_until(c0 + R0 + u * R_PACE);
                tma3(sb + OFF_W + u * ABYTES, &mXr, u * 256, cta * 16, full + 8 * (RE0 + u));
            }
            uint32_t dst = sb;
            auto gemm1 = [&](int i, uint32_t tt) {
                mbar_wait(empty + 8 * (i - NST));
                LATE(i, tt);
                pace_until(tt);
                tma5b(dst, &mB, (i & 15) * 64, (i >> 4) * 64 + dt * 4, full + 8 * i);
                tma4(dst + 2 * ABYTES, &mX, (i & 15) * 64, chunk * 64, full + 8 * i);
                dst = dst == sb + (NST - 1) * SLOT ? sb : dst + SLOT;
            };
            mbar_wait(bar_init2);
            uint32_t tt = c0 + TT0;
#pragma unroll 1
            for (int i = NST; i < AB; i++) {
                gemm1(i, tt);
                if (i < 7) tma3(sb + OFF_W + (i - 3) * ABYTES, &mXr, (i - 3) * 256, cta * 16, full + 8 * (i + 1));
                tt += (i & ~3) == RE0 + 4 ? PER + 72 : PER;
            }
            mbar_wait(bar_base);
            const uint32_t base = uni(lds32(sb + OFF_EPOCH + 8));
            tt = base + Sched<AB>::t;
#pragma unroll 1
            for (int i = AB; i < 32; i++) {
                gemm1(i, tt);
                tt += i >= GU0 + 4 ? PER + 36 : PER;
            }
            const char* hsrc = reinterpret_cast<const char*>(prm.s->h) + (size_t)chunk * 524288;
            auto gemm2 = [&](int i, uint32_t d, int freed, uint32_t tt) {
                mbar_wait(empty + 8 * freed);
                LATE(i, tt);
                pace_until(tt);
                bulk_load(d, hsrc, 2 * ABYTES, raw + 8 * i);
                tma5(d + 2 * ABYTES, (i & 4) ? &mCim : &mCre, ((i & 3) + ((i >> 1) & 12)) * 64, dt * 8, full + 8 * i);
                hsrc += 2 * ABYTES;
            };
            for_entries<32, GU0 + 29>(base, [&](int i, uint32_t tt) {
                gemm2(i, dst, i - NST, tt);
                gutile(i);
                dst = dst == sb + (NST - 1) * SLOT ? sb : dst + SLOT;
            });
            for_entries<GU0 + 29, GU0 + 37>(base, [&](int i, uint32_t tt) {
                gemm2(i, dst, i - NST, tt);
                const int n = i - GU0 - 29;
                if ((n & 5) == 1) tma5(sb + OFF_W + (n & 2) * (ABYTES / 2), &mXe, dt * 128 + (n & 2) * 32, chunk * 64, bar_xa);
                else if (n < 7) asm volatile(ONE "cp.async.bulk.prefetch.tensor.2d.L2.global [%0, {%1, %2}]; }" ::"l"(&mWd), "r"(dc), "r"(dr + 64 * (n < 4 ? 2 + n / 2 : n)) : "memory");
                dst = dst == sb + (NST - 1) * SLOT ? sb : dst + SLOT;
            });
            static_for<NENT - GU0 - 37>([&](auto u) {
                constexpr int i = GU0 + 37 + u;
                if (i == 60) mbar_wait(bar_out + 56);
                gemm2(i, sb + slot_off(i), i < XE ? i - NST : i == XE ? 71   : i - NST - 1, base + Sched<i>::t);
            });
            STAMP(4);
        } else if (warp == 9) {
#pragma unroll
            for (int u = 0; u < 8; u++) {
                const int row = (u >> 2) * 4 + (lane >> 3);
                asm volatile("cp.async.cg.shared.global [%0], [%1], 16;" ::"r"(sb + OFF_XS + (u & 3) * 1024 + row * 128 + (((lane & 7) ^ row) << 4)),
                             "l"((const char*)(u < 4 ? prm.w_r : prm.gate_w) + (u & 3) * 512 + lane * 16) : "memory");
            }
            uint32_t ticket = 0;
            if (lane == 0) ticket = atomicAdd(&prm.s->cnt[0], 1u);
            named_bar(1, 64);
            if (lane == 0) *reinterpret_cast<volatile uint32_t*>(smem + OFF_EPOCH) = ticket / NGRID;
            __syncwarp();
            if (lane < 4) mbar_arrive(bar_epoch);
            asm volatile("cp.async.wait_all;" ::: "memory");
            asm volatile("fence.proxy.async.shared::cta;" ::: "memory");
            __syncwarp();
            if (lane < 4) mbar_arrive(bar_vec);
            STAMP(18);
#pragma unroll 1
            for (int i = 4; i < 22; i++) mbar_init_n<4>(empty + 32 * i, 4, i >= 6 && i < 13);
            if (lane < 2) mbar_arrive(bar_init3);
            STAMP(19);
            mbar_wait(bar_cand);
            {
                const uint32_t* list = reinterpret_cast<const uint32_t*>(smem + OFF_LIST);
                const int n = (int)lds32(sb + OFF_KEYS + 16);
#pragma unroll 1
                for (int i0 = 0; i0 < n; i0 += 32) {
                    const uint32_t k = list[i0 + lane];
                    int rank = 0;
#pragma unroll 2
                    for (int o = 0; o < n; o += 4) {
                        const uint4 l4 = *reinterpret_cast<const uint4*>(list + o);
                        rank += (l4.x > k) + (l4.y > k) + (l4.z > k) + (l4.w > k);
                    }
                    if (rank < 8) reinterpret_cast<uint32_t*>(smem + OFF_SEL)[rank] = k;
                }
                __syncwarp();
                STAMP(6);
                const uint32_t key = lds32(sb + OFF_SEL + 4 * (lane & 7)), tok = ~key & 2047u, tag = lds32(sb + OFF_EPOCH) + 1;
                const uint32_t ta = __shfl_sync(0xffffffffu, tok, lane >> 3), tb = __shfl_sync(0xffffffffu, tok, 4 + (lane >> 3));
                const uint32_t da = sb + OFF_XS + (lane >> 3) * 128 + (((lane & 7) ^ (lane >> 3)) << 4), db = (da ^ 64) + 512;
                const char *sa = (const char*)prm.x + ta * 2048 + (lane & 7) * 16, *sc = (const char*)prm.x + tb * 2048 + (lane & 7) * 16;
#pragma unroll
                for (int u = 0; u < 16; u++) {
                    asm volatile("cp.async.cg.shared.global [%0], [%1], 16;" ::"r"(da + u * 1024), "l"(sa + u * 128) : "memory");
                    asm volatile("cp.async.cg.shared.global [%0], [%1], 16;" ::"r"(db + u * 1024), "l"(sc + u * 128) : "memory");
                    if (u == 3) {
                        asm volatile("cp.async.wait_all;" ::: "memory");
                        asm volatile("fence.proxy.async.shared::cta;" ::: "memory");
                        __syncwarp();
                        if (lane < 4) mbar_arrive(bar_xs0);
                        STAMP(17);
                    }
                }
                if ((tok >> 7) == (uint32_t)chunk) {
                    float4* zp = reinterpret_cast<float4*>(prm.out + tok * D_ + dt * 128) + (lane >> 3) * 2;
#pragma unroll
                    for (int u = 0; u < 8; u++) zp[(u >> 1) * 8 + (u & 1)] = make_float4(0.f, 0.f, 0.f, 0.f);
                }
                uint32_t it = 0;
                unsigned long long u;
                do {
                    u = ld_relaxed1(&prm.s->gpack[tok >> 1]);
                    if (++it > SPIN_LIMIT) __trap();
                } while (!__all_sync(0xffffffffu, (uint32_t)(u >> 32) == tag));
                const uint32_t kb = key >> 16;
                const float r = bf_lo((kb & 0x8000u) ? (kb & 0x7FFFu) : (~kb & 0xFFFFu)), gv = (tok & 1) ? bf_hi((uint32_t)u) : bf_lo((uint32_t)u);
                reinterpret_cast<float*>(smem + OFF_FAC)[lane & 7] = rbf(1.0f - gv) * rbf(sigmoidf_(r));
                asm volatile("cp.async.wait_all;" ::: "memory");
                asm volatile("fence.proxy.async.shared::cta;" ::: "memory");
                __syncwarp();
                if (lane == 0) mbar_arrive(bar_xs);
                STAMP(7);
            }
            char* hd = reinterpret_cast<char*>(prm.s->h) + (size_t)chunk * 524288 + (dt >> 1) * 16384 + (dt & 1) * 4096;
            mbar_wait(bar_base);
            const uint32_t cb = uni(lds32(sb + OFF_EPOCH + 8)) + ST_SHIFT;
            uint32_t tt = cb + Sched<GU0 + 4>::t;
#pragma unroll 1
            for (int np = 0; np < 16; np++) {
                if (!(np & (np & 4 ? 1 : 2))) mbar_wait(bar_st + 4 * (np & 12) + ((np & 3) ? 8 : 0));
                const uint32_t now = clk32() - ST_TOL;
#pragma unroll 1
                while ((int)(tt - now) < 0) tt += PER + 36;
                const uint32_t src = sb + OFF_STG + (np & 3) * 4096;
                pace_until(tt);
                bulk_store(hd, src, 4096);
                asm volatile("cp.async.bulk.commit_group;" ::: "memory");
                if (np & 2) {
                    if (np & 1) asm volatile("cp.async.bulk.wait_group.read 0;" ::: "memory");
                    else asm volatile("cp.async.bulk.wait_group.read 1;" ::: "memory");
                    __syncwarp();
                    const uint32_t u8 = 4 * (np & 12) + 8 * (np & 1);
                    if (lane < 2) mbar_arrive(lane ? (np < 15 ? empty + 8 * 27 + 4 * u8 : bar_dummy) : bar_out + u8);
                }
                STAMPIF(np & 2, 8 + ((np >> 1) & 6) + (np & 1));
                hd += (np & 1) ? 65536 - 8192 : 8192;
                tt += PER + 36;
            }
#pragma unroll 1
            for (int u = 0; u < 2; u++) {
                pace_until(tt);
                tma5(sb + OFF_STG + u * ABYTES, &mXe, dt * 128 + u * 64, chunk * 64 + 8, bar_xb);
                tt += PER + 36;
            }
            wait_count(&prm.s->cnt[32], (lds32(sb + OFF_EPOCH) + 1) * NCTA);
            if (lane < 4) mbar_arrive(bar_zero);
            mbar_wait(bar_hpub);
            sleep_until(cb + Sched<GU0 + HGE>::t);
            load_hid();
            static_for<7>([&](auto u) {
                if (u != 1) mbar_wait(u == 0 ? bar_xbfree : u == 2 ? bar_hs : empty + 8 * (u == 3 ? FIN + DNL : FIN - 2 + u));
                if (u < 3) sleep_until(cb + Sched<(u < 2 ? GU0 + HGE + u : NENT - 1)>::t);
                tma2(sb + dn_off(u), &mWd, dc, dr + u * 64, bar_dn, stream);
            });
            STAMP(27);
        } else {
            named_bar(6, 96);
            if (warp == 10) {
                const char* pb = (const char*)((cta & 64) ? prm.b_im : prm.b_re) + (cta & 63) * 16384;
                const char* pf = (lane < 16 ? (const char*)prm.x + cta * 32768 : pb) + (lane & 15) * 2048 + 512;
#pragma unroll 1
                for (int k = 0; k < 11; k++) {
                    sleep_until(c0 + PF0 + k * PFX_PACE);
                    if (lane < 16 ? k < 6 : lane < 24 && !(k & 1)) prefetch_l2(pf + k * (lane < 16 ? 256 : 128));
                }
                static_for<12>([&](auto k) {
                    sleep_until(c0 + Sched<BP1 + k>::t + ST_SHIFT);
                    bulk_prefetch((k < 4 ? pb + 1048576 : (const char*)(k < 8 ? prm.c_re : prm.c_im) + cta * 16384) + (k & 3) * 4096, 4096);
                    if (k == 4) { mbar_wait(bar_init2); mbar_wait(bar_init3); }
                    if (k >= 4 && lane < 8) mbar_expect_tx(full + 8 * (8 * k + lane), 8 * k + lane < GU0 + 32 && has_gu ? 2 * ABYTES + WBYTES : 2 * ABYTES);
                });
                asm volatile("prefetch.tensormap [%0];" ::"l"(&mCre));
                asm volatile("prefetch.tensormap [%0];" ::"l"(&mCim));
                asm volatile("prefetch.tensormap [%0];" ::"l"(&mWd));
                asm volatile("prefetch.tensormap [%0];" ::"l"(&mXe));
                if (lane < 3) mbar_expect_tx(bar_dn + 8 * lane, lane ? 2 * ABYTES : 7 * ABYTES);
                mbar_wait(bar_xs);
                mbar_wait(bar_st);
                if (lane == 0) red_release(&prm.s->cnt[32]);
                __syncwarp();
                STAMP(22);
            } else {
                asm volatile("prefetch.tensormap [%0];" ::"l"(mw));
                mbar_wait(bar_epoch);
                const uint32_t tag = lds32(sb + OFF_EPOCH) + 1;
                st_cell(prm.s->time + cta, 0, 0, 0, 0, lane == 0);
                mbar_wait(empty + 8 * AE);
                uint32_t gown, tm[4][4] = {}, it = 0;
                asm volatile("mov.u32 %0, %%globaltimer_lo;" : "=r"(gown));
                const uint32_t town = clk32();
                st_cell(prm.s->time + cta, tag, town, gown, 0, lane == 0);
                sleep_until(town + AG0);
                do {
#pragma unroll
                    for (int m = 0; m < 4; m++) ld_cell(tm[m], prm.s->time + ((cta & 96) ^ (32 * m)) + lane);
                    if (++it > SPIN_LIMIT) __trap();
                } while (!__all_sync(0xffffffffu, tm[0][0] == tag && tm[1][0] == tag && tm[2][0] == tag && tm[3][0] == tag));
                const int last = __reduce_max_sync(0xffffffffu, max(max((int)(tm[0][2] - gown), (int)(tm[1][2] - gown)), max((int)(tm[2][2] - gown), (int)(tm[3][2] - gown))));
                const uint32_t cand = tm[0][1] + ((min((int)(gown + last - tm[0][2]), 4000) * CLK_NS) >> 8);
                const uint32_t b0 = __shfl_sync(0xffffffffu, cand, cta & 16), b1 = __shfl_sync(0xffffffffu, cand, cta & 30);
                const uint32_t base = (b0 - b1 + 400u < 800u ? b0 : b1) + MARGIN - Sched<AE + NST>::t;
                *reinterpret_cast<volatile uint32_t*>(smem + OFF_EPOCH + 8) = base;
                mbar_wait(bar_init3);
                if (lane < 4) mbar_arrive(bar_base);
                STAMP(23);
                const uint32_t cb = base + W_SHIFT;
                auto early = [&](int i, uint32_t tt) {
                    mbar_wait(empty + 8 * (i - NST));
                    pace_until(tt);
                    gutile(i);
                };
                for_entries<GU0 - 3, GU0 + 4>(cb, early);
                for_entries<GU0 + 4, 32>(cb, early);
            }
            mbar_wait(bar_epoch);
            const uint32_t t2 = lds32(sb + OFF_EPOCH) + 1, tagw = (t2 & 1) | ((t2 & 2) << 15), half = (warp & 1) * ABYTES;
            const uint32_t lo = half + lane * 32 + (lane & 4) * 4 + (lane >> 3) * 4, retry = bar_retry + (warp & 1) * 8;
            const bool leader = lane == 0;
            uint32_t slot = sb + (32 % NST) * SLOT, rpar = 0;
#pragma unroll 1
            for (int i = 32; i < NENT; i++) {
                const uint32_t src = i == XE ? sb + OFF_W : slot;
                if (i != XE) slot = slot == sb + (NST - 1) * SLOT ? sb : slot + SLOT;
                auto current = [&]() {
                    uint32_t v[8];
#pragma unroll
                    for (int u = 0; u < 8; u++) v[u] = lds32(src + lo + u * 1024);
#pragma unroll
                    for (int u = 0; u < 8; u += 2) asm("lop3.b32 %0, %0, %1, %2, 0x7e;" : "+r"(v[u]) : "r"(v[u + 1]), "r"(tagw));
                    return __all_sync(0xffffffffu, ((v[0] | v[2] | v[4] | v[6]) & 0x00010001u) == 0);
                };
                mbar_wait(raw + 8 * i);
                if (!current()) {
#pragma unroll 1
                    for (uint32_t it = 0;; it++) {
                        if (it > SPIN_LIMIT) __trap();
                        STAMP(16);
                        if (leader) mbar_expect_tx(retry, ABYTES);
                        bulk_load(src + half, reinterpret_cast<const char*>(prm.s->h) + (size_t)chunk * 524288 + (i - 32) * 16384 + half, ABYTES, retry);
                        mbar_wait(retry, rpar);
                        rpar ^= 1;
                        if (current()) break;
                    }
                }
                if (leader) mbar_arrive(full + 8 * i);
            }
        }
    } else {
        asm volatile("setmaxnreg.inc.sync.aligned.u32 216;");
        const int wg = warp >> 2, w = warp & 3, g = lane >> 2, c = lane & 3, at = tid & 127;
        float facc[4];
        float2 a[2], m0[2], a32[2], a128[2];
        auto load_const = [&]() {
            const float2* cp = reinterpret_cast<const float2*>(smem + OFF_CONST) + wg * 64 + w * 8 + g;
#pragma unroll
            for (int h = 0; h < 2; h++) { a[h] = cp[32 * h]; m0[h] = cp[128 + 32 * h]; a32[h] = cp[256 + 32 * h]; a128[h] = cp[384 + 32 * h]; }
        };
        if (wg == 0) {
            named_bar(0, 256);
            STAMPIF(tid == 0, 20);
        } else {
            const int pc = (at >> 5) * 256 + dt * 32 + (at & 31);
            const float lr = __bfloat162float(prm.lam_re[pc]), li = __bfloat162float(prm.lam_im[pc]), ld = __bfloat162float(prm.log_dt[pc]);
            const uint32_t dk = __ldg(reinterpret_cast<const uint32_t*>(prm.dskip + dt * 128) + (at & 63));
#pragma unroll
            for (int i = 0; i < 4; i++) sts128(sb + OFF_LIST + i * 2048 + at * 16, 0u, 0u, 0u, 0u);

            {
                reinterpret_cast<uint32_t*>(smem + OFF_DK)[at & 63] = dk;
                const float dtv = rbf(expf(ld));
                const float er = expf(dtv * lr);
                float sn, cs;
                sincospif(dtv * li * 0.318309886183790672f, &sn, &cs);
                const float ar = er * cs, ai = er * sn;
                const float nr = ar - 1.0f, ni = ai;
                const bool big = fabsf(lr) >= fabsf(li);
                const float t = (big ? li : lr) / (big ? lr : li), dn = big ? lr + li * t : lr * t + li;
                const float cr = (big ? nr + ni * t : nr * t + ni) / dn, ci = (big ? ni - nr * t : ni * t - nr) / dn;
                float2* cp = reinterpret_cast<float2*>(smem + OFF_CONST) + at;
                float2 pw = make_float2(ar, prm.swapped ? ai : -ai);
                cp[0] = pw;
                cp[128] = make_float2(prm.swapped ? -2.f * cr : 2.f * cr, -2.f * ci);
#pragma unroll
                for (int i = 1; i <= 7; i++) {
                    pw = cmul(pw, pw);
                    if (i == 5) cp[256] = pw;
                    if (i == 7) cp[384] = pw;
                }
                __syncwarp();
            }
            named_bar(2, 128);
            load_const();
            mbar_wait(bar_epoch);
            const uint32_t tag = *reinterpret_cast<volatile uint32_t*>(smem + OFF_EPOCH) + 1;
            asm volatile("st.relaxed.gpu.global.b64 [%0], %1;" ::"l"(&prm.s->carry[(chunk >> 2) * 4096 + pc * 4 + (chunk & 3)]), "l"((unsigned long long)(tag + 2)) : "memory");
            if (w == 2) st_cell(lane < 4 ? (uint4*)prm.s->rpack + cta * 4 + lane : (uint4*)prm.s->gpack + cta * 4 + (lane & 3), 0, 0, 0, 0, lane < 8);
            {
                const uint32_t nt = ((tag & 1) | ((tag & 2) << 15)) ^ 0x00010001u;
                st_cell(prm.s->hid + (cta & 1) * F_ + (cta >> 1) * 64 - 512 + (at & 63), nt, nt, nt, nt, has_gu && w >= 2);
            }
            named_bar(2, 128);
            if (at < 2) mbar_arrive(bar_init3);
            unsigned long long* pub = (w ? prm.s->gpack : prm.s->rpack) + cta * 8 + lane;
            asm volatile("" : "+l"(pub));
            STAMPIF(lane == 0, 52);
            mbar_wait(bar_rdone);

            if (w < 2) {
                const float2* red = reinterpret_cast<const float2*>(smem + OFF_RED) + w * 8 + (lane & 7);
                const float2 r0 = red[0], r1 = red[16], r2 = red[32], r3 = red[48];
                const float v0 = (r0.x + r1.x) + (r2.x + r3.x), v1 = (r0.y + r1.y) + (r2.y + r3.y);
                uint32_t pk2;
                if (w == 0) {
                    pk2 = pack_bf(v0, v1);
                    pk2 ^= (((pk2 >> 15) & 0x00010001u) * 0x7FFFu) ^ 0x80008000u;
                } else pk2 = pack_bf(sigmoidf_(rbf(v0)), sigmoidf_(rbf(v1)));
                if (lane < 8) asm volatile("st.relaxed.gpu.global.b64 [%0], %1;" ::"l"(pub), "l"(((unsigned long long)tag << 32) | pk2) : "memory");
                __syncwarp();
            }
            STAMPIF(at == 0, 24);
            uint32_t it = 0, pr[8], g1;
            mbar_wait(bar_init3);
            sleep_until(clk32() + (w < 2 ? G0 : G0 + 250));
            while (true) {
                bool ok = true;
#pragma unroll
                for (int k = 0; k < 4; k++) {
                    const ulonglong2 u = ld_relaxed2(&prm.s->rpack[k * 256 + 2 * at]);
                    ok = ok && (uint32_t)(u.x >> 32) == tag && (uint32_t)(u.y >> 32) == tag;
                    pr[2 * k] = (uint32_t)u.x; pr[2 * k + 1] = (uint32_t)u.y;
                }
                const unsigned long long u1 = ld_relaxed1(&prm.s->gpack[chunk * 64 + (at & 63)]);
                ok = ok && (uint32_t)(u1 >> 32) == tag;
                g1 = (uint32_t)u1;
                if (__all_sync(0xffffffffu, ok)) break;
                if (++it > SPIN_LIMIT) __trap();
            }
            STAMPIF(lane == 0, 25);
            uint32_t m = __vmaxu2(__vimax3_u16x2(__vimax3_u16x2(pr[0], pr[1], pr[2]), pr[3], pr[4]), __vimax3_u16x2(pr[5], pr[6], pr[7]));
            m = (max(m, m << 16) & 0xFFFF0000u) | (uint32_t)lane;
            const uint32_t m1 = __reduce_max_sync(0xffffffffu, m), m2 = __reduce_max_sync(0xffffffffu, m == m1 ? 0u : m);
            uint32_t* keys = reinterpret_cast<uint32_t*>(smem + OFF_KEYS);
            if (lane == 0) keys[w] = m2;
            sts128(sb + OFF_XS + 4096 + at * 16, pr[0], pr[1], pr[2], pr[3]);
            sts128(sb + OFF_XS + 6144 + at * 16, pr[4], pr[5], pr[6], pr[7]);
            *reinterpret_cast<uint32_t*>(smem + OFF_G + 4 * (at & 63)) = g1;
            named_bar(2, 128);
            const uint4 th4 = *reinterpret_cast<const uint4*>(keys);
            const uint32_t th = (max(min(min(th4.x, th4.y), min(th4.z, th4.w)) >> 16, 1u) - 1u) * 0x00010001u;
            uint32_t mask = 0;
#pragma unroll
            for (int k = 7; k >= 0; k--) mask = mask * 2 + __vminu2(__vmaxu2(pr[k], th) ^ th, 0x00010001u);
            uint32_t pos = 0;
            asm volatile("{ .reg .pred p; setp.ne.u32 p, %2, 0; @p atom.shared.add.u32 %0, [%1], %2; }" : "+r"(pos) : "r"(sb + OFF_KEYS + 16), "r"(__popc(mask)) : "memory");
            while (mask) {
                const int bit = __ffs(mask) - 1, k = bit & 7, hi = bit >> 4;
                mask &= mask - 1;
                const uint32_t sc = *reinterpret_cast<const uint16_t*>(smem + OFF_XS + 4096 + (k >> 2) * 2048 + at * 16 + (k & 3) * 4 + hi * 2);
                *reinterpret_cast<uint32_t*>(smem + OFF_LIST + 4 * pos++) = (sc << 16) | (0x8000u + 2047u - (uint32_t)((k >> 1) * 512 + 4 * at + 2 * (k & 1) + hi));
            }
            __syncwarp();
            if (lane == 0) mbar_arrive(bar_cand);
            STAMPIF(lane == 0, 26);
            mbar_wait(bar_order0);
        }

        float accA[64], accB[64];
        Ring ring = {bar_dummy, wg};
        {
            run_entries<0, 0>(ring, wg * 16, wg ? GU0 : RE0, accA, accB, facc, true);
            if (wg == 0) {
                float racc[4];
                mbar_wait(bar_vec);
                run_entries<0, 1>(ring, RE0, RE0 + 4, accA, accB, racc, false, true);
                mbar_wait(bar_init2);
                const uint32_t red = sb + OFF_RED + 4 * (w * 32 + (c >> 1) * 16 + g);
                run_entries<0, 0>(ring, RE0 + 4, RE0 + 5, accA, accB, facc, false, false, [&]() {
                    pin4(racc);
                    asm volatile("{ .reg .pred p; setp.ne.u32 p, %3, 0; @p st.shared.f32 [%0], %1; @p st.shared.f32 [%0 + 32], %2; }" ::"r"(red),
                                 "f"((w & 1) ? racc[1] : racc[0]), "f"((w & 1) ? racc[3] : racc[2]), "r"((uint32_t)((c & 1) == (w >> 1))) : "memory");
                    __syncwarp();
                    if (lane == 0) mbar_arrive(bar_rdone);
                    STAMPIF(lane == 0, 5);
                });
                run_entries<0, 0>(ring, RE0 + 5, 16, accA, accB, facc);
                if (lane == 0) mbar_arrive(bar_order0);
                mbar_wait(bar_init3);
                load_const();
                named_bar(3, 128);
            } else {
#pragma unroll
                for (int u = 0; u < 2; u++) {
                    mbar_wait(u ? bar_xs : bar_xs0);
                    run_entries<0, 2>(ring, GU0 + 8 * u, u ? 32 : GU0 + 8, accA, accB, facc, false, u == 0);
                }
                if (lane == 0) mbar_arrive(bar_order1);
            }
        }
        const uint32_t tag = *reinterpret_cast<volatile uint32_t*>(smem + OFF_EPOCH) + 1;
        const float2 a64[2] = {cmul(a32[0], a32[0]), cmul(a32[1], a32[1])};
        wgmma_wait<0>();
        pin64(accA); pin64(accB); pin4(facc);
        if (lane == 0) mbar_arrive(ring.prev);
        STAMPIF(at == 0, 28 + wg);
        GSTAMP(tid == 0, 1);

        const int tl = 32 * (g >> 1) + (g & 1) + 4 * w + 16 * wg, t0 = chunk * 128 + tl;
        float* op = prm.out + (size_t)t0 * D_ + dt * 128 + 4 * c;
        uint2 xv[8][2], dk[8];
        uint32_t gp[2], om[2], routed[2];
        auto row_setup = [&]() {
            const uint4 sa = *reinterpret_cast<const uint4*>(smem + OFF_SEL), sc = *reinterpret_cast<const uint4*>(smem + OFF_SEL + 16);
#pragma unroll
            for (int r = 0; r < 2; r++) {
                const uint32_t id = 0x8000u + 2047u - (uint32_t)(t0 + 2 * r);
                routed[r] = (uint16_t)sa.x == id || (uint16_t)sa.y == id || (uint16_t)sa.z == id || (uint16_t)sa.w == id ||
                            (uint16_t)sc.x == id || (uint16_t)sc.y == id || (uint16_t)sc.z == id || (uint16_t)sc.w == id;
                gp[r] = reinterpret_cast<const uint16_t*>(smem + OFF_G)[tl + 2 * r] * 0x00010001u;
                om[r] = pack_bf(1.0f - bf_hi(gp[r]), 1.0f - bf_hi(gp[r]));
            }
#pragma unroll
            for (int j = 0; j < 8; j++) dk[j] = lds64(sb + OFF_DK + 32 * j + 8 * c);
        };
        auto release = [&](uint32_t bar) {
            asm volatile("fence.proxy.async.shared::cta;" ::: "memory");
            __syncwarp();
            if (lane == 0) mbar_arrive(bar);
        };

        {
            const uint32_t t2 = tag & 3u;
            float2* cslot = &prm.s->carry[(wg * 512 + dt * 32 + w * 8 + g) * 4];
            const int j1 = chunk - 1 - c;
            unsigned long long v[2][4] = {{t2, t2, t2, t2}, {t2, t2, t2, t2}};
            auto poll = [&](int h) {
#pragma unroll
                for (int m = 0; m < 4; m++)
                    asm volatile("{ .reg .pred p; setp.ge.s32 p, %2, %3; @p ld.relaxed.gpu.global.b64 %0, [%1]; }"
                                 : "+l"(v[h][m]) : "l"(cslot + (j1 >> 2) * 4096 + c - m * 4096 + h * 1024), "r"(j1), "r"(4 * m) : "memory");
            };
            float2 e[2], w0[2];
            auto chain = [&](int h, int s0, int s1) {
                float (&acc)[64] = h ? accB : accA;
                if (s0 == 1) e[h] = make_float2(acc[0], acc[2]);
#pragma unroll
                for (int s = s0; s < s1; s++) {
                    const int i0 = 4 * (s >> 1) + (s & 1);
                    e[h] = cfma(make_float2(a[h].x, -a[h].y), e[h], make_float2(acc[i0], acc[i0 + 2]));
                }
                asm volatile("" : "+f"(e[h].x), "+f"(e[h].y), "+f"(accB[0]), "+f"(accB[2]));
                gap();
            };
            auto publish = [&](int h) {
                float2 f = make_float2(fmaf(m0[h].x, e[h].x, m0[h].y * e[h].y), fmaf(-m0[h].x, e[h].y, m0[h].y * e[h].x));
                float2 y = make_float2(__shfl_up_sync(0xffffffffu, f.x, 1, 4), __shfl_up_sync(0xffffffffu, f.y, 1, 4));
                if (c >= 1) f = cfma(a32[h], y, f);
                y = make_float2(__shfl_up_sync(0xffffffffu, f.x, 2, 4), __shfl_up_sync(0xffffffffu, f.y, 2, 4));
                if (c >= 2) f = cfma(a64[h], y, f);
                asm volatile("{ .reg .pred p; .reg .b64 t; setp.eq.u32 p, %3, 3; mov.b64 t, {%1, %2}; @p st.relaxed.gpu.global.b64 [%0], t; }"
                             ::"l"(cslot + (chunk >> 2) * 4096 + (chunk & 3) + h * 1024), "r"((__float_as_uint(f.x) & ~3u) | t2), "r"(__float_as_uint(f.y)), "r"(c) : "memory");
                w0[h] = make_float2(__shfl_up_sync(0xffffffffu, f.x, 1, 4), __shfl_up_sync(0xffffffffu, f.y, 1, 4));
                if (c == 0) w0[h] = make_float2(0.f, 0.f);
            };
            auto scale = [&](int h, int n0, int n1) {
                float (&acc)[64] = h ? accB : accA;
#pragma unroll
                for (int n = n0; n < n1; n++) {
                    asm volatile("{ .reg .f32 a, b, c, d, n; neg.f32 n, %4; mul.f32 a, %1, %5; mul.f32 b, %0, %5; mul.f32 c, %3, %5; mul.f32 d, %2, %5;\n"
                                 "fma.rn.f32 %0, %0, %4, a; fma.rn.f32 %1, %1, n, b; fma.rn.f32 %2, %2, %4, c; fma.rn.f32 %3, %3, n, d; }"
                                 : "+f"(acc[4 * n]), "+f"(acc[4 * n + 2]), "+f"(acc[4 * n + 1]), "+f"(acc[4 * n + 3]) : "f"(m0[h].x), "f"(m0[h].y));
                    gap();
                }
            };
            auto carry = [&](int h) {
                const float2 one = make_float2(1.f, 0.f), a256 = cmul(a128[h], a128[h]);
                float2 a512 = cmul(a256, a256), pw128 = cmul((j1 & 1) ? a128[h] : one, (j1 & 2) ? a256 : one);
                float2 pw32 = cmul((c & 1) ? a32[h] : one, (c & 2) ? a64[h] : one);
                asm volatile("" : "+f"(a512.x), "+f"(a512.y), "+f"(pw128.x), "+f"(pw128.y), "+f"(pw32.x), "+f"(pw32.y));
                STAMPIF(lane == 0 && !h, 34 + 2 * wg);
                uint32_t it = 0;
                while (!__all_sync(0xffffffffu, ((((uint32_t)v[h][0] ^ t2) | ((uint32_t)v[h][1] ^ t2) | ((uint32_t)v[h][2] ^ t2) | ((uint32_t)v[h][3] ^ t2)) & 3u) == 0)) {
                    poll(h);
                    if (++it > SPIN_LIMIT) __trap();
                }
                STAMPIF(lane == 0 && !h, 35 + 2 * wg);
                if (!h) poll(1);
                float2 hin = make_float2(__uint_as_float((uint32_t)v[h][3]), __uint_as_float((uint32_t)(v[h][3] >> 32)));
#pragma unroll
                for (int m = 2; m >= 0; m--) hin = cfma(a512, hin, make_float2(__uint_as_float((uint32_t)v[h][m]), __uint_as_float((uint32_t)(v[h][m] >> 32))));
                hin = cmul(pw128, hin);
                hin.x += __shfl_xor_sync(0xffffffffu, hin.x, 1); hin.y += __shfl_xor_sync(0xffffffffu, hin.y, 1);
                hin.x += __shfl_xor_sync(0xffffffffu, hin.x, 2); hin.y += __shfl_xor_sync(0xffffffffu, hin.y, 2);
                w0[h] = cfma(pw32, hin, w0[h]);
            };
            chain(0, 1, 32);
            publish(0);
            chain(1, 1, 8);
            STAMPIF(lane == 0, 30 + 2 * wg);
            chain(1, 8, 32);
            publish(1);
            gap();
            scale(0, 0, POLL_S);
            poll(0);
            scale(0, POLL_S, 16);
            carry(0);
            if (wg) mbar_wait(bar_out + 24);
            STAMPIF(lane == 0, 38 + 2 * wg);
            const uint32_t stg = sb + OFF_STG + prm.swapped * 8192 + w * 1024 + (lane & 7) * 128 + (((lane >> 3) ^ (lane & 7)) << 4);
            const uint32_t second = prm.swapped ? -8192 : 8192;
            const uint32_t keep = c == (g >> 1) ? 0xFFFEFFFEu : 0xFFFFFFFFu, tagw = ((t2 & 1) | ((t2 & 2) << 15)) & ~keep;
#pragma unroll
            for (int h = 0; h < 2; h++) {
                float (&acc)[64] = h ? accB : accA;
                uint32_t ra[16], ia[16];
                if (h) {
                    scale(1, 0, 5);
                    release(bar_st + 32 * wg + 8);
                    scale(1, 5, 16);
                    carry(1);
                }
                auto stage = [&](uint32_t (&r)[16], uint32_t base, int j) {
                    stsm4((base ^ ((j & 1) * 64)) + (j >> 1) * 4096, r[4 * j], r[4 * j + 1], r[4 * j + 2], r[4 * j + 3]);
                };
#pragma unroll
                for (int n = 0; n < 16; n++) {
                    const float2 y = cfma(a[h], w0[h], make_float2(acc[4 * n], acc[4 * n + 2]));
                    w0[h] = cfma(a[h], y, make_float2(acc[4 * n + 1], acc[4 * n + 3]));
                    ra[n] = pack_bf(y.x, w0[h].x);
                    ia[n] = pack_bf(y.y, w0[h].y);
                    if (!(n & 1)) { ra[n] = (ra[n] & keep) | tagw; ia[n] = (ia[n] & keep) | tagw; }
                    if (!h && (n & 3) == 3) {
                        if (n == 11) { asm volatile("" : "+r"(ra[n]), "+r"(ia[n])); gap(); release(bar_st + 32 * wg); }
                        stage(ra, stg, n >> 2); stage(ia, stg + second, n >> 2);
                        gap();
                    }
                }
                if (h) {
                    STAMPIF(lane == 0, 39 + 2 * wg);
                    mbar_wait(bar_out + 32 * wg);
                    if (prm.swapped) {
#pragma unroll
                        for (int n = 0; n < 16; n++) { const uint32_t t = ra[n]; ra[n] = ia[n]; ia[n] = t; }
                    }
                    const uint32_t st0 = stg - prm.swapped * 8192;
#pragma unroll
                    for (int j = 0; j < 4; j++) stage(ra, st0, j);
                    mbar_wait(bar_xs);
                    row_setup();
                    release(bar_st + 32 * wg + 16);
                    mbar_wait(bar_out + 32 * wg + 8);
#pragma unroll
                    for (int j = 0; j < 4; j++) stage(ia, st0 + 8192, j);
                    release(bar_st + 32 * wg + 24);
                }
                STAMPIF(lane == 0, 42 + 2 * wg + h);
            }
        }

        const uint32_t xr = 2 * (g & 3) + (g >> 2), xa = sb + (wg ? OFF_STG : OFF_W) + (16 * w + xr) * 128 + (((c >> 1) ^ xr) << 4) + (c & 1) * 8;
        auto handover = [&](uint32_t bar) {
            const uint4 z = ldsm4(sb + OFF_KEYS + 16);
            if (lane == 1) mbar_arrive(bar + z.x);
        };
        auto load_x = [&](int j0, int j1) {
#pragma unroll
            for (int j = j0; j < j1; j++)
#pragma unroll
                for (int r = 0; r < 2; r++) xv[j][r] = lds64((xa ^ (32 * (j & 3))) + (j >> 2) * ABYTES + r * 1024);
        };
        auto skip_term = [&](int j0, int j1) {
#pragma unroll
            for (int j = j0; j < j1; j++)
#pragma unroll
                for (int r = 0; r < 2; r++) {
                    xv[j][r].x = mul_bf2(xv[j][r].x, fma_bf2(gp[r], dk[j].x, om[r]));
                    xv[j][r].y = mul_bf2(xv[j][r].y, fma_bf2(gp[r], dk[j].y, om[r]));
                    asm volatile("" : "+r"(xv[j][r].x), "+r"(xv[j][r].y));
                }
        };
        auto finish = [&](float (&acc)[64], int j, bool gaps) {
#pragma unroll
            for (int r = 0; r < 2; r++) {
                const int o = 8 * j + 2 * r;
                const float gv = bf_hi(gp[r]);
                acc[o] = fmaf(gv, acc[o], bf_lo(xv[j][r].x)); acc[o + 1] = fmaf(gv, acc[o + 1], bf_hi(xv[j][r].x));
                acc[o + 4] = fmaf(gv, acc[o + 4], bf_lo(xv[j][r].y)); acc[o + 5] = fmaf(gv, acc[o + 5], bf_hi(xv[j][r].y));
                stg4_unless(op + r * 2 * D_ + 16 * j, acc[o], acc[o + 1], acc[o + 4], acc[o + 5], routed[r]);
                if (gaps) gap();
            }
        };
        auto finish_routed = [&](float (&acc)[64]) {
#pragma unroll
            for (int r = 0; r < 2; r++)
                if (routed[r]) {
#pragma unroll
                    for (int j = 0; j < 8; j++) red4(op + r * 2 * D_ + 16 * j, acc[8 * j + 2 * r], acc[8 * j + 2 * r + 1], acc[8 * j + 2 * r + 4], acc[8 * j + 2 * r + 5]);
                }
            __syncwarp();
        };
        const uint32_t xbuf = sb + slot_off(FIN) + w * 2048 + lane * 16;

        if (wg == 1) {
            float outB[64];
            const uint32_t tagw = (tag & 1) | ((tag & 2) << 15);
            mbar_wait(bar_fp);
            {
                const float4 o4 = lds128f(sb + OFF_XS + at * 16);
                const float o[4] = {o4.x, o4.y, o4.z, o4.w};
                float v[4];
#pragma unroll
                for (int u = 0; u < 4; u++) {
                    v[u] = rbf(facc[u] + o[u]);
                    if (!(cta & 1)) v[u] = __fdividef(v[u], 1.0f + __expf(-v[u]));
                }
                uint32_t w0 = pack_bf(v[0], v[1]), w1 = pack_bf(v[2], v[3]), cell[4];
                if (c == (g & 3)) { w0 = (w0 & 0xFFFEFFFEu) | tagw; w1 = (w1 & 0xFFFEFFFEu) | tagw; }
#pragma unroll
                for (int u = 0; u < 4; u++) {
                    const uint32_t s0 = __shfl_sync(0xffffffffu, w0, u, 4), s1 = __shfl_sync(0xffffffffu, w1, u, 4);
                    cell[u] = (c & 1) ? s1 : s0;
                }
                st_cell(prm.s->hid + (cta & 1) * F_ + (cta >> 1) * 64 - 512 + w * 16 + g + 8 * c, cell[0], cell[1], cell[2], cell[3], has_gu && c < 2);
            }
            release(bar_hpub);
            STAMPIF(lane == 0, 47);
            mbar_wait(bar_xb);
            load_x(0, 8);
            release(bar_xbfree);
            skip_term(0, 8);
            STAMPIF(lane == 0, 46);
            {
                uint4 hv[4], hu[4];
                const uint32_t ha = sb + OFF_XS + at * 16, hl = sb + OFF_XS + 6144 + (at & 63) * 16;
#pragma unroll 1
                for (uint32_t it = 0;; it++) {
                    mbar_wait(bar_hraw, it & 1);
                    uint32_t bad = 0;
#pragma unroll
                    for (int i = 0; i < 4; i++) {
                        hv[i] = lds128(i < 3 ? ha + i * 2048 : hl); hu[i] = lds128((i < 3 ? ha + i * 2048 : hl) + ABYTES);
                        bad |= (((c & 2) ? ((c & 1) ? hv[i].w : hv[i].z) : ((c & 1) ? hv[i].y : hv[i].x)) ^ tagw) |
                               (((c & 2) ? ((c & 1) ? hu[i].w : hu[i].z) : ((c & 1) ? hu[i].y : hu[i].x)) ^ tagw);
                    }
                    uint32_t again;
                    asm volatile("{ .reg .pred p, q; setp.ne.u32 q, %1, 0; barrier.red.or.pred.aligned p, 2, 128, q; selp.u32 %0, 1, 0, p; }" : "=r"(again) : "r"(bad & 0x00010001u) : "memory");
                    if (!uni(again)) break;
                    if (it > SPIN_LIMIT) __trap();
                    if (w == 0) load_hid();
                }
                STAMPIF(lane == 0, 48);
#pragma unroll
                for (int i = 0; i < 4; i++)
                    sts128(i < 3 ? ha + i * 2048 : hl, mul_bf2(hv[i].x, hu[i].x), mul_bf2(hv[i].y, hu[i].y), mul_bf2(hv[i].z, hu[i].z), mul_bf2(hv[i].w, hu[i].w));
                asm volatile("fence.proxy.async.shared::cta;" ::: "memory");
                __syncwarp();
                if (lane == 0) mbar_arrive(bar_hs);
                STAMPIF(lane == 0, 49);
            }
            mbar_wait(bar_order2);
            static_for<NENT - FIN>([&](auto u) {
                run_small<1, FIN + u>(outB);
                if (u == 2) { wgmma_wait<2>(); if (lane == 0) mbar_arrive(bar_fold); }
            });
            if (lane == 0) mbar_arrive(bar_order3);
            wgmma_wait<0>();
            pin64(outB);
            KSTAMP(2 * NENT - FIN);
            STAMPIF(at == 0, 50);
#pragma unroll
            for (int q = 0; q < 2; q++) {
                uint4 pb[8];
                mbar_wait(bar_accb + 8 * q);
#pragma unroll
                for (int v = 0; v < 8; v++) pb[v] = ldsm4(xbuf + (2 * q + (v >> 2)) * ABYTES + (v & 3) * 512);
#pragma unroll
                for (int v = 0; v < 8; v++) {
                    const int o = 32 * q + 4 * v;
                    outB[o] += __uint_as_float(pb[v].x); outB[o + 1] += __uint_as_float(pb[v].y);
                    outB[o + 2] += __uint_as_float(pb[v].z); outB[o + 3] += __uint_as_float(pb[v].w);
                    if (v & 1) finish(outB, 4 * q + (v >> 1), false);
                }
            }
            finish_routed(outB);
            STAMPIF(lane == 0, 51);
        } else {
            float outA[64], outB[64], gacc[4];
            ring.slot = 32 % NST;
            ring.prev = bar_dummy;
            mbar_wait(bar_order1);
            run_entries<1, 2>(ring, 32, GU0 + 32, outA, outB, gacc, true, true);
            run_entries<1, 0>(ring, GU0 + 32, GU0 + 33, outA, outB, gacc, false, false, [&]() {
                pin4(gacc);
                sts128(sb + OFF_XS + at * 16, __float_as_uint(gacc[0]), __float_as_uint(gacc[1]), __float_as_uint(gacc[2]), __float_as_uint(gacc[3]));
                __syncwarp();
                if (lane == 0) mbar_arrive(bar_fp);
            });
            mbar_wait(bar_xa);
            run_entries<1, 0>(ring, GU0 + 33, GU0 + 34, outA, outB, gacc, false, false, [&]() { load_x(0, 2); });
            load_x(2, 4);
            run_entries<1, 0>(ring, GU0 + 34, GU0 + 35, outA, outB, gacc, false, false, [&]() { load_x(4, 6); });
            load_x(6, 8);
            run_entries<1, 0>(ring, GU0 + 35, GU0 + 36, outA, outB, gacc, false, false, [&]() { release(bar_xafree); });
            run_entries<1, 0>(ring, GU0 + 36, FIN, outA, outB, gacc);
            static_for<NENT - FIN>([&](auto u) {
                mbar_wait(full + 8 * (FIN + u));
                run_small<0, FIN + u>(outA);
                if (u == 5 && lane == 0) mbar_arrive(bar_order2);
                wgmma_wait<1>();
                if (lane == 0) mbar_arrive(empty + 8 * (FIN + u - 1));
                if (u < 4) skip_term(2 * u, 2 * u + 2);
            });
            wgmma_wait<0>();
            pin64(outA); pin64(outB);
            STAMPIF(at == 0, 53);
            GSTAMP(at == 0, 2);
            auto dump = [&](int v) {
                if (v == 4) mbar_wait(bar_fold);
                stsm4(xbuf + (v >> 2) * ABYTES + (v & 3) * 512, __float_as_uint(outB[4 * v]), __float_as_uint(outB[4 * v + 1]), __float_as_uint(outB[4 * v + 2]),
                      __float_as_uint(outB[4 * v + 3]));
                if ((v & 7) == 7) handover(bar_accb + (v & 8));
            };
            mbar_wait(empty + 8 * FIN);
#pragma unroll
            for (int j = 0; j < 8; j++) {
                finish(outA, j, true);
#pragma unroll
                for (int v = j * NDUMP / 8; v < (j + 1) * NDUMP / 8; v++) dump(v);
            }
            STAMPIF(lane == 0, 54);
            if (DWAIT) mbar_wait(bar_order3);
#pragma unroll
            for (int v = NDUMP; v < 16; v++) dump(v);
            STAMPIF(lane == 0, 55);
            finish_routed(outA);
            const uint2 sk = lds64(sb + OFF_SEL + 8 * c), fk = lds64(sb + OFF_FAC + 8 * c);
            float* y0 = prm.out + (~sk.x & 2047u) * D_ + (cta & 15) * 64 + w * 16 + g;
            float* y1 = prm.out + (~sk.y & 2047u) * D_ + (cta & 15) * 64 + w * 16 + g;
            float yacc[4];
            const uint64_t dw = make_desc(sb), dh = (uint64_t)(((sb + OFF_XS) & 0x3FFFF) >> 4) | ((uint64_t)8 << 16) | ((uint64_t)8 << 32);
            mbar_wait(bar_hs);
            mbar_wait(bar_zero);
            mbar_wait(bar_dn);
            mbar_wait(bar_order3);
            STAMPIF(at == 0, 2);
            wgmma_fence();
#pragma unroll
            for (int n = 0; n < 28; n++) wgmma_n8<1, 1>(yacc, dw + (dn_off(n >> 2) >> 4) + (n & 3) * 128, dh + n * 16, n > 0);
            wgmma_commit();
            wgmma_wait<0>();
            pin4(yacc);
            atomicAdd(y0, yacc[0] * __uint_as_float(fk.x)); atomicAdd(y1, yacc[1] * __uint_as_float(fk.y));
            atomicAdd(y0 + 8, yacc[2] * __uint_as_float(fk.x)); atomicAdd(y1 + 8, yacc[3] * __uint_as_float(fk.y));
            STAMPIF(lane == 0, 3);
        }
    }
}

typedef CUresult (*EncodeFn)(CUtensorMap*, CUtensorMapDataType, cuuint32_t, void*, const cuuint64_t*, const cuuint64_t*, const cuuint32_t*,
                             const cuuint32_t*, CUtensorMapInterleave, CUtensorMapSwizzle, CUtensorMapL2promotion, CUtensorMapFloatOOBfill);

bool encode(EncodeFn fn, CUtensorMap* m, const void* ptr, int rank, const cuuint64_t* dims, const cuuint64_t* strides, const cuuint32_t* box,
            CUtensorMapSwizzle sw = CU_TENSOR_MAP_SWIZZLE_128B, CUtensorMapL2promotion promo = CU_TENSOR_MAP_L2_PROMOTION_NONE) {
    const cuuint32_t es[5] = {1, 1, 1, 1, 1};
    return fn(m, CU_TENSOR_MAP_DATA_TYPE_BFLOAT16, rank, const_cast<void*>(ptr), dims, strides, box, es, CU_TENSOR_MAP_INTERLEAVE_NONE,
              sw, promo, CU_TENSOR_MAP_FLOAT_OOB_FILL_NONE) == CUDA_SUCCESS;
}

}

extern "C" void kernel_launch(void* const* d_in, const int* in_sizes, int n_in, void* d_out, int out_size) {
    (void)in_sizes; (void)n_in; (void)out_size;
    Params prm;
    prm.x = (const __nv_bfloat16*)d_in[0];
    prm.lam_re = (const __nv_bfloat16*)d_in[1];
    prm.lam_im = (const __nv_bfloat16*)d_in[2];
    prm.b_re = (const __nv_bfloat16*)d_in[3];
    prm.b_im = (const __nv_bfloat16*)d_in[4];
    prm.c_re = (const __nv_bfloat16*)d_in[5];
    prm.c_im = (const __nv_bfloat16*)d_in[6];
    prm.log_dt = (const __nv_bfloat16*)d_in[7];
    prm.dskip = (const __nv_bfloat16*)d_in[8];
    prm.w_r = (const __nv_bfloat16*)d_in[10];
    prm.gate_w = (const __nv_bfloat16*)d_in[14];
    prm.out = (float*)d_out;
    cudaGetSymbolAddress((void**)&prm.s, g_scratch);
    int dev = 0, sms = 0;
    cudaGetDevice(&dev);
    cudaDeviceGetAttribute(&sms, cudaDevAttrMultiProcessorCount, dev);
    prm.by_smid = sms == NGRID;
    prm.swapped = prm.b_im < prm.b_re;

    void* fnp = nullptr;
    cudaDriverEntryPointQueryResult qr;
    cudaGetDriverEntryPoint("cuTensorMapEncodeTiled", &fnp, cudaEnableDefault, &qr);
    EncodeFn fn = (EncodeFn)fnp;
    cudaFuncSetAttribute(fused_kernel, cudaFuncAttributeMaxDynamicSharedMemorySize, SMEM_BYTES);

    CUtensorMap mX, mB, mCre, mCim, mWg, mWu, mWd, mXr, mXe;
    const cuuint64_t row = 2048;
    {
        const cuuint64_t dims[4] = {1024, 2, 4, 976}, st[3] = {row, 32 * row, 2 * row};
        const cuuint32_t box[4] = {64, 2, 4, 16};
        encode(fn, &mX, prm.x, 4, dims, st, box, CU_TENSOR_MAP_SWIZZLE_128B, PROMO);
    }
    {
        const char *lo = (const char*)(prm.swapped ? prm.b_im : prm.b_re), *hi = (const char*)(prm.swapped ? prm.b_re : prm.b_im);
        const cuuint64_t dims[5] = {1024, 8, 2, 96, 2}, st[4] = {row, (cuuint64_t)(hi - lo), 8 * row, 256 * row};
        const cuuint32_t box[5] = {64, 8, 2, 4, 2};
        encode(fn, &mB, lo, 5, dims, st, box, CU_TENSOR_MAP_SWIZZLE_128B, PROMO);
    }
    {
        const cuuint64_t dims[5] = {1024, 2, 4, 2, 64}, st[4] = {row, 4 * row, 2 * row, 16 * row};
        const cuuint32_t box[5] = {64, 2, 4, 2, 8};
        encode(fn, &mCre, prm.c_re, 5, dims, st, box);
        encode(fn, &mCim, prm.c_im, 5, dims, st, box);
    }
    {
        const cuuint64_t dims[2] = {F_, D_}, st[1] = {F_ * 2}, dimsd[2] = {D_, F_}, std_[1] = {row};
        const cuuint32_t box[2] = {64, 32}, boxd[2] = {64, 64};
        encode(fn, &mWg, d_in[11], 2, dims, st, box, CU_TENSOR_MAP_SWIZZLE_128B, CU_TENSOR_MAP_L2_PROMOTION_NONE);
        encode(fn, &mWu, d_in[12], 2, dims, st, box, CU_TENSOR_MAP_SWIZZLE_128B, CU_TENSOR_MAP_L2_PROMOTION_NONE);
        encode(fn, &mWd, d_in[13], 2, dimsd, std_, boxd, CU_TENSOR_MAP_SWIZZLE_128B, CU_TENSOR_MAP_L2_PROMOTION_NONE);
    }
    {
        const cuuint64_t dims[3] = {D_ - 192, S_, 4}, st[2] = {row, 128};
        const cuuint32_t box[3] = {64, 16, 4};
        encode(fn, &mXr, prm.x, 3, dims, st, box, CU_TENSOR_MAP_SWIZZLE_128B, CU_TENSOR_MAP_L2_PROMOTION_NONE);
    }
    {
        const cuuint64_t dims[5] = {D_, 2, 2, 2, 976}, st[4] = {64 * row, row, 32 * row, 2 * row};
        const cuuint32_t box[5] = {64, 2, 2, 2, 8};
        encode(fn, &mXe, prm.x, 5, dims, st, box);
    }
    fused_kernel<<<NGRID, 384, SMEM_BYTES, cudaStreamPerThread>>>(prm, mX, mB, mCre, mCim, mWg, mWu, mWd, mXr, mXe);
}
```

```cpp
#include <cuda_runtime.h>
#include <cuda_bf16.h>
#include <cuda.h>
#include <stdint.h>

namespace {

constexpr int S_ = 2048, D_ = 1024, F_ = 3584;
constexpr int NCTA = 128, NGRID = 132;
#define XE_ 58
#define GU0_ 18
constexpr int NENT = 64, FIN = 58, XE = XE_;
constexpr int NST = 5;
constexpr int RE0 = 4;
constexpr int GU0 = GU0_;
constexpr uint32_t SLOT = 32768, ABYTES = 8192, WBYTES = 4096;
constexpr uint32_t OFF_XS = NST * SLOT;
constexpr uint32_t OFF_LIST = OFF_XS + 8192;
constexpr uint32_t OFF_W = OFF_XS + 16384;
constexpr uint32_t OFF_STG = OFF_W + 32768;
__host__ __device__ constexpr uint32_t slot_off(int i) { return i < XE ? (i % NST) * SLOT : i == XE ? OFF_W : ((i - 1) % NST) * SLOT; }
__host__ __device__ constexpr uint32_t dn_off(int u) { return u < 2 ? OFF_STG + u * ABYTES : u == 2 ? OFF_XS + ABYTES : slot_off(FIN - 2 + u); }
constexpr uint32_t OFF_CONST = OFF_STG;
constexpr uint32_t OFF_RED = OFF_STG + 4096;
constexpr uint32_t OFF_FULL = OFF_STG + 16384;
constexpr uint32_t OFF_EMPTY = OFF_FULL + 120 * 8;
constexpr uint32_t OFF_G = OFF_EMPTY + 88 * 8;
constexpr uint32_t OFF_DK = OFF_G + 256;
constexpr uint32_t OFF_KEYS = OFF_DK + 256;
constexpr uint32_t OFF_SEL = OFF_KEYS + 32;
constexpr uint32_t OFF_FAC = OFF_SEL + 32;
constexpr uint32_t OFF_EPOCH = OFF_FAC + 32;
constexpr uint32_t OFF_PROF = OFF_EPOCH + 16;
constexpr uint32_t SMEM_BYTES = OFF_PROF + 768;
static_assert(SMEM_BYTES <= 232448, "smem");

constexpr uint32_t sb = 1024;
constexpr uint32_t SPIN_LIMIT = 1u << 18;

struct Scratch {
    unsigned int cnt[2 * 32];
    unsigned long long rpack[S_ / 2];
    unsigned long long gpack[S_ / 2];
    uint4 time[NCTA];
    float2 carry[16 * 1024];
    uint4 hid[2 * F_];
    uint4 h[8 * 4 * 256 * 64];
};
__device__ __align__(128) Scratch g_scratch;
#define STAMPW(cond, w) do {} while (0)
#define LATE(i, tt) do {} while (0)
#define LANDED(i) do {} while (0)
#define GSTAMP(cond, w) do {} while (0)
#define STAMPIF(cond, i) STAMPW(cond, 72 + (i))
#define STAMP(i) STAMPW(1, 72 + (i))
#define KSTAMP(i) STAMPW((threadIdx.x & 127) == 0, i)

struct Params {
    const __nv_bfloat16 *x, *b_re, *b_im;
    int by_smid;
    int swapped;
    const __nv_bfloat16 *lam_re, *lam_im, *c_re, *c_im, *log_dt, *dskip, *w_r, *gate_w;
    float* out;
    Scratch* s;
};

__device__ __forceinline__ uint32_t smem_u32(const void* p) { return (uint32_t)__cvta_generic_to_shared(p); }
__device__ __forceinline__ void mbar_init(uint32_t bar, uint32_t cnt) { asm volatile("mbarrier.init.shared::cta.b64 [%0], %1;" ::"r"(bar), "r"(cnt) : "memory"); }
__device__ __forceinline__ void mbar_expect_tx(uint32_t bar, uint32_t bytes) { asm volatile("mbarrier.arrive.expect_tx.shared::cta.b64 _, [%0], %1;" ::"r"(bar), "r"(bytes) : "memory"); }
__device__ __forceinline__ void mbar_arrive(uint32_t bar) { asm volatile("mbarrier.arrive.shared::cta.b64 _, [%0];" ::"r"(bar) : "memory"); }
__device__ __forceinline__ void mbar_wait(uint32_t bar, uint32_t parity = 0) {
    asm volatile("{ .reg .pred p; .reg .u32 n;\n"
                 "mbarrier.try_wait.parity.shared::cta.b64 p, [%0], %1;\n"
                 "@p bra.uni DONE;\n"
                 "mov.u32 n, 0;\n"
                 "AGAIN: mbarrier.try_wait.parity.shared::cta.b64 p, [%0], %1;\n"
                 "@p bra.uni DONE;\n"
                 "add.u32 n, n, 1;\n"
                 "setp.lt.u32 p, n, %2;\n"
                 "@p bra.uni AGAIN;\n"
                 "trap;\n"
                 "DONE: }" ::"r"(bar), "r"(parity), "n"(SPIN_LIMIT) : "memory");
}
__device__ __forceinline__ bool elect_one() {
    uint32_t pred;
    asm volatile("{ .reg .pred P; elect.sync _|P, 0xffffffff; selp.b32 %0, 1, 0, P; }" : "=r"(pred));
    return pred;
}
__device__ __forceinline__ void named_bar(int id, int n) { asm volatile("bar.sync %0, %1;" ::"r"(id), "r"(n) : "memory"); }

#define ONE "{ .reg .pred e; elect.sync _|e, 0xffffffff;\n@e "
template <int N> __device__ __forceinline__ void mbar_init_n(uint32_t bar, uint32_t cnt, uint32_t extra = 0) {
    if (elect_one()) {
#pragma unroll
        for (int i = 0; i < N; i++) mbar_init(bar + 8 * i, i == N - 1 ? cnt + extra : cnt);
        asm volatile("fence.mbarrier_init.release.cluster;" ::: "memory");
    }
    __syncwarp();
}
__device__ __forceinline__ void bulk_load(uint32_t dst, const void* src, uint32_t bytes, uint32_t bar) {
    asm volatile(ONE "cp.async.bulk.shared::cluster.global.mbarrier::complete_tx::bytes [%0], [%1], %2, [%3]; }" ::"r"(dst), "l"(src), "r"(bytes), "r"(bar) : "memory");
}
__device__ __forceinline__ void sts128(uint32_t a, uint32_t x, uint32_t y, uint32_t z, uint32_t w) {
    asm volatile("st.shared.v4.u32 [%0], {%1,%2,%3,%4};" ::"r"(a), "r"(x), "r"(y), "r"(z), "r"(w) : "memory");
}
__device__ __forceinline__ uint2 lds64(uint32_t a) {
    uint2 v;
    asm volatile("ld.shared.v2.u32 {%0,%1}, [%2];" : "=r"(v.x), "=r"(v.y) : "r"(a) : "memory");
    return v;
}
__device__ __forceinline__ uint32_t clk32() { uint32_t c; asm volatile("mov.u32 %0, %%clock;" : "=r"(c)); return c; }
__device__ __forceinline__ void gap() { asm volatile("pmevent 1;" ::: "memory"); }
__device__ __forceinline__ void pace_until(uint32_t t) { while ((int)(clk32() - t) < 0) {} }
#define SLEEP_MARGIN 200
__device__ __forceinline__ void sleep_until(uint32_t t) {
    while ((int)(clk32() + SLEEP_MARGIN - t) < 0) __nanosleep(40);
    pace_until(t);
}
__device__ __forceinline__ void tma2(uint32_t dst, const CUtensorMap* m, int c0, int c1, uint32_t bar, uint64_t pol) {
    asm volatile(ONE "cp.async.bulk.tensor.2d.shared::cluster.global.mbarrier::complete_tx::bytes.L2::cache_hint [%0], [%1, {%3, %4}], [%2], %5; }"
                 ::"r"(dst), "l"(m), "r"(bar), "r"(c0), "r"(c1), "l"(pol) : "memory");
}
__device__ __forceinline__ void tma3(uint32_t dst, const CUtensorMap* m, int c0, int c1, uint32_t bar) {
    asm volatile(ONE "cp.async.bulk.tensor.3d.shared::cluster.global.mbarrier::complete_tx::bytes [%0], [%1, {%3, %4, %5}], [%2]; }"
                 ::"r"(dst), "l"(m), "r"(bar), "r"(c0), "r"(c1), "r"(0) : "memory");
}
__device__ __forceinline__ void tma4(uint32_t dst, const CUtensorMap* m, int c0, int c3, uint32_t bar) {
    asm volatile(ONE "cp.async.bulk.tensor.4d.shared::cluster.global.mbarrier::complete_tx::bytes [%0], [%1, {%3, %5, %5, %4}], [%2]; }"
                 ::"r"(dst), "l"(m), "r"(bar), "r"(c0), "r"(c3), "r"(0) : "memory");
}
__device__ __forceinline__ void tma5(uint32_t dst, const CUtensorMap* m, int c0, int c4, uint32_t bar) {
    asm volatile(ONE "cp.async.bulk.tensor.5d.shared::cluster.global.mbarrier::complete_tx::bytes [%0], [%1, {%3, %5, %5, %5, %4}], [%2]; }"
                 ::"r"(dst), "l"(m), "r"(bar), "r"(c0), "r"(c4), "r"(0) : "memory");
}
__device__ __forceinline__ void tma5b(uint32_t dst, const CUtensorMap* m, int c0, int c3, uint32_t bar) {
    asm volatile(ONE "cp.async.bulk.tensor.5d.shared::cluster.global.mbarrier::complete_tx::bytes [%0], [%1, {%3, %5, %5, %4, %5}], [%2]; }"
                 ::"r"(dst), "l"(m), "r"(bar), "r"(c0), "r"(c3), "r"(0) : "memory");
}
__device__ __forceinline__ void prefetch_l2(const void* p) {
    asm volatile("cp.async.ca.shared.global.L2::256B [%0], [%1], 4;" ::"r"(sb + OFF_EPOCH + 12), "l"(p) : "memory");
}

__device__ __forceinline__ uint32_t lds32(uint32_t a) {
    uint32_t v;
    asm volatile("ld.volatile.shared.u32 %0, [%1];" : "=r"(v) : "r"(a) : "memory");
    return v;
}
__device__ __forceinline__ uint32_t uni(uint32_t v) { return __shfl_sync(0xffffffffu, v, 0); }   __device__ __forceinline__ uint32_t ld_acquire(const unsigned int* p) {
    uint32_t v;
    asm volatile("ld.acquire.gpu.global.u32 %0, [%1];" : "=r"(v) : "l"(p) : "memory");
    return v;
}
__device__ __forceinline__ void red_release(unsigned int* p) { asm volatile("red.release.gpu.global.add.u32 [%0], 1;" ::"l"(p) : "memory"); }
__device__ __forceinline__ void wait_count(const unsigned int* p, uint32_t target) {
#pragma unroll 1
    for (uint32_t it = 0; it < SPIN_LIMIT; ++it)
        if ((int)(ld_acquire(p) - target) >= 0) return;
    __trap();
}
__device__ __forceinline__ void wait_count_slow(const unsigned int* p, uint32_t target) {
#pragma unroll 1
    for (uint32_t it = 0; it < SPIN_LIMIT; ++it) {
        if ((int)(ld_acquire(p) - target) >= 0) return;
        __nanosleep(200);
    }
    __trap();
}
__device__ __forceinline__ unsigned long long ld_relaxed1(const void* p) {
    unsigned long long v;
    asm volatile("ld.relaxed.gpu.global.b64 %0, [%1];" : "=l"(v) : "l"(p) : "memory");
    return v;
}
__device__ __forceinline__ ulonglong2 ld_relaxed2(const void* p) {
    ulonglong2 v;
    asm volatile("ld.relaxed.gpu.global.v2.b64 {%0, %1}, [%2];" : "=l"(v.x), "=l"(v.y) : "l"(p) : "memory");
    return v;
}
__device__ __forceinline__ void ld_cell(uint32_t (&v)[4], const void* p, bool on = true) {
    asm volatile("{ .reg .pred p; .reg .b64 l, h; .reg .b128 t; setp.ne.u32 p, %5, 0; mov.b64 l, {%0, %1}; mov.b64 h, {%2, %3}; mov.b128 t, {l, h};\n"
                 "@p ld.relaxed.gpu.global.b128 t, [%4]; mov.b128 {l, h}, t; mov.b64 {%0, %1}, l; mov.b64 {%2, %3}, h; }"
                 : "+r"(v[0]), "+r"(v[1]), "+r"(v[2]), "+r"(v[3]) : "l"(p), "r"((uint32_t)on) : "memory");
}
__device__ __forceinline__ void st_cell(void* p, uint32_t a, uint32_t b, uint32_t c, uint32_t d, bool on) {
    asm volatile("{ .reg .pred p; .reg .b64 l, h; .reg .b128 t; setp.ne.u32 p, %5, 0; mov.b64 l, {%1, %2}; mov.b64 h, {%3, %4}; mov.b128 t, {l, h};\n"
                 "@p st.relaxed.gpu.global.b128 [%0], t; }" ::"l"(p), "r"(a), "r"(b), "r"(c), "r"(d), "r"((uint32_t)on) : "memory");
}

__device__ __forceinline__ uint64_t make_desc(uint32_t addr, uint32_t sbo = 1024) {
    return (uint64_t)((addr & 0x3FFFF) >> 4) | ((uint64_t)1 << 16) | ((uint64_t)(sbo >> 4) << 32) | ((uint64_t)1 << 62);
}
__device__ __forceinline__ void wgmma_fence() { asm volatile("wgmma.fence.sync.aligned;" ::: "memory"); }
__device__ __forceinline__ void wgmma_commit() { asm volatile("wgmma.commit_group.sync.aligned;" ::: "memory"); }
template <int N> __device__ __forceinline__ void wgmma_wait() { asm volatile("wgmma.wait_group.sync.aligned %0;" ::"n"(N) : "memory"); }

#define R8(d, i) "+f"(d[i]), "+f"(d[i + 1]), "+f"(d[i + 2]), "+f"(d[i + 3]), "+f"(d[i + 4]), "+f"(d[i + 5]), "+f"(d[i + 6]), "+f"(d[i + 7])
#define R64(d) R8(d, 0), R8(d, 8), R8(d, 16), R8(d, 24), R8(d, 32), R8(d, 40), R8(d, 48), R8(d, 56)
template <int TA>
__device__ __forceinline__ void wgmma_n128(float (&d)[64], uint64_t da, uint64_t db, int scale_d = 1) {
    asm volatile("{ .reg .pred p; setp.ne.b32 p, %66, 0;\n"
                 "wgmma.mma_async.sync.aligned.m64n128k16.f32.bf16.bf16 "
                 "{%0,%1,%2,%3,%4,%5,%6,%7,%8,%9,%10,%11,%12,%13,%14,%15,%16,%17,%18,%19,%20,%21,%22,%23,%24,%25,%26,%27,%28,%29,%30,%31,"
                 "%32,%33,%34,%35,%36,%37,%38,%39,%40,%41,%42,%43,%44,%45,%46,%47,%48,%49,%50,%51,%52,%53,%54,%55,%56,%57,%58,%59,%60,%61,%62,%63}, "
                 "%64, %65, p, 1, 1, %67, 0; }"
                 : R64(d)
                 : "l"(da), "l"(db), "r"(scale_d), "n"(TA));
}
__device__ __forceinline__ void pin4(float (&d)[4]) { asm volatile("" : "+f"(d[0]), "+f"(d[1]), "+f"(d[2]), "+f"(d[3])::"memory"); }
__device__ __forceinline__ void pin64(float (&d)[64]) { asm volatile("" : R64(d)::"memory"); }

template <int TA, int TB = 0>
__device__ __forceinline__ void wgmma_n8(float (&d)[4], uint64_t da, uint64_t db, int scale_d = 1) {
    asm volatile("{ .reg .pred p; setp.ne.b32 p, %7, 0;\n"
                 "wgmma.mma_async.sync.aligned.m64n8k16.f32.bf16.bf16 {%0,%1,%2,%3}, %4, %5, p, 1, 1, %6, %8; }"
                 : "+f"(d[0]), "+f"(d[1]), "+f"(d[2]), "+f"(d[3])
                 : "l"(da), "l"(db), "n"(TA), "r"(scale_d), "n"(TB));
}

__device__ __forceinline__ float bf_lo(uint32_t u) { return __uint_as_float(u << 16); }
__device__ __forceinline__ float bf_hi(uint32_t u) { return __uint_as_float(u & 0xFFFF0000u); }
__device__ __forceinline__ float rbf(float v) { return __bfloat162float(__float2bfloat16_rn(v)); }
__device__ __forceinline__ uint32_t pack_bf(float lo, float hi) {
    uint32_t r;
    asm("cvt.rn.bf16x2.f32 %0, %1, %2;" : "=r"(r) : "f"(hi), "f"(lo));
    return r;
}
__device__ __forceinline__ uint32_t mul_bf2(uint32_t a, uint32_t b) {
    __nv_bfloat162 r = __hmul2(*reinterpret_cast<__nv_bfloat162*>(&a), *reinterpret_cast<__nv_bfloat162*>(&b));
    return *reinterpret_cast<uint32_t*>(&r);
}
__device__ __forceinline__ uint32_t fma_bf2(uint32_t a, uint32_t b, uint32_t c) {
    uint32_t r;
    asm("fma.rn.bf16x2 %0, %1, %2, %3;" : "=r"(r) : "r"(a), "r"(b), "r"(c));
    return r;
}
__device__ __forceinline__ float2 cmul(float2 a, float2 b) { return make_float2(a.x * b.x - a.y * b.y, a.x * b.y + a.y * b.x); }
__device__ __forceinline__ float2 cfma(float2 a, float2 b, float2 c) {
    return make_float2(fmaf(a.x, b.x, fmaf(-a.y, b.y, c.x)), fmaf(a.x, b.y, fmaf(a.y, b.x, c.y)));
}
__device__ __forceinline__ float sigmoidf_(float v) { return __fdividef(1.0f, 1.0f + expf(-v)); }

__device__ __forceinline__ void bulk_prefetch(const void* src, uint32_t bytes) {
    asm volatile(ONE "cp.async.bulk.prefetch.L2.global [%0], %1; }" ::"l"(src), "r"(bytes) : "memory");
}
__device__ __forceinline__ void bulk_store(void* dst, uint32_t src, uint32_t bytes) {
    asm volatile(ONE "cp.async.bulk.global.shared::cta.bulk_group [%0], [%1], %2; }" ::"l"(dst), "r"(src), "r"(bytes) : "memory");
}
__device__ __forceinline__ uint4 lds128(uint32_t a) {
    uint4 v;
    asm volatile("ld.shared.v4.u32 {%0,%1,%2,%3}, [%4];" : "=r"(v.x), "=r"(v.y), "=r"(v.z), "=r"(v.w) : "r"(a) : "memory");
    return v;
}
__device__ __forceinline__ float4 lds128f(uint32_t a) {
    float4 v;
    asm volatile("ld.shared.v4.f32 {%0,%1,%2,%3}, [%4];" : "=f"(v.x), "=f"(v.y), "=f"(v.z), "=f"(v.w) : "r"(a) : "memory");
    return v;
}
__device__ __forceinline__ void stsm4(uint32_t a, uint32_t x, uint32_t y, uint32_t z, uint32_t w) {
    asm volatile("stmatrix.sync.aligned.m8n8.x4.shared.b16 [%0], {%1,%2,%3,%4};" ::"r"(a), "r"(x), "r"(y), "r"(z), "r"(w) : "memory");
}
__device__ __forceinline__ uint4 ldsm4(uint32_t a) {
    uint4 v;
    asm volatile("ldmatrix.sync.aligned.m8n8.x4.shared.b16 {%0,%1,%2,%3}, [%4];" : "=r"(v.x), "=r"(v.y), "=r"(v.z), "=r"(v.w) : "r"(a) : "memory");
    return v;
}
__device__ __forceinline__ void stg4_unless(float* p, float a, float b, float c, float d, uint32_t skip) {
    asm volatile("{ .reg .pred p; setp.eq.u32 p, %5, 0; @p st.global.v4.f32 [%0], {%1,%2,%3,%4}; }" ::"l"(p), "f"(a), "f"(b), "f"(c), "f"(d), "r"(skip) : "memory");
}
__device__ __forceinline__ void red4(float* p, float a, float b, float c, float d) {
    asm volatile("red.global.add.v4.f32 [%0], {%1,%2,%3,%4};" ::"l"(p), "f"(a), "f"(b), "f"(c), "f"(d) : "memory");
}

#define TT0 3100
#define PER 520
#define PCUT 60
#define PFIN 400
#define PF0 1700
#define PFX_PACE 400
#define PFV 6
#define PFT 0
#define PF1 700
#define T2 400
#define P2 550
#define G0 450
#define R0 2300
#define R_PACE 350
#define W_SHIFT 250
#define PROMO CU_TENSOR_MAP_L2_PROMOTION_L2_256B
#define POLL_S 0
#define ST_TOL 100
#define ST_SHIFT 300
#define CLK_NS 420
#define MARGIN 150
#define BP1 10
#define NDUMP 4
#define HP NDUMP
#define DNL 1
#define AE 6
#define AG0 900
#define AB 16
#define HGE 38
constexpr uint32_t duration(int i) { return PER + (i >= RE0 && i < RE0 + 4 ? 72 : 0) + (i >= GU0 && i < GU0 + 32 ? 36 : 0); }
constexpr uint32_t cmax(uint32_t a, uint32_t b) { return a > b ? a : b; }
constexpr uint32_t issue_time(int i) {
    return i <= NST ? TT0 : i < XE ? issue_time(i - 1) + duration(i - NST) - (i >= XE - 3 && i > GU0 + 36 ? PCUT : 0) : issue_time(XE - 1) + cmax((i - XE + 1) * PFIN, (i - XE) * 512);
}
template <int I> struct Sched { static constexpr uint32_t t = issue_time(I); };
template <int LO, int HI, class F>
__device__ __forceinline__ void for_entries(uint32_t base, F body) {
    constexpr uint32_t per = Sched<LO + 1>::t - Sched<LO>::t;
    static_assert(Sched<HI - 1>::t - Sched<LO>::t == (HI - 1 - LO) * per, "period");
    uint32_t tt = base + Sched<LO>::t;
#pragma unroll 1
    for (int i = LO; i < HI; i++) {
        body(i, tt);
        tt += per;
    }
}

struct Ring { uint32_t prev; int slot; };
struct NoHook { __device__ void operator()() const {} };
template <int TA, int SM, class H = NoHook>
__device__ __forceinline__ void run_entries(Ring& r, int lo, int hi, float (&accA)[64], float (&accB)[64], float (&small)[4],
                                            bool fresh = false, bool sfresh = false, H released = H()) {
    const uint64_t d0 = make_desc(sb);
    const bool leader = (threadIdx.x & 31) == 0;
#pragma unroll 1
    for (int i = lo; i < hi; i++) {
        const uint32_t bar = sb + OFF_FULL + 8 * i;
        const uint64_t da = d0 + (uint64_t)(r.slot * (SLOT >> 4));
        const int n = i - (SM == 1 ? RE0 : GU0);
        const uint64_t dw = d0 + (uint64_t)((OFF_W >> 4) + (SM == 1 ? n * 512 : (n & 7) * 256));
        const uint64_t dt8 = d0 + (uint64_t)((OFF_XS >> 4) + (SM == 1 ? n * 64 : (n >> 1) * 64 + (n & 1) * 4));
        r.slot = r.slot == NST - 1 ? 0 : r.slot + 1;
        mbar_wait(bar);
        KSTAMP(i);
        wgmma_fence();
#pragma unroll
        for (int kk = 0; kk < 4; kk++) {
            wgmma_n128<TA>(accA, da + kk * (TA ? 128 : 2), da + 1024 + kk * 2, kk > 0 || !fresh);
            if (SM == 1) wgmma_n8<0>(small, dw + kk * 2, dt8 + kk * 2, kk > 0 || !sfresh);
            if (SM == 2 && (kk & 1)) wgmma_n8<1>(small, dw + (kk >> 1) * 128, dt8 + (kk >> 1) * 2, kk > 1 || !sfresh);
            wgmma_n128<TA>(accB, da + 512 + kk * (TA ? 128 : 2), da + 1024 + kk * 2, kk > 0 || !fresh);
            if (kk == 1) {
                wgmma_commit();
                wgmma_wait<1>();
                if (leader) mbar_arrive(r.prev);
                released();
            }
        }
        wgmma_commit();
        r.prev = bar + (OFF_EMPTY - OFF_FULL);
        fresh = sfresh = false;
    }
}
template <int HALF, int I>
__device__ __forceinline__ void run_small(float (&acc)[64]) {
    const uint64_t da = make_desc(sb) + (slot_off(I) >> 4);
    KSTAMP(I + HALF * (NENT - FIN));
    wgmma_fence();
#pragma unroll
    for (int kk = 0; kk < 4; kk++) wgmma_n128<1>(acc, da + HALF * 512 + kk * 128, da + 1024 + kk * 2, kk > 0 || !(HALF && I == FIN));
    wgmma_commit();
}
template <int V> struct Int { __host__ __device__ constexpr operator int() const { return V; } };
template <int N, class F> __device__ __forceinline__ void static_for(F f) {
    if constexpr (N > 0) { static_for<N - 1>(f); f(Int<N - 1>()); }
}

__global__ void __launch_bounds__(384, 1)
fused_kernel(const __grid_constant__ Params prm, const __grid_constant__ CUtensorMap mX, const __grid_constant__ CUtensorMap mB, const __grid_constant__ CUtensorMap mCre,
             const __grid_constant__ CUtensorMap mCim, const __grid_constant__ CUtensorMap mWg, const __grid_constant__ CUtensorMap mWu,
             const __grid_constant__ CUtensorMap mWd, const __grid_constant__ CUtensorMap mXr, const __grid_constant__ CUtensorMap mXe) {
    extern __shared__ __align__(1024) uint8_t smem[];
    const uint32_t cstart = clk32();
    const int tid = threadIdx.x, lane = tid & 31;
    uint32_t smid;
    asm volatile("mov.u32 %0, %%smid;" : "=r"(smid));
    {
        const uint32_t b = blockIdx.x & 127, r = tid - PFT, o = (r >> 1) * 2048 + (r & 1) * 128;
#define PFS "@q prefetch.global.L2 [%1]; @p prefetch.global.L2 [%0]; @q prefetch.global.L2 [%2];"
        asm volatile("{ .reg .pred p, q; setp.lt.u32 p, %3, 32; setp.lt.u32 q, %3, 8;\n" PFS " }"
                     ::"l"((const char*)prm.x + (b * 32768 + o)), "l"((const char*)prm.b_re + (b * 8192 + o)), "l"((const char*)prm.b_im + (b * 8192 + o)), "r"(r),
                     "r"(sb + OFF_EPOCH + 12) : "memory");
        gap();
        STAMPIF(tid == PFT, 33);
    }
    const int warp = __shfl_sync(0xffffffffu, tid >> 5, 0);
    int cta;
    asm("{ .reg .pred p; .reg .u32 s, a, b, u, q;\n"
                 "mov.u32 s, %3;\n"
                 "and.b32 a, s, 14; shl.b32 a, a, 2; shr.u32 b, s, 4; add.u32 a, a, b;\n"
                 "sub.u32 u, s, 64; shr.u32 u, u, 1; mul.lo.u32 q, u, 37; shr.u32 q, q, 8; shl.b32 u, u, 3; mad.lo.u32 u, q, -55, u; add.u32 u, u, 12;\n"
                 "setp.lt.u32 p, s, 64; selp.u32 a, a, u, p; and.b32 b, s, 1; mad.lo.u32 a, a, 2, b;\n"
                 "setp.lt.u32 p, s, 124; selp.u32 b, 8, -116, p; add.u32 b, b, s; setp.lt.u32 p, s, 120; selp.u32 a, a, b, p;\n"
                 "setp.ne.u32 p, %2, 0; selp.u32 %0, a, %1, p; }" : "=r"(cta) : "r"(blockIdx.x), "r"(prm.by_smid), "r"(smid));
    const int chunk = (cta >> 5) * 4 + ((cta >> 2) & 3);
    const int dt = ((cta >> 4) & 1) * 4 + (cta & 3);
    asm volatile("{ .reg .pred e, p; elect.sync _|e, 0xffffffff; setp.eq.and.u32 p, %0, 5, e;\n"
                 "@p mbarrier.init.shared::cta.b64 [%1], 1; @p mbarrier.init.shared::cta.b64 [%1 + 8], 1;\n"
                 "fence.mbarrier_init.release.cluster; }" ::"r"(warp), "r"(sb + OFF_FULL) : "memory");
    if (warp == 5 && cta < NCTA) {
        tma5b(sb, &mB, 0, dt * 4, sb + OFF_FULL);
        tma4(sb + 2 * ABYTES, &mX, 0, chunk * 64, sb + OFF_FULL);
        STAMP(31);
        tma5b(sb + SLOT, &mB, 64, dt * 4, sb + OFF_FULL + 8);
        tma4(sb + SLOT + 2 * ABYTES, &mX, 64, chunk * 64, sb + OFF_FULL + 8);
    }
    if (cta >= NCTA) {
        if (smem_u32(smem) != sb) __trap();
        if (tid == 0) wait_count_slow(&prm.s->cnt[0], (atomicAdd(&prm.s->cnt[0], 1u) / NGRID + 1) * NGRID);
        return;
    }
    const bool has_gu = cta >= 16;
    constexpr uint32_t full = sb + OFF_FULL, empty = sb + OFF_EMPTY;
    constexpr uint32_t raw = full + 8 * 32;
    constexpr uint32_t bar_hraw = full + 8 * 97, bar_xs = full + 8 * 98, bar_xb = full + 8 * 100, bar_xa = full + 8 * 101,
        bar_retry = full + 8 * 102, bar_out = full + 8 * 104;
    constexpr uint32_t bar_base = empty - 64, bar_init3 = empty - 56, bar_rdone = empty - 48, bar_order0 = empty - 40, bar_init2 = empty - 32,
        bar_vec = empty - 24, bar_epoch = empty - 16, bar_dummy = empty - 8, bar_xs0 = empty + 8 * 69,
        bar_zero = empty + 8 * 70, bar_xafree = empty + 8 * 71, bar_order2 = empty + 8 * 72, bar_dn = empty + 8 * 73, bar_fp = empty + 8 * 74,
        bar_hs = empty + 8 * 75, bar_accb = empty + 8 * 76, bar_xbfree = empty + 8 * 78, bar_fold = empty + 8 * 79, bar_st = empty + 8 * 80,
        bar_hpub = empty + 8 * 66, bar_order1 = empty + 8 * 67, bar_cand = empty + 8 * 68;

    auto load_hid = [&]() {
        if (lane == 0) mbar_expect_tx(bar_hraw, 2 * 7168);
        bulk_load(sb + OFF_XS, prm.s->hid + (cta >> 4) * 448, 7168, bar_hraw);
        bulk_load(sb + OFF_XS + ABYTES, prm.s->hid + F_ + (cta >> 4) * 448, 7168, bar_hraw);
    };

    if (warp == 5) {
        if (lane < 2) mbar_expect_tx(full + 8 * lane, SLOT);
        __syncwarp();
        named_bar(0, 256);
#pragma unroll 1
        for (int i = 2; i < NST; i++) {
            pace_until(cstart + T2 + i * P2);
            tma5b(sb + i * SLOT, &mB, i * 64, dt * 4, full + 8 * i);
            tma4(sb + i * SLOT + 2 * ABYTES, &mX, i * 64, chunk * 64, full + 8 * i);
            STAMPIF(i == 4, 1);
        }
    } else if (warp == 4) {
        mbar_init_n<12>(bar_init2, 4);
        asm volatile("bar.arrive 0, 256;" ::: "memory");
        mbar_init_n<4>(bar_base, 4);
        mbar_init_n<8>(empty + 64, 4);
        *reinterpret_cast<uint2*>(smem + OFF_KEYS + 16) = make_uint2(0, 0);
        asm volatile("bar.arrive 1, 64;" ::: "memory");
        asm volatile("bar.arrive 5, 96;" ::: "memory");
        asm volatile("bar.arrive 6, 96;" ::: "memory");
        mbar_init_n<32>(full + 256, 3);
        if (lane < 2) mbar_arrive(bar_init2);
    } else if ((warp >> 1) == 3) {
        if (warp == 6) {
            mbar_init_n<8>(full + 16, 1);
            if (lane >= 2 && lane < 10) mbar_expect_tx(full + 8 * lane, lane >= RE0 && lane < RE0 + 4 ? SLOT + ABYTES : SLOT);
            __syncwarp();
            asm volatile("bar.arrive 0, 256;" ::: "memory");
        }
        const char* pf0 = (warp & 1) ? (const char*)((cta & 64) ? prm.b_im : prm.b_re) + (cta & 63) * 16384 : (const char*)prm.x + cta * 32768;
        pace_until(cstart + PF1);
        asm volatile("prefetch.global.L2 [%0];" ::"l"(pf0 + (lane & (30 >> (warp & 1) & 30)) * 1024 + (lane & 1) * 128 + 256));
        const int i0 = warp == 6 ? 10 : 21;
        mbar_init_n<11>(full + 8 * i0, 1);
        if (lane >= i0 && lane < i0 + 11) mbar_expect_tx(full + 8 * lane, lane >= GU0 && has_gu ? SLOT + WBYTES : SLOT);
        mbar_init_n<24>(full + 512 + 192 * (warp & 1), 1);
        named_bar(5, 96);
        if (lane == 0) mbar_arrive(bar_init2);
        STAMP(21);
    }
    __syncwarp();

    if (warp >= 8) {
        asm volatile("setmaxnreg.dec.sync.aligned.u32 72;");
        const uint32_t c0 = cstart;
        uint64_t stream;
        asm volatile("createpolicy.fractional.L2::evict_first.b64 %0, 1.0;" : "=l"(stream));
        const CUtensorMap* mw = (cta & 1) ? &mWu : &mWg;
        const int dc = (cta & 15) * 64, dr = (cta >> 4) * 448;
        auto gutile = [&](int i) {
            const int n = i + 3 - GU0;
            if (has_gu) tma2(sb + OFF_W + (n & 7) * WBYTES, mw, (cta >> 1) * 64 - 512, n * 32, full + 8 * (i + 3), stream);
        };
        if (warp == 8) {
            named_bar(0, 256);
            asm volatile("prefetch.tensormap [%0];" ::"l"(&mXr));
#pragma unroll 1
            for (int u = 0; u < 2; u++) {
                sleep_until(c0 + R0 + u * R_PACE);
                tma3(sb + OFF_W + u * ABYTES, &mXr, u * 256, cta * 16, full + 8 * (RE0 + u));
            }
            uint32_t dst = sb;
            auto gemm1 = [&](int i, uint32_t tt) {
                mbar_wait(empty + 8 * (i - NST));
                LATE(i, tt);
                pace_until(tt);
                tma5b(dst, &mB, (i & 15) * 64, (i >> 4) * 64 + dt * 4, full + 8 * i);
                tma4(dst + 2 * ABYTES, &mX, (i & 15) * 64, chunk * 64, full + 8 * i);
                dst = dst == sb + (NST - 1) * SLOT ? sb : dst + SLOT;
            };
            mbar_wait(bar_init2);
            uint32_t tt = c0 + TT0;
#pragma unroll 1
            for (int i = NST; i < AB; i++) {
                gemm1(i, tt);
                if (i < 7) tma3(sb + OFF_W + (i - 3) * ABYTES, &mXr, (i - 3) * 256, cta * 16, full + 8 * (i + 1));
                tt += (i & ~3) == RE0 + 4 ? PER + 72 : PER;
            }
            mbar_wait(bar_base);
            const uint32_t base = uni(lds32(sb + OFF_EPOCH + 8));
            tt = base + Sched<AB>::t;
#pragma unroll 1
            for (int i = AB; i < 32; i++) {
                gemm1(i, tt);
                tt += i >= GU0 + 4 ? PER + 36 : PER;
            }
            const char* hsrc = reinterpret_cast<const char*>(prm.s->h) + (size_t)chunk * 524288;
            auto gemm2 = [&](int i, uint32_t d, int freed, uint32_t tt) {
                mbar_wait(empty + 8 * freed);
                LATE(i, tt);
                pace_until(tt);
                bulk_load(d, hsrc, 2 * ABYTES, raw + 8 * i);
                tma5(d + 2 * ABYTES, (i & 4) ? &mCim : &mCre, ((i & 3) + ((i >> 1) & 12)) * 64, dt * 8, full + 8 * i);
                hsrc += 2 * ABYTES;
            };
            for_entries<32, GU0 + 29>(base, [&](int i, uint32_t tt) {
                gemm2(i, dst, i - NST, tt);
                gutile(i);
                dst = dst == sb + (NST - 1) * SLOT ? sb : dst + SLOT;
            });
            for_entries<GU0 + 29, GU0 + 37>(base, [&](int i, uint32_t tt) {
                gemm2(i, dst, i - NST, tt);
                const int n = i - GU0 - 29;
                if ((n & 5) == 1) tma5(sb + OFF_W + (n & 2) * (ABYTES / 2), &mXe, dt * 128 + (n & 2) * 32, chunk * 64, bar_xa);
                else if (n < 7) asm volatile(ONE "cp.async.bulk.prefetch.tensor.2d.L2.global [%0, {%1, %2}]; }" ::"l"(&mWd), "r"(dc), "r"(dr + 64 * (n < 4 ? 2 + n / 2 : n)) : "memory");
                dst = dst == sb + (NST - 1) * SLOT ? sb : dst + SLOT;
            });
            static_for<NENT - GU0 - 37>([&](auto u) {
                constexpr int i = GU0 + 37 + u;
                if (i == 60) mbar_wait(bar_out + 56);
                gemm2(i, sb + slot_off(i), i < XE ? i - NST : i == XE ? 71   : i - NST - 1, base + Sched<i>::t);
            });
            STAMP(4);
        } else if (warp == 9) {
#pragma unroll
            for (int u = 0; u < 8; u++) {
                const int row = (u >> 2) * 4 + (lane >> 3);
                asm volatile("cp.async.cg.shared.global [%0], [%1], 16;" ::"r"(sb + OFF_XS + (u & 3) * 1024 + row * 128 + (((lane & 7) ^ row) << 4)),
                             "l"((const char*)(u < 4 ? prm.w_r : prm.gate_w) + (u & 3) * 512 + lane * 16) : "memory");
            }
            uint32_t ticket = 0;
            if (lane == 0) ticket = atomicAdd(&prm.s->cnt[0], 1u);
            named_bar(1, 64);
            if (lane == 0) *reinterpret_cast<volatile uint32_t*>(smem + OFF_EPOCH) = ticket / NGRID;
            __syncwarp();
            if (lane < 4) mbar_arrive(bar_epoch);
            asm volatile("cp.async.wait_all;" ::: "memory");
            asm volatile("fence.proxy.async.shared::cta;" ::: "memory");
            __syncwarp();
            if (lane < 4) mbar_arrive(bar_vec);
            STAMP(18);
#pragma unroll 1
            for (int i = 4; i < 22; i++) mbar_init_n<4>(empty + 32 * i, 4, i >= 6 && i < 13);
            if (lane < 2) mbar_arrive(bar_init3);
            STAMP(19);
            mbar_wait(bar_cand);
            {
                const uint32_t* list = reinterpret_cast<const uint32_t*>(smem + OFF_LIST);
                const int n = (int)lds32(sb + OFF_KEYS + 16);
#pragma unroll 1
                for (int i0 = 0; i0 < n; i0 += 32) {
                    const uint32_t k = list[i0 + lane];
                    int rank = 0;
#pragma unroll 2
                    for (int o = 0; o < n; o += 4) {
                        const uint4 l4 = *reinterpret_cast<const uint4*>(list + o);
                        rank += (l4.x > k) + (l4.y > k) + (l4.z > k) + (l4.w > k);
                    }
                    if (rank < 8) reinterpret_cast<uint32_t*>(smem + OFF_SEL)[rank] = k;
                }
                __syncwarp();
                STAMP(6);
                const uint32_t key = lds32(sb + OFF_SEL + 4 * (lane & 7)), tok = ~key & 2047u, tag = lds32(sb + OFF_EPOCH) + 1;
                const uint32_t ta = __shfl_sync(0xffffffffu, tok, lane >> 3), tb = __shfl_sync(0xffffffffu, tok, 4 + (lane >> 3));
                const uint32_t da = sb + OFF_XS + (lane >> 3) * 128 + (((lane & 7) ^ (lane >> 3)) << 4), db = (da ^ 64) + 512;
                const char *sa = (const char*)prm.x + ta * 2048 + (lane & 7) * 16, *sc = (const char*)prm.x + tb * 2048 + (lane & 7) * 16;
#pragma unroll
                for (int u = 0; u < 16; u++) {
                    asm volatile("cp.async.cg.shared.global [%0], [%1], 16;" ::"r"(da + u * 1024), "l"(sa + u * 128) : "memory");
                    asm volatile("cp.async.cg.shared.global [%0], [%1], 16;" ::"r"(db + u * 1024), "l"(sc + u * 128) : "memory");
                    if (u == 3) {
                        asm volatile("cp.async.wait_all;" ::: "memory");
                        asm volatile("fence.proxy.async.shared::cta;" ::: "memory");
                        __syncwarp();
                        if (lane < 4) mbar_arrive(bar_xs0);
                        STAMP(17);
                    }
                }
                if ((tok >> 7) == (uint32_t)chunk) {
                    float4* zp = reinterpret_cast<float4*>(prm.out + tok * D_ + dt * 128) + (lane >> 3) * 2;
#pragma unroll
                    for (int u = 0; u < 8; u++) zp[(u >> 1) * 8 + (u & 1)] = make_float4(0.f, 0.f, 0.f, 0.f);
                }
                uint32_t it = 0;
                unsigned long long u;
                do {
                    u = ld_relaxed1(&prm.s->gpack[tok >> 1]);
                    if (++it > SPIN_LIMIT) __trap();
                } while (!__all_sync(0xffffffffu, (uint32_t)(u >> 32) == tag));
                const uint32_t kb = key >> 16;
                const float r = bf_lo((kb & 0x8000u) ? (kb & 0x7FFFu) : (~kb & 0xFFFFu)), gv = (tok & 1) ? bf_hi((uint32_t)u) : bf_lo((uint32_t)u);
                reinterpret_cast<float*>(smem + OFF_FAC)[lane & 7] = rbf(1.0f - gv) * rbf(sigmoidf_(r));
                asm volatile("cp.async.wait_all;" ::: "memory");
                asm volatile("fence.proxy.async.shared::cta;" ::: "memory");
                __syncwarp();
                if (lane == 0) mbar_arrive(bar_xs);
                STAMP(7);
            }
            char* hd = reinterpret_cast<char*>(prm.s->h) + (size_t)chunk * 524288 + (dt >> 1) * 16384 + (dt & 1) * 4096;
            mbar_wait(bar_base);
            const uint32_t cb = uni(lds32(sb + OFF_EPOCH + 8)) + ST_SHIFT;
            uint32_t tt = cb + Sched<GU0 + 4>::t;
#pragma unroll 1
            for (int np = 0; np < 16; np++) {
                if (!(np & (np & 4 ? 1 : 2))) mbar_wait(bar_st + 4 * (np & 12) + ((np & 3) ? 8 : 0));
                const uint32_t now = clk32() - ST_TOL;
#pragma unroll 1
                while ((int)(tt - now) < 0) tt += PER + 36;
                const uint32_t src = sb + OFF_STG + (np & 3) * 4096;
                pace_until(tt);
                bulk_store(hd, src, 4096);
                asm volatile("cp.async.bulk.commit_group;" ::: "memory");
                if (np & 2) {
                    if (np & 1) asm volatile("cp.async.bulk.wait_group.read 0;" ::: "memory");
                    else asm volatile("cp.async.bulk.wait_group.read 1;" ::: "memory");
                    __syncwarp();
                    const uint32_t u8 = 4 * (np & 12) + 8 * (np & 1);
                    if (lane < 2) mbar_arrive(lane ? (np < 15 ? empty + 8 * 27 + 4 * u8 : bar_dummy) : bar_out + u8);
                }
                STAMPIF(np & 2, 8 + ((np >> 1) & 6) + (np & 1));
                hd += (np & 1) ? 65536 - 8192 : 8192;
                tt += PER + 36;
            }
#pragma unroll 1
            for (int u = 0; u < 2; u++) {
                pace_until(tt);
                tma5(sb + OFF_STG + u * ABYTES, &mXe, dt * 128 + u * 64, chunk * 64 + 8, bar_xb);
                tt += PER + 36;
            }
            wait_count(&prm.s->cnt[32], (lds32(sb + OFF_EPOCH) + 1) * NCTA);
            if (lane < 4) mbar_arrive(bar_zero);
            mbar_wait(bar_hpub);
            sleep_until(cb + Sched<GU0 + HGE>::t);
            load_hid();
            static_for<7>([&](auto u) {
                if (u != 1) mbar_wait(u == 0 ? bar_xbfree : u == 2 ? bar_hs : empty + 8 * (u == 3 ? FIN + DNL : FIN - 2 + u));
                if (u < 3) sleep_until(cb + Sched<(u < 2 ? GU0 + HGE + u : NENT - 1)>::t);
                tma2(sb + dn_off(u), &mWd, dc, dr + u * 64, bar_dn, stream);
            });
            STAMP(27);
        } else {
            named_bar(6, 96);
            if (warp == 10) {
                const char* pb = (const char*)((cta & 64) ? prm.b_im : prm.b_re) + (cta & 63) * 16384;
                const char* pf = (lane < 16 ? (const char*)prm.x + cta * 32768 : pb) + (lane & 15) * 2048 + 512;
#pragma unroll 1
                for (int k = 0; k < 11; k++) {
                    sleep_until(c0 + PF0 + k * PFX_PACE);
                    if (lane < 16 ? k < 6 : lane < 24 && !(k & 1)) prefetch_l2(pf + k * (lane < 16 ? 256 : 128));
                }
                static_for<12>([&](auto k) {
                    sleep_until(c0 + Sched<BP1 + k>::t + ST_SHIFT);
                    bulk_prefetch((k < 4 ? pb + 1048576 : (const char*)(k < 8 ? prm.c_re : prm.c_im) + cta * 16384) + (k & 3) * 4096, 4096);
                    if (k == 4) { mbar_wait(bar_init2); mbar_wait(bar_init3); }
                    if (k >= 4 && lane < 8) mbar_expect_tx(full + 8 * (8 * k + lane), 8 * k + lane < GU0 + 32 && has_gu ? 2 * ABYTES + WBYTES : 2 * ABYTES);
                });
                asm volatile("prefetch.tensormap [%0];" ::"l"(&mCre));
                asm volatile("prefetch.tensormap [%0];" ::"l"(&mCim));
                asm volatile("prefetch.tensormap [%0];" ::"l"(&mWd));
                asm volatile("prefetch.tensormap [%0];" ::"l"(&mXe));
                if (lane < 2) mbar_expect_tx(bar_xb + 8 * lane, 2 * ABYTES);
                mbar_wait(bar_xs);
                mbar_wait(bar_st);
                if (lane == 0) red_release(&prm.s->cnt[32]);
                __syncwarp();
                STAMP(22);
            } else {
                asm volatile("prefetch.tensormap [%0];" ::"l"(mw));
                mbar_wait(bar_epoch);
                const uint32_t tag = lds32(sb + OFF_EPOCH) + 1;
                st_cell(prm.s->time + cta, 0, 0, 0, 0, lane == 0);
                mbar_wait(empty + 8 * AE);
                uint32_t gown, tm[4][4] = {}, it = 0;
                asm volatile("mov.u32 %0, %%globaltimer_lo;" : "=r"(gown));
                const uint32_t town = clk32();
                st_cell(prm.s->time + cta, tag, town, gown, 0, lane == 0);
                sleep_until(town + AG0);
                do {
#pragma unroll
                    for (int m = 0; m < 4; m++) ld_cell(tm[m], prm.s->time + ((cta & 96) ^ (32 * m)) + lane);
                    if (++it > SPIN_LIMIT) __trap();
                } while (!__all_sync(0xffffffffu, tm[0][0] == tag && tm[1][0] == tag && tm[2][0] == tag && tm[3][0] == tag));
                const int last = __reduce_max_sync(0xffffffffu, max(max((int)(tm[0][2] - gown), (int)(tm[1][2] - gown)), max((int)(tm[2][2] - gown), (int)(tm[3][2] - gown))));
                const uint32_t cand = tm[0][1] + ((min((int)(gown + last - tm[0][2]), 4000) * CLK_NS) >> 8);
                const uint32_t b0 = __shfl_sync(0xffffffffu, cand, cta & 16), b1 = __shfl_sync(0xffffffffu, cand, cta & 30);
                const uint32_t base = (b0 - b1 + 400u < 800u ? b0 : b1) + MARGIN - Sched<AE + NST>::t;
                *reinterpret_cast<volatile uint32_t*>(smem + OFF_EPOCH + 8) = base;
                mbar_wait(bar_init3);
                if (lane < 4) mbar_arrive(bar_base);
                STAMP(23);
                const uint32_t cb = base + W_SHIFT;
                auto early = [&](int i, uint32_t tt) {
                    mbar_wait(empty + 8 * (i - NST));
                    pace_until(tt);
                    gutile(i);
                };
                for_entries<GU0 - 3, GU0 + 4>(cb, early);
                for_entries<GU0 + 4, 32>(cb, early);
            }
            mbar_wait(bar_epoch);
            const uint32_t t2 = lds32(sb + OFF_EPOCH) + 1, tagw = (t2 & 1) | ((t2 & 2) << 15), half = (warp & 1) * ABYTES;
            const uint32_t lo = half + lane * 32 + (lane & 4) * 4 + (lane >> 3) * 4, retry = bar_retry + (warp & 1) * 8;
            const bool leader = lane == 0;
            uint32_t slot = sb + (32 % NST) * SLOT, rpar = 0;
#pragma unroll 1
            for (int i = 32; i < NENT; i++) {
                const uint32_t src = i == XE ? sb + OFF_W : slot;
                if (i != XE) slot = slot == sb + (NST - 1) * SLOT ? sb : slot + SLOT;
                auto current = [&]() {
                    uint32_t v[8];
#pragma unroll
                    for (int u = 0; u < 8; u++) v[u] = lds32(src + lo + u * 1024);
#pragma unroll
                    for (int u = 0; u < 8; u += 2) asm("lop3.b32 %0, %0, %1, %2, 0x7e;" : "+r"(v[u]) : "r"(v[u + 1]), "r"(tagw));
                    return __all_sync(0xffffffffu, ((v[0] | v[2] | v[4] | v[6]) & 0x00010001u) == 0);
                };
                mbar_wait(raw + 8 * i);
                if (!current()) {
#pragma unroll 1
                    for (uint32_t it = 0;; it++) {
                        if (it > SPIN_LIMIT) __trap();
                        STAMP(16);
                        if (leader) mbar_expect_tx(retry, ABYTES);
                        bulk_load(src + half, reinterpret_cast<const char*>(prm.s->h) + (size_t)chunk * 524288 + (i - 32) * 16384 + half, ABYTES, retry);
                        mbar_wait(retry, rpar);
                        rpar ^= 1;
                        if (current()) break;
                    }
                }
                if (leader) mbar_arrive(full + 8 * i);
            }
        }
    } else {
        asm volatile("setmaxnreg.inc.sync.aligned.u32 216;");
        const int wg = warp >> 2, w = warp & 3, g = lane >> 2, c = lane & 3, at = tid & 127;
        float facc[4];
        float2 a[2], m0[2], a32[2], a128[2];
        auto load_const = [&]() {
            const float2* cp = reinterpret_cast<const float2*>(smem + OFF_CONST) + wg * 64 + w * 8 + g;
#pragma unroll
            for (int h = 0; h < 2; h++) { a[h] = cp[32 * h]; m0[h] = cp[128 + 32 * h]; a32[h] = cp[256 + 32 * h]; a128[h] = cp[384 + 32 * h]; }
        };
        if (wg == 0) {
            named_bar(0, 256);
            STAMPIF(tid == 0, 20);
        } else {
            const int pc = (at >> 5) * 256 + dt * 32 + (at & 31);
            const float lr = __bfloat162float(prm.lam_re[pc]), li = __bfloat162float(prm.lam_im[pc]), ld = __bfloat162float(prm.log_dt[pc]);
            const uint32_t dk = __ldg(reinterpret_cast<const uint32_t*>(prm.dskip + dt * 128) + (at & 63));
#pragma unroll
            for (int i = 0; i < 4; i++) sts128(sb + OFF_LIST + i * 2048 + at * 16, 0u, 0u, 0u, 0u);

            {
                reinterpret_cast<uint32_t*>(smem + OFF_DK)[at & 63] = dk;
                const float dtv = rbf(expf(ld));
                const float er = expf(dtv * lr);
                float sn, cs;
                sincospif(dtv * li * 0.318309886183790672f, &sn, &cs);
                const float ar = er * cs, ai = er * sn;
                const float nr = ar - 1.0f, ni = ai;
                const bool big = fabsf(lr) >= fabsf(li);
                const float t = (big ? li : lr) / (big ? lr : li), dn = big ? lr + li * t : lr * t + li;
                const float cr = (big ? nr + ni * t : nr * t + ni) / dn, ci = (big ? ni - nr * t : ni * t - nr) / dn;
                float2* cp = reinterpret_cast<float2*>(smem + OFF_CONST) + at;
                float2 pw = make_float2(ar, prm.swapped ? ai : -ai);
                cp[0] = pw;
                cp[128] = make_float2(prm.swapped ? -2.f * cr : 2.f * cr, -2.f * ci);
#pragma unroll
                for (int i = 1; i <= 7; i++) {
                    pw = cmul(pw, pw);
                    if (i == 5) cp[256] = pw;
                    if (i == 7) cp[384] = pw;
                }
                __syncwarp();
            }
            named_bar(2, 128);
            load_const();
            mbar_wait(bar_epoch);
            const uint32_t tag = *reinterpret_cast<volatile uint32_t*>(smem + OFF_EPOCH) + 1;
            asm volatile("st.relaxed.gpu.global.b64 [%0], %1;" ::"l"(&prm.s->carry[(chunk >> 2) * 4096 + pc * 4 + (chunk & 3)]), "l"((unsigned long long)(tag + 2)) : "memory");
            if (w == 2) st_cell(lane < 4 ? (uint4*)prm.s->rpack + cta * 4 + lane : (uint4*)prm.s->gpack + cta * 4 + (lane & 3), 0, 0, 0, 0, lane < 8);
            {
                const uint32_t nt = ((tag & 1) | ((tag & 2) << 15)) ^ 0x00010001u;
                st_cell(prm.s->hid + (cta & 1) * F_ + (cta >> 1) * 64 - 512 + (at & 63), nt, nt, nt, nt, has_gu && w >= 2);
            }
            named_bar(2, 128);
            if (at < 2) mbar_arrive(bar_init3);
            unsigned long long* pub = (w ? prm.s->gpack : prm.s->rpack) + cta * 8 + lane;
            asm volatile("" : "+l"(pub));
            STAMPIF(lane == 0, 52);
            mbar_wait(bar_rdone);

            if (w < 2) {
                const float2* red = reinterpret_cast<const float2*>(smem + OFF_RED) + w * 8 + (lane & 7);
                const float2 r0 = red[0], r1 = red[16], r2 = red[32], r3 = red[48];
                const float v0 = (r0.x + r1.x) + (r2.x + r3.x), v1 = (r0.y + r1.y) + (r2.y + r3.y);
                uint32_t pk2;
                if (w == 0) {
                    pk2 = pack_bf(v0, v1);
                    pk2 ^= (((pk2 >> 15) & 0x00010001u) * 0x7FFFu) ^ 0x80008000u;
                } else pk2 = pack_bf(sigmoidf_(rbf(v0)), sigmoidf_(rbf(v1)));
                if (lane < 8) asm volatile("st.relaxed.gpu.global.b64 [%0], %1;" ::"l"(pub), "l"(((unsigned long long)tag << 32) | pk2) : "memory");
                __syncwarp();
            }
            STAMPIF(at == 0, 24);
            uint32_t it = 0, pr[8], g1;
            mbar_wait(bar_init3);
            sleep_until(clk32() + (w < 2 ? G0 : G0 + 250));
            while (true) {
                bool ok = true;
#pragma unroll
                for (int k = 0; k < 4; k++) {
                    const ulonglong2 u = ld_relaxed2(&prm.s->rpack[k * 256 + 2 * at]);
                    ok = ok && (uint32_t)(u.x >> 32) == tag && (uint32_t)(u.y >> 32) == tag;
                    pr[2 * k] = (uint32_t)u.x; pr[2 * k + 1] = (uint32_t)u.y;
                }
                const unsigned long long u1 = ld_relaxed1(&prm.s->gpack[chunk * 64 + (at & 63)]);
                ok = ok && (uint32_t)(u1 >> 32) == tag;
                g1 = (uint32_t)u1;
                if (__all_sync(0xffffffffu, ok)) break;
                if (++it > SPIN_LIMIT) __trap();
            }
            STAMPIF(lane == 0, 25);
            uint32_t m = __vmaxu2(__vimax3_u16x2(__vimax3_u16x2(pr[0], pr[1], pr[2]), pr[3], pr[4]), __vimax3_u16x2(pr[5], pr[6], pr[7]));
            m = (max(m, m << 16) & 0xFFFF0000u) | (uint32_t)lane;
            const uint32_t m1 = __reduce_max_sync(0xffffffffu, m), m2 = __reduce_max_sync(0xffffffffu, m == m1 ? 0u : m);
            uint32_t* keys = reinterpret_cast<uint32_t*>(smem + OFF_KEYS);
            if (lane == 0) keys[w] = m2;
            sts128(sb + OFF_XS + 4096 + at * 16, pr[0], pr[1], pr[2], pr[3]);
            sts128(sb + OFF_XS + 6144 + at * 16, pr[4], pr[5], pr[6], pr[7]);
            *reinterpret_cast<uint32_t*>(smem + OFF_G + 4 * (at & 63)) = g1;
            named_bar(2, 128);
            const uint4 th4 = *reinterpret_cast<const uint4*>(keys);
            const uint32_t th = (max(min(min(th4.x, th4.y), min(th4.z, th4.w)) >> 16, 1u) - 1u) * 0x00010001u;
            uint32_t mask = 0;
#pragma unroll
            for (int k = 7; k >= 0; k--) mask = mask * 2 + __vminu2(__vmaxu2(pr[k], th) ^ th, 0x00010001u);
            uint32_t pos = 0;
            asm volatile("{ .reg .pred p; setp.ne.u32 p, %2, 0; @p atom.shared.add.u32 %0, [%1], %2; }" : "+r"(pos) : "r"(sb + OFF_KEYS + 16), "r"(__popc(mask)) : "memory");
            while (mask) {
                const int bit = __ffs(mask) - 1, k = bit & 7, hi = bit >> 4;
                mask &= mask - 1;
                const uint32_t sc = *reinterpret_cast<const uint16_t*>(smem + OFF_XS + 4096 + (k >> 2) * 2048 + at * 16 + (k & 3) * 4 + hi * 2);
                *reinterpret_cast<uint32_t*>(smem + OFF_LIST + 4 * pos++) = (sc << 16) | (0x8000u + 2047u - (uint32_t)((k >> 1) * 512 + 4 * at + 2 * (k & 1) + hi));
            }
            __syncwarp();
            if (lane == 0) mbar_arrive(bar_cand);
            STAMPIF(lane == 0, 26);
            mbar_wait(bar_order0);
        }

        float accA[64], accB[64];
        Ring ring = {bar_dummy, wg};
        {
            run_entries<0, 0>(ring, wg * 16, wg ? GU0 : RE0, accA, accB, facc, true);
            if (wg == 0) {
                float racc[4];
                mbar_wait(bar_vec);
                run_entries<0, 1>(ring, RE0, RE0 + 4, accA, accB, racc, false, true);
                mbar_wait(bar_init2);
                const uint32_t red = sb + OFF_RED + 4 * (w * 32 + (c >> 1) * 16 + g);
                run_entries<0, 0>(ring, RE0 + 4, RE0 + 5, accA, accB, facc, false, false, [&]() {
                    pin4(racc);
                    asm volatile("{ .reg .pred p; setp.ne.u32 p, %3, 0; @p st.shared.f32 [%0], %1; @p st.shared.f32 [%0 + 32], %2; }" ::"r"(red),
                                 "f"((w & 1) ? racc[1] : racc[0]), "f"((w & 1) ? racc[3] : racc[2]), "r"((uint32_t)((c & 1) == (w >> 1))) : "memory");
                    __syncwarp();
                    if (lane == 0) mbar_arrive(bar_rdone);
                    STAMPIF(lane == 0, 5);
                });
                run_entries<0, 0>(ring, RE0 + 5, 16, accA, accB, facc);
                if (lane == 0) mbar_arrive(bar_order0);
                mbar_wait(bar_init3);
                load_const();
                named_bar(3, 128);
            } else {
#pragma unroll
                for (int u = 0; u < 2; u++) {
                    mbar_wait(u ? bar_xs : bar_xs0);
                    run_entries<0, 2>(ring, GU0 + 8 * u, u ? 32 : GU0 + 8, accA, accB, facc, false, u == 0);
                }
                if (lane == 0) mbar_arrive(bar_order1);
            }
        }
        const uint32_t tag = *reinterpret_cast<volatile uint32_t*>(smem + OFF_EPOCH) + 1;
        const float2 a64[2] = {cmul(a32[0], a32[0]), cmul(a32[1], a32[1])};
        wgmma_wait<0>();
        pin64(accA); pin64(accB); pin4(facc);
        if (lane == 0) mbar_arrive(ring.prev);
        STAMPIF(at == 0, 28 + wg);
        GSTAMP(tid == 0, 1);

        const int tl = 32 * (g >> 1) + (g & 1) + 4 * w + 16 * wg, t0 = chunk * 128 + tl;
        float* op = prm.out + (size_t)t0 * D_ + dt * 128 + 4 * c;
        uint2 xv[8][2], dk[8];
        uint32_t gp[2], om[2], routed[2];
        auto row_setup = [&]() {
            const uint4 sa = *reinterpret_cast<const uint4*>(smem + OFF_SEL), sc = *reinterpret_cast<const uint4*>(smem + OFF_SEL + 16);
#pragma unroll
            for (int r = 0; r < 2; r++) {
                const uint32_t id = 0x8000u + 2047u - (uint32_t)(t0 + 2 * r);
                routed[r] = (uint16_t)sa.x == id || (uint16_t)sa.y == id || (uint16_t)sa.z == id || (uint16_t)sa.w == id ||
                            (uint16_t)sc.x == id || (uint16_t)sc.y == id || (uint16_t)sc.z == id || (uint16_t)sc.w == id;
                gp[r] = reinterpret_cast<const uint16_t*>(smem + OFF_G)[tl + 2 * r] * 0x00010001u;
                om[r] = pack_bf(1.0f - bf_hi(gp[r]), 1.0f - bf_hi(gp[r]));
            }
#pragma unroll
            for (int j = 0; j < 8; j++) dk[j] = lds64(sb + OFF_DK + 32 * j + 8 * c);
        };
        auto release = [&](uint32_t bar) {
            asm volatile("fence.proxy.async.shared::cta;" ::: "memory");
            __syncwarp();
            if (lane == 0) mbar_arrive(bar);
        };

        {
            const uint32_t t2 = tag & 3u;
            float2* cslot = &prm.s->carry[(wg * 512 + dt * 32 + w * 8 + g) * 4];
            const int j1 = chunk - 1 - c;
            unsigned long long v[2][4] = {{t2, t2, t2, t2}, {t2, t2, t2, t2}};
            auto poll = [&](int h) {
#pragma unroll
                for (int m = 0; m < 4; m++)
                    asm volatile("{ .reg .pred p; setp.ge.s32 p, %2, %3; @p ld.relaxed.gpu.global.b64 %0, [%1]; }"
                                 : "+l"(v[h][m]) : "l"(cslot + (j1 >> 2) * 4096 + c - m * 4096 + h * 1024), "r"(j1), "r"(4 * m) : "memory");
            };
            float2 e[2], w0[2];
            auto chain = [&](int h, int s0, int s1) {
                float (&acc)[64] = h ? accB : accA;
                if (s0 == 1) e[h] = make_float2(acc[0], acc[2]);
#pragma unroll
                for (int s = s0; s < s1; s++) {
                    const int i0 = 4 * (s >> 1) + (s & 1);
                    e[h] = cfma(make_float2(a[h].x, -a[h].y), e[h], make_float2(acc[i0], acc[i0 + 2]));
                }
                asm volatile("" : "+f"(e[h].x), "+f"(e[h].y), "+f"(accB[0]), "+f"(accB[2]));
                gap();
            };
            auto publish = [&](int h) {
                float2 f = make_float2(fmaf(m0[h].x, e[h].x, m0[h].y * e[h].y), fmaf(-m0[h].x, e[h].y, m0[h].y * e[h].x));
                float2 y = make_float2(__shfl_up_sync(0xffffffffu, f.x, 1, 4), __shfl_up_sync(0xffffffffu, f.y, 1, 4));
                if (c >= 1) f = cfma(a32[h], y, f);
                y = make_float2(__shfl_up_sync(0xffffffffu, f.x, 2, 4), __shfl_up_sync(0xffffffffu, f.y, 2, 4));
                if (c >= 2) f = cfma(a64[h], y, f);
                asm volatile("{ .reg .pred p; .reg .b64 t; setp.eq.u32 p, %3, 3; mov.b64 t, {%1, %2}; @p st.relaxed.gpu.global.b64 [%0], t; }"
                             ::"l"(cslot + (chunk >> 2) * 4096 + (chunk & 3) + h * 1024), "r"((__float_as_uint(f.x) & ~3u) | t2), "r"(__float_as_uint(f.y)), "r"(c) : "memory");
                w0[h] = make_float2(__shfl_up_sync(0xffffffffu, f.x, 1, 4), __shfl_up_sync(0xffffffffu, f.y, 1, 4));
                if (c == 0) w0[h] = make_float2(0.f, 0.f);
            };
            auto scale = [&](int h, int n0, int n1) {
                float (&acc)[64] = h ? accB : accA;
#pragma unroll
                for (int n = n0; n < n1; n++) {
                    asm volatile("{ .reg .f32 a, b, c, d, n; neg.f32 n, %4; mul.f32 a, %1, %5; mul.f32 b, %0, %5; mul.f32 c, %3, %5; mul.f32 d, %2, %5;\n"
                                 "fma.rn.f32 %0, %0, %4, a; fma.rn.f32 %1, %1, n, b; fma.rn.f32 %2, %2, %4, c; fma.rn.f32 %3, %3, n, d; }"
                                 : "+f"(acc[4 * n]), "+f"(acc[4 * n + 2]), "+f"(acc[4 * n + 1]), "+f"(acc[4 * n + 3]) : "f"(m0[h].x), "f"(m0[h].y));
                    gap();
                }
            };
            auto carry = [&](int h) {
                const float2 one = make_float2(1.f, 0.f), a256 = cmul(a128[h], a128[h]);
                float2 a512 = cmul(a256, a256), pw128 = cmul((j1 & 1) ? a128[h] : one, (j1 & 2) ? a256 : one);
                float2 pw32 = cmul((c & 1) ? a32[h] : one, (c & 2) ? a64[h] : one);
                asm volatile("" : "+f"(a512.x), "+f"(a512.y), "+f"(pw128.x), "+f"(pw128.y), "+f"(pw32.x), "+f"(pw32.y));
                STAMPIF(lane == 0 && !h, 34 + 2 * wg);
                uint32_t it = 0;
                while (!__all_sync(0xffffffffu, ((((uint32_t)v[h][0] ^ t2) | ((uint32_t)v[h][1] ^ t2) | ((uint32_t)v[h][2] ^ t2) | ((uint32_t)v[h][3] ^ t2)) & 3u) == 0)) {
                    poll(h);
                    if (++it > SPIN_LIMIT) __trap();
                }
                STAMPIF(lane == 0 && !h, 35 + 2 * wg);
                if (!h) poll(1);
                float2 hin = make_float2(__uint_as_float((uint32_t)v[h][3]), __uint_as_float((uint32_t)(v[h][3] >> 32)));
#pragma unroll
                for (int m = 2; m >= 0; m--) hin = cfma(a512, hin, make_float2(__uint_as_float((uint32_t)v[h][m]), __uint_as_float((uint32_t)(v[h][m] >> 32))));
                hin = cmul(pw128, hin);
                hin.x += __shfl_xor_sync(0xffffffffu, hin.x, 1); hin.y += __shfl_xor_sync(0xffffffffu, hin.y, 1);
                hin.x += __shfl_xor_sync(0xffffffffu, hin.x, 2); hin.y += __shfl_xor_sync(0xffffffffu, hin.y, 2);
                w0[h] = cfma(pw32, hin, w0[h]);
            };
            chain(0, 1, 32);
            publish(0);
            chain(1, 1, 8);
            STAMPIF(lane == 0, 30 + 2 * wg);
            chain(1, 8, 32);
            publish(1);
            gap();
            scale(0, 0, POLL_S);
            poll(0);
            scale(0, POLL_S, 16);
            carry(0);
            if (wg) mbar_wait(bar_out + 24);
            STAMPIF(lane == 0, 38 + 2 * wg);
            const uint32_t stg = sb + OFF_STG + prm.swapped * 8192 + w * 1024 + (lane & 7) * 128 + (((lane >> 3) ^ (lane & 7)) << 4);
            const uint32_t second = prm.swapped ? -8192 : 8192;
            const uint32_t keep = c == (g >> 1) ? 0xFFFEFFFEu : 0xFFFFFFFFu, tagw = ((t2 & 1) | ((t2 & 2) << 15)) & ~keep;
#pragma unroll
            for (int h = 0; h < 2; h++) {
                float (&acc)[64] = h ? accB : accA;
                uint32_t ra[16], ia[16];
                if (h) {
                    scale(1, 0, 5);
                    release(bar_st + 32 * wg + 8);
                    scale(1, 5, 16);
                    carry(1);
                }
                auto stage = [&](uint32_t (&r)[16], uint32_t base, int j) {
                    stsm4((base ^ ((j & 1) * 64)) + (j >> 1) * 4096, r[4 * j], r[4 * j + 1], r[4 * j + 2], r[4 * j + 3]);
                };
#pragma unroll
                for (int n = 0; n < 16; n++) {
                    const float2 y = cfma(a[h], w0[h], make_float2(acc[4 * n], acc[4 * n + 2]));
                    w0[h] = cfma(a[h], y, make_float2(acc[4 * n + 1], acc[4 * n + 3]));
                    ra[n] = pack_bf(y.x, w0[h].x);
                    ia[n] = pack_bf(y.y, w0[h].y);
                    if (!(n & 1)) { ra[n] = (ra[n] & keep) | tagw; ia[n] = (ia[n] & keep) | tagw; }
                    if (!h && (n & 3) == 3) {
                        if (n == 11) { asm volatile("" : "+r"(ra[n]), "+r"(ia[n])); gap(); release(bar_st + 32 * wg); }
                        stage(ra, stg, n >> 2); stage(ia, stg + second, n >> 2);
                        gap();
                    }
                }
                if (h) {
                    STAMPIF(lane == 0, 39 + 2 * wg);
                    mbar_wait(bar_out + 32 * wg);
                    if (prm.swapped) {
#pragma unroll
                        for (int n = 0; n < 16; n++) { const uint32_t t = ra[n]; ra[n] = ia[n]; ia[n] = t; }
                    }
                    const uint32_t st0 = stg - prm.swapped * 8192;
#pragma unroll
                    for (int j = 0; j < 4; j++) stage(ra, st0, j);
                    mbar_wait(bar_xs);
                    row_setup();
                    release(bar_st + 32 * wg + 16);
                    mbar_wait(bar_out + 32 * wg + 8);
#pragma unroll
                    for (int j = 0; j < 4; j++) stage(ia, st0 + 8192, j);
                    release(bar_st + 32 * wg + 24);
                }
                STAMPIF(lane == 0, 42 + 2 * wg + h);
            }
        }

        const uint32_t xr = 2 * (g & 3) + (g >> 2), xa = sb + (wg ? OFF_STG : OFF_W) + (16 * w + xr) * 128 + (((c >> 1) ^ xr) << 4) + (c & 1) * 8;
        auto handover = [&](uint32_t bar) {
            const uint4 z = ldsm4(sb + OFF_KEYS + 16);
            if (lane == 1) mbar_arrive(bar + z.x);
        };
        auto load_x = [&](int j0, int j1) {
#pragma unroll
            for (int j = j0; j < j1; j++)
#pragma unroll
                for (int r = 0; r < 2; r++) xv[j][r] = lds64((xa ^ (32 * (j & 3))) + (j >> 2) * ABYTES + r * 1024);
        };
        auto skip_term = [&](int j0, int j1) {
#pragma unroll
            for (int j = j0; j < j1; j++)
#pragma unroll
                for (int r = 0; r < 2; r++) {
                    xv[j][r].x = mul_bf2(xv[j][r].x, fma_bf2(gp[r], dk[j].x, om[r]));
                    xv[j][r].y = mul_bf2(xv[j][r].y, fma_bf2(gp[r], dk[j].y, om[r]));
                    asm volatile("" : "+r"(xv[j][r].x), "+r"(xv[j][r].y));
                }
        };
        auto finish = [&](float (&acc)[64], int j, bool gaps) {
#pragma unroll
            for (int r = 0; r < 2; r++) {
                const int o = 8 * j + 2 * r;
                const float gv = bf_hi(gp[r]);
                acc[o] = fmaf(gv, acc[o], bf_lo(xv[j][r].x)); acc[o + 1] = fmaf(gv, acc[o + 1], bf_hi(xv[j][r].x));
                acc[o + 4] = fmaf(gv, acc[o + 4], bf_lo(xv[j][r].y)); acc[o + 5] = fmaf(gv, acc[o + 5], bf_hi(xv[j][r].y));
                stg4_unless(op + r * 2 * D_ + 16 * j, acc[o], acc[o + 1], acc[o + 4], acc[o + 5], routed[r]);
                if (gaps) gap();
            }
        };
        auto finish_routed = [&](float (&acc)[64]) {
#pragma unroll
            for (int r = 0; r < 2; r++)
                if (routed[r]) {
#pragma unroll
                    for (int j = 0; j < 8; j++) red4(op + r * 2 * D_ + 16 * j, acc[8 * j + 2 * r], acc[8 * j + 2 * r + 1], acc[8 * j + 2 * r + 4], acc[8 * j + 2 * r + 5]);
                }
            __syncwarp();
        };
        const uint32_t xbuf = sb + slot_off(FIN) + w * 2048 + lane * 16;

        if (wg == 1) {
            float outB[64];
            const uint32_t tagw = (tag & 1) | ((tag & 2) << 15);
            mbar_wait(bar_fp);
            {
                const float4 o4 = lds128f(sb + OFF_XS + at * 16);
                const float o[4] = {o4.x, o4.y, o4.z, o4.w};
                float v[4];
#pragma unroll
                for (int u = 0; u < 4; u++) {
                    v[u] = rbf(facc[u] + o[u]);
                    if (!(cta & 1)) v[u] = __fdividef(v[u], 1.0f + __expf(-v[u]));
                }
                uint32_t w0 = pack_bf(v[0], v[1]), w1 = pack_bf(v[2], v[3]), cell[4];
                if (c == (g & 3)) { w0 = (w0 & 0xFFFEFFFEu) | tagw; w1 = (w1 & 0xFFFEFFFEu) | tagw; }
#pragma unroll
                for (int u = 0; u < 4; u++) {
                    const uint32_t s0 = __shfl_sync(0xffffffffu, w0, u, 4), s1 = __shfl_sync(0xffffffffu, w1, u, 4);
                    cell[u] = (c & 1) ? s1 : s0;
                }
                st_cell(prm.s->hid + (cta & 1) * F_ + (cta >> 1) * 64 - 512 + w * 16 + g + 8 * c, cell[0], cell[1], cell[2], cell[3], has_gu && c < 2);
            }
            release(bar_hpub);
            STAMPIF(lane == 0, 47);
            mbar_wait(bar_xb);
            load_x(0, 8);
            release(bar_xbfree);
            skip_term(0, 8);
            STAMPIF(lane == 0, 46);
            {
                uint4 hv[4], hu[4];
                const uint32_t ha = sb + OFF_XS + at * 16, hl = sb + OFF_XS + 6144 + (at & 63) * 16;
#pragma unroll 1
                for (uint32_t it = 0;; it++) {
                    mbar_wait(bar_hraw, it & 1);
                    uint32_t bad = 0;
#pragma unroll
                    for (int i = 0; i < 4; i++) {
                        hv[i] = lds128(i < 3 ? ha + i * 2048 : hl); hu[i] = lds128((i < 3 ? ha + i * 2048 : hl) + ABYTES);
                        bad |= (((c & 2) ? ((c & 1) ? hv[i].w : hv[i].z) : ((c & 1) ? hv[i].y : hv[i].x)) ^ tagw) |
                               (((c & 2) ? ((c & 1) ? hu[i].w : hu[i].z) : ((c & 1) ? hu[i].y : hu[i].x)) ^ tagw);
                    }
                    uint32_t again;
                    asm volatile("{ .reg .pred p, q; setp.ne.u32 q, %1, 0; barrier.red.or.pred.aligned p, 2, 128, q; selp.u32 %0, 1, 0, p; }" : "=r"(again) : "r"(bad & 0x00010001u) : "memory");
                    if (!uni(again)) break;
                    if (it > SPIN_LIMIT) __trap();
                    if (w == 0) load_hid();
                }
                STAMPIF(lane == 0, 48);
#pragma unroll
                for (int i = 0; i < 4; i++)
                    sts128(i < 3 ? ha + i * 2048 : hl, mul_bf2(hv[i].x, hu[i].x), mul_bf2(hv[i].y, hu[i].y), mul_bf2(hv[i].z, hu[i].z), mul_bf2(hv[i].w, hu[i].w));
                asm volatile("fence.proxy.async.shared::cta;" ::: "memory");
                __syncwarp();
                if (lane == 0) mbar_arrive(bar_hs);
                STAMPIF(lane == 0, 49);
            }
            mbar_wait(bar_order2);
            static_for<NENT - FIN>([&](auto u) {
                run_small<1, FIN + u>(outB);
                if (u == 2) { wgmma_wait<2>(); if (lane == 0) mbar_arrive(bar_fold); }
            });
            if (lane == 0) mbar_expect_tx(bar_dn, w ? 0 : 7 * ABYTES);
            wgmma_wait<0>();
            pin64(outB);
            KSTAMP(2 * NENT - FIN);
            STAMPIF(at == 0, 50);
#pragma unroll
            for (int q = 0; q < 2; q++) {
                uint4 pb[16];
                mbar_wait(bar_accb + 8 * q);
#pragma unroll
                for (int v = q * HP; v < (q ? 16 : HP); v++) pb[v] = ldsm4(xbuf + (v >> 2) * ABYTES + (v & 3) * 512);
#pragma unroll
                for (int v = q * HP; v < (q ? 16 : HP); v++) {
                    outB[4 * v] += __uint_as_float(pb[v].x); outB[4 * v + 1] += __uint_as_float(pb[v].y);
                    outB[4 * v + 2] += __uint_as_float(pb[v].z); outB[4 * v + 3] += __uint_as_float(pb[v].w);
                    if (v & 1) finish(outB, v >> 1, false);
                }
            }
            finish_routed(outB);
            STAMPIF(lane == 0, 51);
        } else {
            float outA[64], outB[64], gacc[4];
            ring.slot = 32 % NST;
            ring.prev = bar_dummy;
            mbar_wait(bar_order1);
            run_entries<1, 2>(ring, 32, GU0 + 32, outA, outB, gacc, true, true);
            run_entries<1, 0>(ring, GU0 + 32, GU0 + 33, outA, outB, gacc, false, false, [&]() {
                pin4(gacc);
                sts128(sb + OFF_XS + at * 16, __float_as_uint(gacc[0]), __float_as_uint(gacc[1]), __float_as_uint(gacc[2]), __float_as_uint(gacc[3]));
                __syncwarp();
                if (lane == 0) mbar_arrive(bar_fp);
            });
            mbar_wait(bar_xa);
            run_entries<1, 0>(ring, GU0 + 33, GU0 + 34, outA, outB, gacc, false, false, [&]() { load_x(0, 2); });
            load_x(2, 4);
            run_entries<1, 0>(ring, GU0 + 34, GU0 + 35, outA, outB, gacc, false, false, [&]() { load_x(4, 6); });
            load_x(6, 8);
            run_entries<1, 0>(ring, GU0 + 35, GU0 + 36, outA, outB, gacc, false, false, [&]() { release(bar_xafree); });
            run_entries<1, 0>(ring, GU0 + 36, FIN, outA, outB, gacc);
            static_for<NENT - FIN>([&](auto u) {
                mbar_wait(full + 8 * (FIN + u));
                run_small<0, FIN + u>(outA);
                if (u == 5 && lane == 0) mbar_arrive(bar_order2);
                wgmma_wait<1>();
                if (lane == 0) mbar_arrive(empty + 8 * (FIN + u - 1));
                if (u < 4) skip_term(2 * u, 2 * u + 2);
            });
            const uint2 sk = lds64(sb + OFF_SEL + 8 * c), fk = lds64(sb + OFF_FAC + 8 * c);
            float* y0 = prm.out + (~sk.x & 2047u) * D_ + (cta & 15) * 64 + w * 16 + g;
            float* y1 = prm.out + (~sk.y & 2047u) * D_ + (cta & 15) * 64 + w * 16 + g;
            asm volatile("" : "+l"(y0), "+l"(y1));
            mbar_wait(bar_zero);
            mbar_wait(empty + 8 * FIN);
            wgmma_wait<0>();
            pin64(outA); pin64(outB);
            STAMPIF(at == 0, 53);
            GSTAMP(at == 0, 2);
            auto dump = [&](int v) {
                if (v == 4) mbar_wait(bar_fold);
                stsm4(xbuf + (v >> 2) * ABYTES + (v & 3) * 512, __float_as_uint(outB[4 * v]), __float_as_uint(outB[4 * v + 1]), __float_as_uint(outB[4 * v + 2]),
                      __float_as_uint(outB[4 * v + 3]));
                if (v == HP - 1 || v == 15) handover(bar_accb + 8 * (v == 15));
            };
#pragma unroll
            for (int j = 0; j < 8; j++) {
                finish(outA, j, true);
#pragma unroll
                for (int v = j * NDUMP / 8; v < (j + 1) * NDUMP / 8; v++) dump(v);
            }
            STAMPIF(lane == 0, 54);
#pragma unroll
            for (int v = NDUMP; v < 16; v++) dump(v);
            STAMPIF(lane == 0, 55);
            float yacc[4];
            const uint64_t dw = make_desc(sb), dh = (uint64_t)(((sb + OFF_XS) & 0x3FFFF) >> 4) | ((uint64_t)8 << 16) | ((uint64_t)8 << 32);
            mbar_wait(bar_dn);
            STAMPIF(at == 0, 2);
            wgmma_fence();
#pragma unroll
            for (int n = 0; n < 28; n++) wgmma_n8<1, 1>(yacc, dw + (dn_off(n >> 2) >> 4) + (n & 3) * 128, dh + n * 16, n > 0);
            wgmma_commit();
            finish_routed(outA);
            wgmma_wait<0>();
            pin4(yacc);
            atomicAdd(y0, yacc[0] * __uint_as_float(fk.x)); atomicAdd(y1, yacc[1] * __uint_as_float(fk.y));
            atomicAdd(y0 + 8, yacc[2] * __uint_as_float(fk.x)); atomicAdd(y1 + 8, yacc[3] * __uint_as_float(fk.y));
            STAMPIF(lane == 0, 3);
        }
    }
}

typedef CUresult (*EncodeFn)(CUtensorMap*, CUtensorMapDataType, cuuint32_t, void*, const cuuint64_t*, const cuuint64_t*, const cuuint32_t*,
                             const cuuint32_t*, CUtensorMapInterleave, CUtensorMapSwizzle, CUtensorMapL2promotion, CUtensorMapFloatOOBfill);

bool encode(EncodeFn fn, CUtensorMap* m, const void* ptr, int rank, const cuuint64_t* dims, const cuuint64_t* strides, const cuuint32_t* box,
            CUtensorMapSwizzle sw = CU_TENSOR_MAP_SWIZZLE_128B, CUtensorMapL2promotion promo = CU_TENSOR_MAP_L2_PROMOTION_NONE) {
    const cuuint32_t es[5] = {1, 1, 1, 1, 1};
    return fn(m, CU_TENSOR_MAP_DATA_TYPE_BFLOAT16, rank, const_cast<void*>(ptr), dims, strides, box, es, CU_TENSOR_MAP_INTERLEAVE_NONE,
              sw, promo, CU_TENSOR_MAP_FLOAT_OOB_FILL_NONE) == CUDA_SUCCESS;
}

}

extern "C" void kernel_launch(void* const* d_in, const int* in_sizes, int n_in, void* d_out, int out_size) {
    (void)in_sizes; (void)n_in; (void)out_size;
    Params prm;
    prm.x = (const __nv_bfloat16*)d_in[0];
    prm.lam_re = (const __nv_bfloat16*)d_in[1];
    prm.lam_im = (const __nv_bfloat16*)d_in[2];
    prm.b_re = (const __nv_bfloat16*)d_in[3];
    prm.b_im = (const __nv_bfloat16*)d_in[4];
    prm.c_re = (const __nv_bfloat16*)d_in[5];
    prm.c_im = (const __nv_bfloat16*)d_in[6];
    prm.log_dt = (const __nv_bfloat16*)d_in[7];
    prm.dskip = (const __nv_bfloat16*)d_in[8];
    prm.w_r = (const __nv_bfloat16*)d_in[10];
    prm.gate_w = (const __nv_bfloat16*)d_in[14];
    prm.out = (float*)d_out;
    cudaGetSymbolAddress((void**)&prm.s, g_scratch);
    int dev = 0, sms = 0;
    cudaGetDevice(&dev);
    cudaDeviceGetAttribute(&sms, cudaDevAttrMultiProcessorCount, dev);
    prm.by_smid = sms == NGRID;
    prm.swapped = prm.b_im < prm.b_re;

    void* fnp = nullptr;
    cudaDriverEntryPointQueryResult qr;
    cudaGetDriverEntryPoint("cuTensorMapEncodeTiled", &fnp, cudaEnableDefault, &qr);
    EncodeFn fn = (EncodeFn)fnp;
    cudaFuncSetAttribute(fused_kernel, cudaFuncAttributeMaxDynamicSharedMemorySize, SMEM_BYTES);

    CUtensorMap mX, mB, mCre, mCim, mWg, mWu, mWd, mXr, mXe;
    const cuuint64_t row = 2048;
    {
        const cuuint64_t dims[4] = {1024, 2, 4, 976}, st[3] = {row, 32 * row, 2 * row};
        const cuuint32_t box[4] = {64, 2, 4, 16};
        encode(fn, &mX, prm.x, 4, dims, st, box, CU_TENSOR_MAP_SWIZZLE_128B, PROMO);
    }
    {
        const char *lo = (const char*)(prm.swapped ? prm.b_im : prm.b_re), *hi = (const char*)(prm.swapped ? prm.b_re : prm.b_im);
        const cuuint64_t dims[5] = {1024, 8, 2, 96, 2}, st[4] = {row, (cuuint64_t)(hi - lo), 8 * row, 256 * row};
        const cuuint32_t box[5] = {64, 8, 2, 4, 2};
        encode(fn, &mB, lo, 5, dims, st, box, CU_TENSOR_MAP_SWIZZLE_128B, PROMO);
    }
    {
        const cuuint64_t dims[5] = {1024, 2, 4, 2, 64}, st[4] = {row, 4 * row, 2 * row, 16 * row};
        const cuuint32_t box[5] = {64, 2, 4, 2, 8};
        encode(fn, &mCre, prm.c_re, 5, dims, st, box);
        encode(fn, &mCim, prm.c_im, 5, dims, st, box);
    }
    {
        const cuuint64_t dims[2] = {F_, D_}, st[1] = {F_ * 2}, dimsd[2] = {D_, F_}, std_[1] = {row};
        const cuuint32_t box[2] = {64, 32}, boxd[2] = {64, 64};
        encode(fn, &mWg, d_in[11], 2, dims, st, box, CU_TENSOR_MAP_SWIZZLE_128B, CU_TENSOR_MAP_L2_PROMOTION_NONE);
        encode(fn, &mWu, d_in[12], 2, dims, st, box, CU_TENSOR_MAP_SWIZZLE_128B, CU_TENSOR_MAP_L2_PROMOTION_NONE);
        encode(fn, &mWd, d_in[13], 2, dimsd, std_, boxd, CU_TENSOR_MAP_SWIZZLE_128B, CU_TENSOR_MAP_L2_PROMOTION_NONE);
    }
    {
        const cuuint64_t dims[3] = {D_ - 192, S_, 4}, st[2] = {row, 128};
        const cuuint32_t box[3] = {64, 16, 4};
        encode(fn, &mXr, prm.x, 3, dims, st, box, CU_TENSOR_MAP_SWIZZLE_128B, CU_TENSOR_MAP_L2_PROMOTION_NONE);
    }
    {
        const cuuint64_t dims[5] = {D_, 2, 2, 2, 976}, st[4] = {64 * row, row, 32 * row, 2 * row};
        const cuuint32_t box[5] = {64, 2, 2, 2, 8};
        encode(fn, &mXe, prm.x, 5, dims, st, box);
    }
    fused_kernel<<<NGRID, 384, SMEM_BYTES, cudaStreamPerThread>>>(prm, mX, mB, mCre, mCim, mWg, mWu, mWd, mXr, mXe);
}
```

```cpp
#include <cuda_runtime.h>
#include <cuda_bf16.h>
#include <cuda.h>
#include <stdint.h>

namespace {

constexpr int S_ = 2048, D_ = 1024, F_ = 3584;
constexpr int NCTA = 128, NGRID = 132;
#define XE_ 58
#define GU0_ 18
constexpr int NENT = 64, FIN = 58, XE = XE_;
constexpr int NST = 5;
constexpr int RE0 = 4;
constexpr int GU0 = GU0_;
constexpr uint32_t SLOT = 32768, ABYTES = 8192, WBYTES = 4096;
constexpr uint32_t OFF_XS = NST * SLOT;
constexpr uint32_t OFF_LIST = OFF_XS + 8192;
constexpr uint32_t OFF_W = OFF_XS + 16384;
constexpr uint32_t OFF_STG = OFF_W + 32768;
__host__ __device__ constexpr uint32_t slot_off(int i) { return i < XE ? (i % NST) * SLOT : i == XE ? OFF_W : ((i - 1) % NST) * SLOT; }
__host__ __device__ constexpr uint32_t dn_off(int u) { return u < 2 ? OFF_STG + u * ABYTES : u == 2 ? OFF_XS + ABYTES : slot_off(FIN - 2 + u); }
constexpr uint32_t OFF_CONST = OFF_STG;
constexpr uint32_t OFF_RED = OFF_STG + 4096;
constexpr uint32_t OFF_FULL = OFF_STG + 16384;
constexpr uint32_t OFF_EMPTY = OFF_FULL + 120 * 8;
constexpr uint32_t OFF_G = OFF_EMPTY + 88 * 8;
constexpr uint32_t OFF_DK = OFF_G + 256;
constexpr uint32_t OFF_KEYS = OFF_DK + 256;
constexpr uint32_t OFF_SEL = OFF_KEYS + 32;
constexpr uint32_t OFF_FAC = OFF_SEL + 32;
constexpr uint32_t OFF_EPOCH = OFF_FAC + 32;
constexpr uint32_t OFF_PROF = OFF_EPOCH + 16;
constexpr uint32_t SMEM_BYTES = OFF_PROF + 768;
static_assert(SMEM_BYTES <= 232448, "smem");

constexpr uint32_t sb = 1024;
constexpr uint32_t SPIN_LIMIT = 1u << 18;

struct Scratch {
    unsigned int cnt[2 * 32];
    unsigned long long rpack[S_ / 2];
    unsigned long long gpack[S_ / 2];
    uint4 time[NCTA];
    float2 carry[16 * 1024];
    uint4 hid[2 * F_];
    uint4 h[8 * 4 * 256 * 64];
};
__device__ __align__(128) Scratch g_scratch;
#define STAMPW(cond, w) do {} while (0)
#define LATE(i, tt) do {} while (0)
#define LANDED(i) do {} while (0)
#define GSTAMP(cond, w) do {} while (0)
#define STAMPIF(cond, i) STAMPW(cond, 72 + (i))
#define STAMP(i) STAMPW(1, 72 + (i))
#define KSTAMP(i) STAMPW((threadIdx.x & 127) == 0, i)

struct Params {
    const __nv_bfloat16 *x, *b_re, *b_im;
    int by_smid;
    int swapped;
    const __nv_bfloat16 *lam_re, *lam_im, *c_re, *c_im, *log_dt, *dskip, *w_r, *gate_w;
    float* out;
    Scratch* s;
};

__device__ __forceinline__ uint32_t smem_u32(const void* p) { return (uint32_t)__cvta_generic_to_shared(p); }
__device__ __forceinline__ void mbar_init(uint32_t bar, uint32_t cnt) { asm volatile("mbarrier.init.shared::cta.b64 [%0], %1;" ::"r"(bar), "r"(cnt) : "memory"); }
__device__ __forceinline__ void mbar_expect_tx(uint32_t bar, uint32_t bytes) { asm volatile("mbarrier.arrive.expect_tx.shared::cta.b64 _, [%0], %1;" ::"r"(bar), "r"(bytes) : "memory"); }
__device__ __forceinline__ void mbar_arrive(uint32_t bar) { asm volatile("mbarrier.arrive.shared::cta.b64 _, [%0];" ::"r"(bar) : "memory"); }
__device__ __forceinline__ void mbar_wait(uint32_t bar, uint32_t parity = 0) {
    asm volatile("{ .reg .pred p; .reg .u32 n;\n"
                 "mbarrier.try_wait.parity.shared::cta.b64 p, [%0], %1;\n"
                 "@p bra.uni DONE;\n"
                 "mov.u32 n, 0;\n"
                 "AGAIN: mbarrier.try_wait.parity.shared::cta.b64 p, [%0], %1;\n"
                 "@p bra.uni DONE;\n"
                 "add.u32 n, n, 1;\n"
                 "setp.lt.u32 p, n, %2;\n"
                 "@p bra.uni AGAIN;\n"
                 "trap;\n"
                 "DONE: }" ::"r"(bar), "r"(parity), "n"(SPIN_LIMIT) : "memory");
}
__device__ __forceinline__ bool elect_one() {
    uint32_t pred;
    asm volatile("{ .reg .pred P; elect.sync _|P, 0xffffffff; selp.b32 %0, 1, 0, P; }" : "=r"(pred));
    return pred;
}
__device__ __forceinline__ void named_bar(int id, int n) { asm volatile("bar.sync %0, %1;" ::"r"(id), "r"(n) : "memory"); }

#define ONE "{ .reg .pred e; elect.sync _|e, 0xffffffff;\n@e "
template <int N> __device__ __forceinline__ void mbar_init_n(uint32_t bar, uint32_t cnt, uint32_t extra = 0) {
    if (elect_one()) {
#pragma unroll
        for (int i = 0; i < N; i++) mbar_init(bar + 8 * i, i == N - 1 ? cnt + extra : cnt);
        asm volatile("fence.mbarrier_init.release.cluster;" ::: "memory");
    }
    __syncwarp();
}
__device__ __forceinline__ void bulk_load(uint32_t dst, const void* src, uint32_t bytes, uint32_t bar) {
    asm volatile(ONE "cp.async.bulk.shared::cluster.global.mbarrier::complete_tx::bytes [%0], [%1], %2, [%3]; }" ::"r"(dst), "l"(src), "r"(bytes), "r"(bar) : "memory");
}
__device__ __forceinline__ void sts128(uint32_t a, uint32_t x, uint32_t y, uint32_t z, uint32_t w) {
    asm volatile("st.shared.v4.u32 [%0], {%1,%2,%3,%4};" ::"r"(a), "r"(x), "r"(y), "r"(z), "r"(w) : "memory");
}
__device__ __forceinline__ uint2 lds64(uint32_t a) {
    uint2 v;
    asm volatile("ld.shared.v2.u32 {%0,%1}, [%2];" : "=r"(v.x), "=r"(v.y) : "r"(a) : "memory");
    return v;
}
__device__ __forceinline__ uint32_t clk32() { uint32_t c; asm volatile("mov.u32 %0, %%clock;" : "=r"(c)); return c; }
__device__ __forceinline__ void gap() { asm volatile("pmevent 1;" ::: "memory"); }
__device__ __forceinline__ void pace_until(uint32_t t) { while ((int)(clk32() - t) < 0) {} }
#define SLEEP_MARGIN 200
__device__ __forceinline__ void sleep_until(uint32_t t) {
    while ((int)(clk32() + SLEEP_MARGIN - t) < 0) __nanosleep(40);
    pace_until(t);
}
__device__ __forceinline__ void tma2(uint32_t dst, const CUtensorMap* m, int c0, int c1, uint32_t bar, uint64_t pol) {
    asm volatile(ONE "cp.async.bulk.tensor.2d.shared::cluster.global.mbarrier::complete_tx::bytes.L2::cache_hint [%0], [%1, {%3, %4}], [%2], %5; }"
                 ::"r"(dst), "l"(m), "r"(bar), "r"(c0), "r"(c1), "l"(pol) : "memory");
}
__device__ __forceinline__ void tma3(uint32_t dst, const CUtensorMap* m, int c0, int c1, uint32_t bar) {
    asm volatile(ONE "cp.async.bulk.tensor.3d.shared::cluster.global.mbarrier::complete_tx::bytes [%0], [%1, {%3, %4, %5}], [%2]; }"
                 ::"r"(dst), "l"(m), "r"(bar), "r"(c0), "r"(c1), "r"(0) : "memory");
}
__device__ __forceinline__ void tma4(uint32_t dst, const CUtensorMap* m, int c0, int c3, uint32_t bar) {
    asm volatile(ONE "cp.async.bulk.tensor.4d.shared::cluster.global.mbarrier::complete_tx::bytes [%0], [%1, {%3, %5, %5, %4}], [%2]; }"
                 ::"r"(dst), "l"(m), "r"(bar), "r"(c0), "r"(c3), "r"(0) : "memory");
}
__device__ __forceinline__ void tma5(uint32_t dst, const CUtensorMap* m, int c0, int c4, uint32_t bar) {
    asm volatile(ONE "cp.async.bulk.tensor.5d.shared::cluster.global.mbarrier::complete_tx::bytes [%0], [%1, {%3, %5, %5, %5, %4}], [%2]; }"
                 ::"r"(dst), "l"(m), "r"(bar), "r"(c0), "r"(c4), "r"(0) : "memory");
}
__device__ __forceinline__ void tma5b(uint32_t dst, const CUtensorMap* m, int c0, int c3, uint32_t bar) {
    asm volatile(ONE "cp.async.bulk.tensor.5d.shared::cluster.global.mbarrier::complete_tx::bytes [%0], [%1, {%3, %5, %5, %4, %5}], [%2]; }"
                 ::"r"(dst), "l"(m), "r"(bar), "r"(c0), "r"(c3), "r"(0) : "memory");
}
__device__ __forceinline__ void prefetch_l2(const void* p) {
    asm volatile("cp.async.ca.shared.global.L2::256B [%0], [%1], 4;" ::"r"(sb + OFF_EPOCH + 12), "l"(p) : "memory");
}

__device__ __forceinline__ uint32_t lds32(uint32_t a) {
    uint32_t v;
    asm volatile("ld.volatile.shared.u32 %0, [%1];" : "=r"(v) : "r"(a) : "memory");
    return v;
}
__device__ __forceinline__ uint32_t uni(uint32_t v) { return __shfl_sync(0xffffffffu, v, 0); }   __device__ __forceinline__ uint32_t ld_acquire(const unsigned int* p) {
    uint32_t v;
    asm volatile("ld.acquire.gpu.global.u32 %0, [%1];" : "=r"(v) : "l"(p) : "memory");
    return v;
}
__device__ __forceinline__ void red_release(unsigned int* p) { asm volatile("red.release.gpu.global.add.u32 [%0], 1;" ::"l"(p) : "memory"); }
__device__ __forceinline__ void wait_count(const unsigned int* p, uint32_t target) {
#pragma unroll 1
    for (uint32_t it = 0; it < SPIN_LIMIT; ++it)
        if ((int)(ld_acquire(p) - target) >= 0) return;
    __trap();
}
__device__ __forceinline__ void wait_count_slow(const unsigned int* p, uint32_t target) {
#pragma unroll 1
    for (uint32_t it = 0; it < SPIN_LIMIT; ++it) {
        if ((int)(ld_acquire(p) - target) >= 0) return;
        __nanosleep(200);
    }
    __trap();
}
__device__ __forceinline__ unsigned long long ld_relaxed1(const void* p) {
    unsigned long long v;
    asm volatile("ld.relaxed.gpu.global.b64 %0, [%1];" : "=l"(v) : "l"(p) : "memory");
    return v;
}
__device__ __forceinline__ ulonglong2 ld_relaxed2(const void* p) {
    ulonglong2 v;
    asm volatile("ld.relaxed.gpu.global.v2.b64 {%0, %1}, [%2];" : "=l"(v.x), "=l"(v.y) : "l"(p) : "memory");
    return v;
}
__device__ __forceinline__ void ld_cell(uint32_t (&v)[4], const void* p, bool on = true) {
    asm volatile("{ .reg .pred p; .reg .b64 l, h; .reg .b128 t; setp.ne.u32 p, %5, 0; mov.b64 l, {%0, %1}; mov.b64 h, {%2, %3}; mov.b128 t, {l, h};\n"
                 "@p ld.relaxed.gpu.global.b128 t, [%4]; mov.b128 {l, h}, t; mov.b64 {%0, %1}, l; mov.b64 {%2, %3}, h; }"
                 : "+r"(v[0]), "+r"(v[1]), "+r"(v[2]), "+r"(v[3]) : "l"(p), "r"((uint32_t)on) : "memory");
}
__device__ __forceinline__ void st_cell(void* p, uint32_t a, uint32_t b, uint32_t c, uint32_t d, bool on) {
    asm volatile("{ .reg .pred p; .reg .b64 l, h; .reg .b128 t; setp.ne.u32 p, %5, 0; mov.b64 l, {%1, %2}; mov.b64 h, {%3, %4}; mov.b128 t, {l, h};\n"
                 "@p st.relaxed.gpu.global.b128 [%0], t; }" ::"l"(p), "r"(a), "r"(b), "r"(c), "r"(d), "r"((uint32_t)on) : "memory");
}

__device__ __forceinline__ uint64_t make_desc(uint32_t addr, uint32_t sbo = 1024) {
    return (uint64_t)((addr & 0x3FFFF) >> 4) | ((uint64_t)1 << 16) | ((uint64_t)(sbo >> 4) << 32) | ((uint64_t)1 << 62);
}
__device__ __forceinline__ void wgmma_fence() { asm volatile("wgmma.fence.sync.aligned;" ::: "memory"); }
__device__ __forceinline__ void wgmma_commit() { asm volatile("wgmma.commit_group.sync.aligned;" ::: "memory"); }
template <int N> __device__ __forceinline__ void wgmma_wait() { asm volatile("wgmma.wait_group.sync.aligned %0;" ::"n"(N) : "memory"); }

#define R8(d, i) "+f"(d[i]), "+f"(d[i + 1]), "+f"(d[i + 2]), "+f"(d[i + 3]), "+f"(d[i + 4]), "+f"(d[i + 5]), "+f"(d[i + 6]), "+f"(d[i + 7])
#define R64(d) R8(d, 0), R8(d, 8), R8(d, 16), R8(d, 24), R8(d, 32), R8(d, 40), R8(d, 48), R8(d, 56)
template <int TA>
__device__ __forceinline__ void wgmma_n128(float (&d)[64], uint64_t da, uint64_t db, int scale_d = 1) {
    asm volatile("{ .reg .pred p; setp.ne.b32 p, %66, 0;\n"
                 "wgmma.mma_async.sync.aligned.m64n128k16.f32.bf16.bf16 "
                 "{%0,%1,%2,%3,%4,%5,%6,%7,%8,%9,%10,%11,%12,%13,%14,%15,%16,%17,%18,%19,%20,%21,%22,%23,%24,%25,%26,%27,%28,%29,%30,%31,"
                 "%32,%33,%34,%35,%36,%37,%38,%39,%40,%41,%42,%43,%44,%45,%46,%47,%48,%49,%50,%51,%52,%53,%54,%55,%56,%57,%58,%59,%60,%61,%62,%63}, "
                 "%64, %65, p, 1, 1, %67, 0; }"
                 : R64(d)
                 : "l"(da), "l"(db), "r"(scale_d), "n"(TA));
}
__device__ __forceinline__ void pin4(float (&d)[4]) { asm volatile("" : "+f"(d[0]), "+f"(d[1]), "+f"(d[2]), "+f"(d[3])::"memory"); }
__device__ __forceinline__ void pin64(float (&d)[64]) { asm volatile("" : R64(d)::"memory"); }

template <int TA, int TB = 0>
__device__ __forceinline__ void wgmma_n8(float (&d)[4], uint64_t da, uint64_t db, int scale_d = 1) {
    asm volatile("{ .reg .pred p; setp.ne.b32 p, %7, 0;\n"
                 "wgmma.mma_async.sync.aligned.m64n8k16.f32.bf16.bf16 {%0,%1,%2,%3}, %4, %5, p, 1, 1, %6, %8; }"
                 : "+f"(d[0]), "+f"(d[1]), "+f"(d[2]), "+f"(d[3])
                 : "l"(da), "l"(db), "n"(TA), "r"(scale_d), "n"(TB));
}

__device__ __forceinline__ float bf_lo(uint32_t u) { return __uint_as_float(u << 16); }
__device__ __forceinline__ float bf_hi(uint32_t u) { return __uint_as_float(u & 0xFFFF0000u); }
__device__ __forceinline__ float rbf(float v) { return __bfloat162float(__float2bfloat16_rn(v)); }
__device__ __forceinline__ uint32_t pack_bf(float lo, float hi) {
    uint32_t r;
    asm("cvt.rn.bf16x2.f32 %0, %1, %2;" : "=r"(r) : "f"(hi), "f"(lo));
    return r;
}
__device__ __forceinline__ uint32_t mul_bf2(uint32_t a, uint32_t b) {
    __nv_bfloat162 r = __hmul2(*reinterpret_cast<__nv_bfloat162*>(&a), *reinterpret_cast<__nv_bfloat162*>(&b));
    return *reinterpret_cast<uint32_t*>(&r);
}
__device__ __forceinline__ uint32_t fma_bf2(uint32_t a, uint32_t b, uint32_t c) {
    uint32_t r;
    asm("fma.rn.bf16x2 %0, %1, %2, %3;" : "=r"(r) : "r"(a), "r"(b), "r"(c));
    return r;
}
__device__ __forceinline__ float2 cmul(float2 a, float2 b) { return make_float2(a.x * b.x - a.y * b.y, a.x * b.y + a.y * b.x); }
__device__ __forceinline__ float2 cfma(float2 a, float2 b, float2 c) {
    return make_float2(fmaf(a.x, b.x, fmaf(-a.y, b.y, c.x)), fmaf(a.x, b.y, fmaf(a.y, b.x, c.y)));
}
__device__ __forceinline__ float sigmoidf_(float v) { return __fdividef(1.0f, 1.0f + expf(-v)); }

__device__ __forceinline__ void bulk_prefetch(const void* src, uint32_t bytes) {
    asm volatile(ONE "cp.async.bulk.prefetch.L2.global [%0], %1; }" ::"l"(src), "r"(bytes) : "memory");
}
__device__ __forceinline__ void bulk_store(void* dst, uint32_t src, uint32_t bytes) {
    asm volatile(ONE "cp.async.bulk.global.shared::cta.bulk_group [%0], [%1], %2; }" ::"l"(dst), "r"(src), "r"(bytes) : "memory");
}
__device__ __forceinline__ uint4 lds128(uint32_t a) {
    uint4 v;
    asm volatile("ld.shared.v4.u32 {%0,%1,%2,%3}, [%4];" : "=r"(v.x), "=r"(v.y), "=r"(v.z), "=r"(v.w) : "r"(a) : "memory");
    return v;
}
__device__ __forceinline__ float4 lds128f(uint32_t a) {
    float4 v;
    asm volatile("ld.shared.v4.f32 {%0,%1,%2,%3}, [%4];" : "=f"(v.x), "=f"(v.y), "=f"(v.z), "=f"(v.w) : "r"(a) : "memory");
    return v;
}
__device__ __forceinline__ void stsm4(uint32_t a, uint32_t x, uint32_t y, uint32_t z, uint32_t w) {
    asm volatile("stmatrix.sync.aligned.m8n8.x4.shared.b16 [%0], {%1,%2,%3,%4};" ::"r"(a), "r"(x), "r"(y), "r"(z), "r"(w) : "memory");
}
__device__ __forceinline__ uint4 ldsm4(uint32_t a) {
    uint4 v;
    asm volatile("ldmatrix.sync.aligned.m8n8.x4.shared.b16 {%0,%1,%2,%3}, [%4];" : "=r"(v.x), "=r"(v.y), "=r"(v.z), "=r"(v.w) : "r"(a) : "memory");
    return v;
}
__device__ __forceinline__ void stg4_unless(float* p, float a, float b, float c, float d, uint32_t skip) {
    asm volatile("{ .reg .pred p; setp.eq.u32 p, %5, 0; @p st.global.v4.f32 [%0], {%1,%2,%3,%4}; }" ::"l"(p), "f"(a), "f"(b), "f"(c), "f"(d), "r"(skip) : "memory");
}
__device__ __forceinline__ void red4(float* p, float a, float b, float c, float d) {
    asm volatile("red.global.add.v4.f32 [%0], {%1,%2,%3,%4};" ::"l"(p), "f"(a), "f"(b), "f"(c), "f"(d) : "memory");
}

#define TT0 3100
#define PER 516
#define PCUT 60
#define PFIN 400
#define PF0 1700
#define PFX_PACE 400
#define PFV 6
#define PFT 0
#define PF1 700
#define T2 400
#define P2 550
#define G0 450
#define R0 2300
#define R_PACE 350
#define W_SHIFT 250
#define PROMO CU_TENSOR_MAP_L2_PROMOTION_L2_256B
#define POLL_S 0
#define ST_TOL 100
#define ST_SHIFT 300
#define CLK_NS 420
#define MARGIN 200
#define BP1 10
#define NDUMP 4
#define HP NDUMP
#define DNL 1
#define AE 6
#define AG0 900
#define AB 16
#define HGE 38
constexpr uint32_t duration(int i) { return PER + (i >= RE0 && i < RE0 + 4 ? 72 : 0) + (i >= GU0 && i < GU0 + 32 ? 36 : 0); }
constexpr uint32_t cmax(uint32_t a, uint32_t b) { return a > b ? a : b; }
constexpr uint32_t issue_time(int i) {
    return i <= NST ? TT0 : i < XE ? issue_time(i - 1) + duration(i - NST) - (i >= XE - 3 && i > GU0 + 36 ? PCUT : 0) : issue_time(XE - 1) + cmax((i - XE + 1) * PFIN, (i - XE) * 512);
}
template <int I> struct Sched { static constexpr uint32_t t = issue_time(I); };
template <int LO, int HI, class F>
__device__ __forceinline__ void for_entries(uint32_t base, F body) {
    constexpr uint32_t per = Sched<LO + 1>::t - Sched<LO>::t;
    static_assert(Sched<HI - 1>::t - Sched<LO>::t == (HI - 1 - LO) * per, "period");
    uint32_t tt = base + Sched<LO>::t;
#pragma unroll 1
    for (int i = LO; i < HI; i++) {
        body(i, tt);
        tt += per;
    }
}

struct Ring { uint32_t prev; int slot; };
struct NoHook { __device__ void operator()() const {} };
template <int TA, int SM, class H = NoHook>
__device__ __forceinline__ void run_entries(Ring& r, int lo, int hi, float (&accA)[64], float (&accB)[64], float (&small)[4],
                                            bool fresh = false, bool sfresh = false, H released = H()) {
    const uint64_t d0 = make_desc(sb);
    const bool leader = (threadIdx.x & 31) == 0;
#pragma unroll 1
    for (int i = lo; i < hi; i++) {
        const uint32_t bar = sb + OFF_FULL + 8 * i;
        const uint64_t da = d0 + (uint64_t)(r.slot * (SLOT >> 4));
        const int n = i - (SM == 1 ? RE0 : GU0);
        const uint64_t dw = d0 + (uint64_t)((OFF_W >> 4) + (SM == 1 ? n * 512 : (n & 7) * 256));
        const uint64_t dt8 = d0 + (uint64_t)((OFF_XS >> 4) + (SM == 1 ? n * 64 : (n >> 1) * 64 + (n & 1) * 4));
        r.slot = r.slot == NST - 1 ? 0 : r.slot + 1;
        mbar_wait(bar);
        KSTAMP(i);
        wgmma_fence();
#pragma unroll
        for (int kk = 0; kk < 4; kk++) {
            wgmma_n128<TA>(accA, da + kk * (TA ? 128 : 2), da + 1024 + kk * 2, kk > 0 || !fresh);
            if (SM == 1) wgmma_n8<0>(small, dw + kk * 2, dt8 + kk * 2, kk > 0 || !sfresh);
            if (SM == 2 && (kk & 1)) wgmma_n8<1>(small, dw + (kk >> 1) * 128, dt8 + (kk >> 1) * 2, kk > 1 || !sfresh);
            wgmma_n128<TA>(accB, da + 512 + kk * (TA ? 128 : 2), da + 1024 + kk * 2, kk > 0 || !fresh);
            if (kk == 1) {
                wgmma_commit();
                wgmma_wait<1>();
                if (leader) mbar_arrive(r.prev);
                released();
            }
        }
        wgmma_commit();
        r.prev = bar + (OFF_EMPTY - OFF_FULL);
        fresh = sfresh = false;
    }
}
template <int HALF, int I>
__device__ __forceinline__ void run_small(float (&acc)[64]) {
    const uint64_t da = make_desc(sb) + (slot_off(I) >> 4);
    KSTAMP(I + HALF * (NENT - FIN));
    wgmma_fence();
#pragma unroll
    for (int kk = 0; kk < 4; kk++) wgmma_n128<1>(acc, da + HALF * 512 + kk * 128, da + 1024 + kk * 2, kk > 0 || !(HALF && I == FIN));
    wgmma_commit();
}
template <int V> struct Int { __host__ __device__ constexpr operator int() const { return V; } };
template <int N, class F> __device__ __forceinline__ void static_for(F f) {
    if constexpr (N > 0) { static_for<N - 1>(f); f(Int<N - 1>()); }
}

__global__ void __launch_bounds__(384, 1)
fused_kernel(const __grid_constant__ Params prm, const __grid_constant__ CUtensorMap mX, const __grid_constant__ CUtensorMap mB, const __grid_constant__ CUtensorMap mCre,
             const __grid_constant__ CUtensorMap mCim, const __grid_constant__ CUtensorMap mWg, const __grid_constant__ CUtensorMap mWu,
             const __grid_constant__ CUtensorMap mWd, const __grid_constant__ CUtensorMap mXr, const __grid_constant__ CUtensorMap mXe) {
    extern __shared__ __align__(1024) uint8_t smem[];
    const uint32_t cstart = clk32();
    const int tid = threadIdx.x, lane = tid & 31;
    uint32_t smid;
    asm volatile("mov.u32 %0, %%smid;" : "=r"(smid));
    {
        const uint32_t b = blockIdx.x & 127, r = tid - PFT, o = (r >> 1) * 2048 + (r & 1) * 128;
#define PFS "@q prefetch.global.L2 [%1]; @p prefetch.global.L2 [%0]; @q prefetch.global.L2 [%2];"
        asm volatile("{ .reg .pred p, q; setp.lt.u32 p, %3, 32; setp.lt.u32 q, %3, 8;\n" PFS " }"
                     ::"l"((const char*)prm.x + (b * 32768 + o)), "l"((const char*)prm.b_re + (b * 8192 + o)), "l"((const char*)prm.b_im + (b * 8192 + o)), "r"(r),
                     "r"(sb + OFF_EPOCH + 12) : "memory");
        gap();
        STAMPIF(tid == PFT, 33);
    }
    const int warp = __shfl_sync(0xffffffffu, tid >> 5, 0);
    int cta;
    asm("{ .reg .pred p; .reg .u32 s, a, b, u, q;\n"
                 "mov.u32 s, %3;\n"
                 "and.b32 a, s, 14; shl.b32 a, a, 2; shr.u32 b, s, 4; add.u32 a, a, b;\n"
                 "sub.u32 u, s, 64; shr.u32 u, u, 1; mul.lo.u32 q, u, 37; shr.u32 q, q, 8; shl.b32 u, u, 3; mad.lo.u32 u, q, -55, u; add.u32 u, u, 12;\n"
                 "setp.lt.u32 p, s, 64; selp.u32 a, a, u, p; and.b32 b, s, 1; mad.lo.u32 a, a, 2, b;\n"
                 "setp.lt.u32 p, s, 124; selp.u32 b, 8, -116, p; add.u32 b, b, s; setp.lt.u32 p, s, 120; selp.u32 a, a, b, p;\n"
                 "setp.ne.u32 p, %2, 0; selp.u32 %0, a, %1, p; }" : "=r"(cta) : "r"(blockIdx.x), "r"(prm.by_smid), "r"(smid));
    const int chunk = (cta >> 5) * 4 + ((cta >> 2) & 3);
    const int dt = ((cta >> 4) & 1) * 4 + (cta & 3);
    asm volatile("{ .reg .pred e, p; elect.sync _|e, 0xffffffff; setp.eq.and.u32 p, %0, 5, e;\n"
                 "@p mbarrier.init.shared::cta.b64 [%1], 1; @p mbarrier.init.shared::cta.b64 [%1 + 8], 1;\n"
                 "fence.mbarrier_init.release.cluster; }" ::"r"(warp), "r"(sb + OFF_FULL) : "memory");
    if (warp == 5 && cta < NCTA) {
        tma5b(sb, &mB, 0, dt * 4, sb + OFF_FULL);
        tma4(sb + 2 * ABYTES, &mX, 0, chunk * 64, sb + OFF_FULL);
        STAMP(31);
        tma5b(sb + SLOT, &mB, 64, dt * 4, sb + OFF_FULL + 8);
        tma4(sb + SLOT + 2 * ABYTES, &mX, 64, chunk * 64, sb + OFF_FULL + 8);
    }
    if (cta >= NCTA) {
        if (smem_u32(smem) != sb) __trap();
        if (tid == 0) wait_count_slow(&prm.s->cnt[0], (atomicAdd(&prm.s->cnt[0], 1u) / NGRID + 1) * NGRID);
        return;
    }
    const bool has_gu = cta >= 16;
    constexpr uint32_t full = sb + OFF_FULL, empty = sb + OFF_EMPTY;
    constexpr uint32_t raw = full + 8 * 32;
    constexpr uint32_t bar_hraw = full + 8 * 97, bar_xs = full + 8 * 98, bar_xb = full + 8 * 100, bar_xa = full + 8 * 101,
        bar_retry = full + 8 * 102, bar_out = full + 8 * 104;
    constexpr uint32_t bar_base = empty - 64, bar_init3 = empty - 56, bar_rdone = empty - 48, bar_order0 = empty - 40, bar_init2 = empty - 32,
        bar_vec = empty - 24, bar_epoch = empty - 16, bar_dummy = empty - 8, bar_xs0 = empty + 8 * 69,
        bar_zero = empty + 8 * 70, bar_xafree = empty + 8 * 71, bar_order2 = empty + 8 * 72, bar_dn = empty + 8 * 73, bar_fp = empty + 8 * 74,
        bar_hs = empty + 8 * 75, bar_accb = empty + 8 * 76, bar_xbfree = empty + 8 * 78, bar_fold = empty + 8 * 79, bar_st = empty + 8 * 80,
        bar_hpub = empty + 8 * 66, bar_order1 = empty + 8 * 67, bar_cand = empty + 8 * 68;

    auto load_hid = [&]() {
        if (lane == 0) mbar_expect_tx(bar_hraw, 2 * 7168);
        bulk_load(sb + OFF_XS, prm.s->hid + (cta >> 4) * 448, 7168, bar_hraw);
        bulk_load(sb + OFF_XS + ABYTES, prm.s->hid + F_ + (cta >> 4) * 448, 7168, bar_hraw);
    };

    if (warp == 5) {
        if (lane < 2) mbar_expect_tx(full + 8 * lane, SLOT);
        __syncwarp();
        named_bar(0, 256);
#pragma unroll 1
        for (int i = 2; i < NST; i++) {
            pace_until(cstart + T2 + i * P2);
            tma5b(sb + i * SLOT, &mB, i * 64, dt * 4, full + 8 * i);
            tma4(sb + i * SLOT + 2 * ABYTES, &mX, i * 64, chunk * 64, full + 8 * i);
            STAMPIF(i == 4, 1);
        }
    } else if (warp == 4) {
        mbar_init_n<12>(bar_init2, 4);
        asm volatile("bar.arrive 0, 256;" ::: "memory");
        mbar_init_n<4>(bar_base, 4);
        mbar_init_n<8>(empty + 64, 4);
        *reinterpret_cast<uint2*>(smem + OFF_KEYS + 16) = make_uint2(0, 0);
        asm volatile("bar.arrive 1, 64;" ::: "memory");
        asm volatile("bar.arrive 5, 96;" ::: "memory");
        asm volatile("bar.arrive 6, 96;" ::: "memory");
        mbar_init_n<32>(full + 256, 3);
        if (lane < 2) mbar_arrive(bar_init2);
    } else if ((warp >> 1) == 3) {
        if (warp == 6) {
            mbar_init_n<8>(full + 16, 1);
            if (lane >= 2 && lane < 10) mbar_expect_tx(full + 8 * lane, lane >= RE0 && lane < RE0 + 4 ? SLOT + ABYTES : SLOT);
            __syncwarp();
            asm volatile("bar.arrive 0, 256;" ::: "memory");
        }
        const char* pf0 = (warp & 1) ? (const char*)((cta & 64) ? prm.b_im : prm.b_re) + (cta & 63) * 16384 : (const char*)prm.x + cta * 32768;
        pace_until(cstart + PF1);
        asm volatile("prefetch.global.L2 [%0];" ::"l"(pf0 + (lane & (30 >> (warp & 1) & 30)) * 1024 + (lane & 1) * 128 + 256));
        const int i0 = warp == 6 ? 10 : 21;
        mbar_init_n<11>(full + 8 * i0, 1);
        if (lane >= i0 && lane < i0 + 11) mbar_expect_tx(full + 8 * lane, lane >= GU0 && has_gu ? SLOT + WBYTES : SLOT);
        mbar_init_n<24>(full + 512 + 192 * (warp & 1), 1);
        named_bar(5, 96);
        if (lane == 0) mbar_arrive(bar_init2);
        STAMP(21);
    }
    __syncwarp();

    if (warp >= 8) {
        asm volatile("setmaxnreg.dec.sync.aligned.u32 72;");
        const uint32_t c0 = cstart;
        uint64_t stream;
        asm volatile("createpolicy.fractional.L2::evict_first.b64 %0, 1.0;" : "=l"(stream));
        const CUtensorMap* mw = (cta & 1) ? &mWu : &mWg;
        const int dc = (cta & 15) * 64, dr = (cta >> 4) * 448;
        auto gutile = [&](int i) {
            const int n = i + 3 - GU0;
            if (has_gu) tma2(sb + OFF_W + (n & 7) * WBYTES, mw, (cta >> 1) * 64 - 512, n * 32, full + 8 * (i + 3), stream);
        };
        if (warp == 8) {
            named_bar(0, 256);
            asm volatile("prefetch.tensormap [%0];" ::"l"(&mXr));
#pragma unroll 1
            for (int u = 0; u < 2; u++) {
                sleep_until(c0 + R0 + u * R_PACE);
                tma3(sb + OFF_W + u * ABYTES, &mXr, u * 256, cta * 16, full + 8 * (RE0 + u));
            }
            uint32_t dst = sb;
            auto gemm1 = [&](int i, uint32_t tt) {
                mbar_wait(empty + 8 * (i - NST));
                LATE(i, tt);
                pace_until(tt);
                tma5b(dst, &mB, (i & 15) * 64, (i >> 4) * 64 + dt * 4, full + 8 * i);
                tma4(dst + 2 * ABYTES, &mX, (i & 15) * 64, chunk * 64, full + 8 * i);
                dst = dst == sb + (NST - 1) * SLOT ? sb : dst + SLOT;
            };
            mbar_wait(bar_init2);
            uint32_t tt = c0 + TT0;
#pragma unroll 1
            for (int i = NST; i < AB; i++) {
                gemm1(i, tt);
                if (i < 7) tma3(sb + OFF_W + (i - 3) * ABYTES, &mXr, (i - 3) * 256, cta * 16, full + 8 * (i + 1));
                tt += (i & ~3) == RE0 + 4 ? PER + 72 : PER;
            }
            mbar_wait(bar_base);
            const uint32_t base = uni(lds32(sb + OFF_EPOCH + 8));
            tt = base + Sched<AB>::t;
#pragma unroll 1
            for (int i = AB; i < 32; i++) {
                gemm1(i, tt);
                tt += i >= GU0 + 4 ? PER + 36 : PER;
            }
            const char* hsrc = reinterpret_cast<const char*>(prm.s->h) + (size_t)chunk * 524288;
            auto gemm2 = [&](int i, uint32_t d, int freed, uint32_t tt) {
                mbar_wait(empty + 8 * freed);
                LATE(i, tt);
                pace_until(tt);
                bulk_load(d, hsrc, 2 * ABYTES, raw + 8 * i);
                tma5(d + 2 * ABYTES, (i & 4) ? &mCim : &mCre, ((i & 3) + ((i >> 1) & 12)) * 64, dt * 8, full + 8 * i);
                hsrc += 2 * ABYTES;
            };
            for_entries<32, GU0 + 29>(base, [&](int i, uint32_t tt) {
                gemm2(i, dst, i - NST, tt);
                gutile(i);
                dst = dst == sb + (NST - 1) * SLOT ? sb : dst + SLOT;
            });
            for_entries<GU0 + 29, GU0 + 37>(base, [&](int i, uint32_t tt) {
                gemm2(i, dst, i - NST, tt);
                const int n = i - GU0 - 29;
                if ((n & 5) == 1) tma5(sb + OFF_W + (n & 2) * (ABYTES / 2), &mXe, dt * 128 + (n & 2) * 32, chunk * 64, bar_xa);
                else if (n < 7) asm volatile(ONE "cp.async.bulk.prefetch.tensor.2d.L2.global [%0, {%1, %2}]; }" ::"l"(&mWd), "r"(dc), "r"(dr + 64 * (n < 4 ? 2 + n / 2 : n)) : "memory");
                dst = dst == sb + (NST - 1) * SLOT ? sb : dst + SLOT;
            });
            static_for<NENT - GU0 - 37>([&](auto u) {
                constexpr int i = GU0 + 37 + u;
                if (i == 60) mbar_wait(bar_out + 56);
                gemm2(i, sb + slot_off(i), i < XE ? i - NST : i == XE ? 71   : i - NST - 1, base + Sched<i>::t);
            });
            STAMP(4);
        } else if (warp == 9) {
#pragma unroll
            for (int u = 0; u < 8; u++) {
                const int row = (u >> 2) * 4 + (lane >> 3);
                asm volatile("cp.async.cg.shared.global [%0], [%1], 16;" ::"r"(sb + OFF_XS + (u & 3) * 1024 + row * 128 + (((lane & 7) ^ row) << 4)),
                             "l"((const char*)(u < 4 ? prm.w_r : prm.gate_w) + (u & 3) * 512 + lane * 16) : "memory");
            }
            uint32_t ticket = 0;
            if (lane == 0) ticket = atomicAdd(&prm.s->cnt[0], 1u);
            named_bar(1, 64);
            if (lane == 0) *reinterpret_cast<volatile uint32_t*>(smem + OFF_EPOCH) = ticket / NGRID;
            __syncwarp();
            if (lane < 4) mbar_arrive(bar_epoch);
            asm volatile("cp.async.wait_all;" ::: "memory");
            asm volatile("fence.proxy.async.shared::cta;" ::: "memory");
            __syncwarp();
            if (lane < 4) mbar_arrive(bar_vec);
            STAMP(18);
#pragma unroll 1
            for (int i = 4; i < 22; i++) mbar_init_n<4>(empty + 32 * i, 4, i >= 6 && i < 13);
            if (lane < 2) mbar_arrive(bar_init3);
            STAMP(19);
            mbar_wait(bar_cand);
            {
                const uint32_t* list = reinterpret_cast<const uint32_t*>(smem + OFF_LIST);
                const int n = (int)lds32(sb + OFF_KEYS + 16);
#pragma unroll 1
                for (int i0 = 0; i0 < n; i0 += 32) {
                    const uint32_t k = list[i0 + lane];
                    int rank = 0;
#pragma unroll 2
                    for (int o = 0; o < n; o += 4) {
                        const uint4 l4 = *reinterpret_cast<const uint4*>(list + o);
                        rank += (l4.x > k) + (l4.y > k) + (l4.z > k) + (l4.w > k);
                    }
                    if (rank < 8) reinterpret_cast<uint32_t*>(smem + OFF_SEL)[rank] = k;
                }
                __syncwarp();
                STAMP(6);
                const uint32_t key = lds32(sb + OFF_SEL + 4 * (lane & 7)), tok = ~key & 2047u, tag = lds32(sb + OFF_EPOCH) + 1;
                const uint32_t ta = __shfl_sync(0xffffffffu, tok, lane >> 3), tb = __shfl_sync(0xffffffffu, tok, 4 + (lane >> 3));
                const uint32_t da = sb + OFF_XS + (lane >> 3) * 128 + (((lane & 7) ^ (lane >> 3)) << 4), db = (da ^ 64) + 512;
                const char *sa = (const char*)prm.x + ta * 2048 + (lane & 7) * 16, *sc = (const char*)prm.x + tb * 2048 + (lane & 7) * 16;
#pragma unroll
                for (int u = 0; u < 16; u++) {
                    asm volatile("cp.async.cg.shared.global [%0], [%1], 16;" ::"r"(da + u * 1024), "l"(sa + u * 128) : "memory");
                    asm volatile("cp.async.cg.shared.global [%0], [%1], 16;" ::"r"(db + u * 1024), "l"(sc + u * 128) : "memory");
                    if (u == 3) {
                        asm volatile("cp.async.wait_all;" ::: "memory");
                        asm volatile("fence.proxy.async.shared::cta;" ::: "memory");
                        __syncwarp();
                        if (lane < 4) mbar_arrive(bar_xs0);
                        STAMP(17);
                    }
                }
                if ((tok >> 7) == (uint32_t)chunk) {
                    float4* zp = reinterpret_cast<float4*>(prm.out + tok * D_ + dt * 128) + (lane >> 3) * 2;
#pragma unroll
                    for (int u = 0; u < 8; u++) zp[(u >> 1) * 8 + (u & 1)] = make_float4(0.f, 0.f, 0.f, 0.f);
                }
                uint32_t it = 0;
                unsigned long long u;
                do {
                    u = ld_relaxed1(&prm.s->gpack[tok >> 1]);
                    if (++it > SPIN_LIMIT) __trap();
                } while (!__all_sync(0xffffffffu, (uint32_t)(u >> 32) == tag));
                const uint32_t kb = key >> 16;
                const float r = bf_lo((kb & 0x8000u) ? (kb & 0x7FFFu) : (~kb & 0xFFFFu)), gv = (tok & 1) ? bf_hi((uint32_t)u) : bf_lo((uint32_t)u);
                reinterpret_cast<float*>(smem + OFF_FAC)[lane & 7] = rbf(1.0f - gv) * rbf(sigmoidf_(r));
                asm volatile("cp.async.wait_all;" ::: "memory");
                asm volatile("fence.proxy.async.shared::cta;" ::: "memory");
                __syncwarp();
                if (lane == 0) mbar_arrive(bar_xs);
                STAMP(7);
            }
            char* hd = reinterpret_cast<char*>(prm.s->h) + (size_t)chunk * 524288 + (dt >> 1) * 16384 + (dt & 1) * 4096;
            mbar_wait(bar_base);
            const uint32_t cb = uni(lds32(sb + OFF_EPOCH + 8)) + ST_SHIFT;
            uint32_t tt = cb + Sched<GU0 + 4>::t;
#pragma unroll 1
            for (int np = 0; np < 16; np++) {
                if (!(np & (np & 4 ? 1 : 2))) mbar_wait(bar_st + 4 * (np & 12) + ((np & 3) ? 8 : 0));
                const uint32_t now = clk32() - ST_TOL;
#pragma unroll 1
                while ((int)(tt - now) < 0) tt += PER + 36;
                const uint32_t src = sb + OFF_STG + (np & 3) * 4096;
                pace_until(tt);
                bulk_store(hd, src, 4096);
                asm volatile("cp.async.bulk.commit_group;" ::: "memory");
                if (np & 2) {
                    if (np & 1) asm volatile("cp.async.bulk.wait_group.read 0;" ::: "memory");
                    else asm volatile("cp.async.bulk.wait_group.read 1;" ::: "memory");
                    __syncwarp();
                    const uint32_t u8 = 4 * (np & 12) + 8 * (np & 1);
                    if (lane < 2) mbar_arrive(lane ? (np < 15 ? empty + 8 * 27 + 4 * u8 : bar_dummy) : bar_out + u8);
                }
                STAMPIF(np & 2, 8 + ((np >> 1) & 6) + (np & 1));
                hd += (np & 1) ? 65536 - 8192 : 8192;
                tt += PER + 36;
            }
#pragma unroll 1
            for (int u = 0; u < 2; u++) {
                pace_until(tt);
                tma5(sb + OFF_STG + u * ABYTES, &mXe, dt * 128 + u * 64, chunk * 64 + 8, bar_xb);
                tt += PER + 36;
            }
            wait_count(&prm.s->cnt[32], (lds32(sb + OFF_EPOCH) + 1) * NCTA);
            if (lane < 4) mbar_arrive(bar_zero);
            mbar_wait(bar_hpub);
            sleep_until(cb + Sched<GU0 + HGE>::t);
            load_hid();
            static_for<7>([&](auto u) {
                if (u != 1) mbar_wait(u == 0 ? bar_xbfree : u == 2 ? bar_hs : empty + 8 * (u == 3 ? FIN + DNL : FIN - 2 + u));
                if (u < 3) sleep_until(cb + Sched<(u < 2 ? GU0 + HGE + u : NENT - 1)>::t);
                tma2(sb + dn_off(u), &mWd, dc, dr + u * 64, bar_dn, stream);
            });
            STAMP(27);
        } else {
            named_bar(6, 96);
            if (warp == 10) {
                const char* pb = (const char*)((cta & 64) ? prm.b_im : prm.b_re) + (cta & 63) * 16384;
                const char* pf = (lane < 16 ? (const char*)prm.x + cta * 32768 : pb) + (lane & 15) * 2048 + 512;
#pragma unroll 1
                for (int k = 0; k < 11; k++) {
                    sleep_until(c0 + PF0 + k * PFX_PACE);
                    if (lane < 16 ? k < 6 : lane < 24 && !(k & 1)) prefetch_l2(pf + k * (lane < 16 ? 256 : 128));
                }
                static_for<12>([&](auto k) {
                    sleep_until(c0 + Sched<BP1 + k>::t + ST_SHIFT);
                    bulk_prefetch((k < 4 ? pb + 1048576 : (const char*)(k < 8 ? prm.c_re : prm.c_im) + cta * 16384) + (k & 3) * 4096, 4096);
                    if (k == 4) { mbar_wait(bar_init2); mbar_wait(bar_init3); }
                    if (k >= 4 && lane < 8) mbar_expect_tx(full + 8 * (8 * k + lane), 8 * k + lane < GU0 + 32 && has_gu ? 2 * ABYTES + WBYTES : 2 * ABYTES);
                });
                asm volatile("prefetch.tensormap [%0];" ::"l"(&mCre));
                asm volatile("prefetch.tensormap [%0];" ::"l"(&mCim));
                asm volatile("prefetch.tensormap [%0];" ::"l"(&mWd));
                asm volatile("prefetch.tensormap [%0];" ::"l"(&mXe));
                if (lane < 2) mbar_expect_tx(bar_xb + 8 * lane, 2 * ABYTES);
                mbar_wait(bar_xs);
                mbar_wait(bar_st);
                if (lane == 0) red_release(&prm.s->cnt[32]);
                __syncwarp();
                STAMP(22);
            } else {
                asm volatile("prefetch.tensormap [%0];" ::"l"(mw));
                mbar_wait(bar_epoch);
                const uint32_t tag = lds32(sb + OFF_EPOCH) + 1;
                st_cell(prm.s->time + cta, 0, 0, 0, 0, lane == 0);
                mbar_wait(empty + 8 * AE);
                uint32_t gown, tm[4][4] = {}, it = 0;
                asm volatile("mov.u32 %0, %%globaltimer_lo;" : "=r"(gown));
                const uint32_t town = clk32();
                st_cell(prm.s->time + cta, tag, town, gown, 0, lane == 0);
                sleep_until(town + AG0);
                do {
#pragma unroll
                    for (int m = 0; m < 4; m++) ld_cell(tm[m], prm.s->time + ((cta & 96) ^ (32 * m)) + lane);
                    if (++it > SPIN_LIMIT) __trap();
                } while (!__all_sync(0xffffffffu, tm[0][0] == tag && tm[1][0] == tag && tm[2][0] == tag && tm[3][0] == tag));
                const int last = __reduce_max_sync(0xffffffffu, max(max((int)(tm[0][2] - gown), (int)(tm[1][2] - gown)), max((int)(tm[2][2] - gown), (int)(tm[3][2] - gown))));
                const uint32_t cand = tm[0][1] + ((min((int)(gown + last - tm[0][2]), 4000) * CLK_NS) >> 8);
                const uint32_t b0 = __shfl_sync(0xffffffffu, cand, cta & 16), b1 = __shfl_sync(0xffffffffu, cand, cta & 30);
                const uint32_t base = (b0 - b1 + 400u < 800u ? b0 : b1) + MARGIN - Sched<AE + NST>::t;
                *reinterpret_cast<volatile uint32_t*>(smem + OFF_EPOCH + 8) = base;
                mbar_wait(bar_init3);
                if (lane < 4) mbar_arrive(bar_base);
                STAMP(23);
                const uint32_t cb = base + W_SHIFT;
                auto early = [&](int i, uint32_t tt) {
                    mbar_wait(empty + 8 * (i - NST));
                    pace_until(tt);
                    gutile(i);
                };
                for_entries<GU0 - 3, GU0 + 4>(cb, early);
                for_entries<GU0 + 4, 32>(cb, early);
            }
            mbar_wait(bar_epoch);
            const uint32_t t2 = lds32(sb + OFF_EPOCH) + 1, tagw = (t2 & 1) | ((t2 & 2) << 15), half = (warp & 1) * ABYTES;
            const uint32_t lo = half + lane * 32 + (lane & 4) * 4 + (lane >> 3) * 4, retry = bar_retry + (warp & 1) * 8;
            const bool leader = lane == 0;
            uint32_t slot = sb + (32 % NST) * SLOT, rpar = 0;
#pragma unroll 1
            for (int i = 32; i < NENT; i++) {
                const uint32_t src = i == XE ? sb + OFF_W : slot;
                if (i != XE) slot = slot == sb + (NST - 1) * SLOT ? sb : slot + SLOT;
                auto current = [&]() {
                    uint32_t v[8];
#pragma unroll
                    for (int u = 0; u < 8; u++) v[u] = lds32(src + lo + u * 1024);
#pragma unroll
                    for (int u = 0; u < 8; u += 2) asm("lop3.b32 %0, %0, %1, %2, 0x7e;" : "+r"(v[u]) : "r"(v[u + 1]), "r"(tagw));
                    return __all_sync(0xffffffffu, ((v[0] | v[2] | v[4] | v[6]) & 0x00010001u) == 0);
                };
                mbar_wait(raw + 8 * i);
                if (!current()) {
#pragma unroll 1
                    for (uint32_t it = 0;; it++) {
                        if (it > SPIN_LIMIT) __trap();
                        STAMP(16);
                        if (leader) mbar_expect_tx(retry, ABYTES);
                        bulk_load(src + half, reinterpret_cast<const char*>(prm.s->h) + (size_t)chunk * 524288 + (i - 32) * 16384 + half, ABYTES, retry);
                        mbar_wait(retry, rpar);
                        rpar ^= 1;
                        if (current()) break;
                    }
                }
                if (leader) mbar_arrive(full + 8 * i);
            }
        }
    } else {
        asm volatile("setmaxnreg.inc.sync.aligned.u32 216;");
        const int wg = warp >> 2, w = warp & 3, g = lane >> 2, c = lane & 3, at = tid & 127;
        float facc[4];
        float2 a[2], m0[2], a32[2], a128[2];
        auto load_const = [&]() {
            const float2* cp = reinterpret_cast<const float2*>(smem + OFF_CONST) + wg * 64 + w * 8 + g;
#pragma unroll
            for (int h = 0; h < 2; h++) { a[h] = cp[32 * h]; m0[h] = cp[128 + 32 * h]; a32[h] = cp[256 + 32 * h]; a128[h] = cp[384 + 32 * h]; }
        };
        if (wg == 0) {
            named_bar(0, 256);
            STAMPIF(tid == 0, 20);
        } else {
            const int pc = (at >> 5) * 256 + dt * 32 + (at & 31);
            const float lr = __bfloat162float(prm.lam_re[pc]), li = __bfloat162float(prm.lam_im[pc]), ld = __bfloat162float(prm.log_dt[pc]);
            const uint32_t dk = __ldg(reinterpret_cast<const uint32_t*>(prm.dskip + dt * 128) + (at & 63));
#pragma unroll
            for (int i = 0; i < 4; i++) sts128(sb + OFF_LIST + i * 2048 + at * 16, 0u, 0u, 0u, 0u);

            {
                reinterpret_cast<uint32_t*>(smem + OFF_DK)[at & 63] = dk;
                const float dtv = rbf(expf(ld));
                const float er = expf(dtv * lr);
                float sn, cs;
                sincospif(dtv * li * 0.318309886183790672f, &sn, &cs);
                const float ar = er * cs, ai = er * sn;
                const float nr = ar - 1.0f, ni = ai;
                const bool big = fabsf(lr) >= fabsf(li);
                const float t = (big ? li : lr) / (big ? lr : li), dn = big ? lr + li * t : lr * t + li;
                const float cr = (big ? nr + ni * t : nr * t + ni) / dn, ci = (big ? ni - nr * t : ni * t - nr) / dn;
                float2* cp = reinterpret_cast<float2*>(smem + OFF_CONST) + at;
                float2 pw = make_float2(ar, prm.swapped ? ai : -ai);
                cp[0] = pw;
                cp[128] = make_float2(prm.swapped ? -2.f * cr : 2.f * cr, -2.f * ci);
#pragma unroll
                for (int i = 1; i <= 7; i++) {
                    pw = cmul(pw, pw);
                    if (i == 5) cp[256] = pw;
                    if (i == 7) cp[384] = pw;
                }
                __syncwarp();
            }
            named_bar(2, 128);
            load_const();
            mbar_wait(bar_epoch);
            const uint32_t tag = *reinterpret_cast<volatile uint32_t*>(smem + OFF_EPOCH) + 1;
            asm volatile("st.relaxed.gpu.global.b64 [%0], %1;" ::"l"(&prm.s->carry[(chunk >> 2) * 4096 + pc * 4 + (chunk & 3)]), "l"((unsigned long long)(tag + 2)) : "memory");
            if (w == 2) st_cell(lane < 4 ? (uint4*)prm.s->rpack + cta * 4 + lane : (uint4*)prm.s->gpack + cta * 4 + (lane & 3), 0, 0, 0, 0, lane < 8);
            {
                const uint32_t nt = ((tag & 1) | ((tag & 2) << 15)) ^ 0x00010001u;
                st_cell(prm.s->hid + (cta & 1) * F_ + (cta >> 1) * 64 - 512 + (at & 63), nt, nt, nt, nt, has_gu && w >= 2);
            }
            named_bar(2, 128);
            if (at < 2) mbar_arrive(bar_init3);
            unsigned long long* pub = (w ? prm.s->gpack : prm.s->rpack) + cta * 8 + lane;
            asm volatile("" : "+l"(pub));
            STAMPIF(lane == 0, 52);
            mbar_wait(bar_rdone);

            if (w < 2) {
                const float2* red = reinterpret_cast<const float2*>(smem + OFF_RED) + w * 8 + (lane & 7);
                const float2 r0 = red[0], r1 = red[16], r2 = red[32], r3 = red[48];
                const float v0 = (r0.x + r1.x) + (r2.x + r3.x), v1 = (r0.y + r1.y) + (r2.y + r3.y);
                uint32_t pk2;
                if (w == 0) {
                    pk2 = pack_bf(v0, v1);
                    pk2 ^= (((pk2 >> 15) & 0x00010001u) * 0x7FFFu) ^ 0x80008000u;
                } else pk2 = pack_bf(sigmoidf_(rbf(v0)), sigmoidf_(rbf(v1)));
                if (lane < 8) asm volatile("st.relaxed.gpu.global.b64 [%0], %1;" ::"l"(pub), "l"(((unsigned long long)tag << 32) | pk2) : "memory");
                __syncwarp();
            }
            STAMPIF(at == 0, 24);
            uint32_t it = 0, pr[8], g1;
            mbar_wait(bar_init3);
            sleep_until(clk32() + (w < 2 ? G0 : G0 + 250));
            while (true) {
                bool ok = true;
#pragma unroll
                for (int k = 0; k < 4; k++) {
                    const ulonglong2 u = ld_relaxed2(&prm.s->rpack[k * 256 + 2 * at]);
                    ok = ok && (uint32_t)(u.x >> 32) == tag && (uint32_t)(u.y >> 32) == tag;
                    pr[2 * k] = (uint32_t)u.x; pr[2 * k + 1] = (uint32_t)u.y;
                }
                const unsigned long long u1 = ld_relaxed1(&prm.s->gpack[chunk * 64 + (at & 63)]);
                ok = ok && (uint32_t)(u1 >> 32) == tag;
                g1 = (uint32_t)u1;
                if (__all_sync(0xffffffffu, ok)) break;
                if (++it > SPIN_LIMIT) __trap();
            }
            STAMPIF(lane == 0, 25);
            uint32_t m = __vmaxu2(__vimax3_u16x2(__vimax3_u16x2(pr[0], pr[1], pr[2]), pr[3], pr[4]), __vimax3_u16x2(pr[5], pr[6], pr[7]));
            m = (max(m, m << 16) & 0xFFFF0000u) | (uint32_t)lane;
            const uint32_t m1 = __reduce_max_sync(0xffffffffu, m), m2 = __reduce_max_sync(0xffffffffu, m == m1 ? 0u : m);
            uint32_t* keys = reinterpret_cast<uint32_t*>(smem + OFF_KEYS);
            if (lane == 0) keys[w] = m2;
            sts128(sb + OFF_XS + 4096 + at * 16, pr[0], pr[1], pr[2], pr[3]);
            sts128(sb + OFF_XS + 6144 + at * 16, pr[4], pr[5], pr[6], pr[7]);
            *reinterpret_cast<uint32_t*>(smem + OFF_G + 4 * (at & 63)) = g1;
            named_bar(2, 128);
            const uint4 th4 = *reinterpret_cast<const uint4*>(keys);
            const uint32_t th = (max(min(min(th4.x, th4.y), min(th4.z, th4.w)) >> 16, 1u) - 1u) * 0x00010001u;
            uint32_t mask = 0;
#pragma unroll
            for (int k = 7; k >= 0; k--) mask = mask * 2 + __vminu2(__vmaxu2(pr[k], th) ^ th, 0x00010001u);
            uint32_t pos = 0;
            asm volatile("{ .reg .pred p; setp.ne.u32 p, %2, 0; @p atom.shared.add.u32 %0, [%1], %2; }" : "+r"(pos) : "r"(sb + OFF_KEYS + 16), "r"(__popc(mask)) : "memory");
            while (mask) {
                const int bit = __ffs(mask) - 1, k = bit & 7, hi = bit >> 4;
                mask &= mask - 1;
                const uint32_t sc = *reinterpret_cast<const uint16_t*>(smem + OFF_XS + 4096 + (k >> 2) * 2048 + at * 16 + (k & 3) * 4 + hi * 2);
                *reinterpret_cast<uint32_t*>(smem + OFF_LIST + 4 * pos++) = (sc << 16) | (0x8000u + 2047u - (uint32_t)((k >> 1) * 512 + 4 * at + 2 * (k & 1) + hi));
            }
            __syncwarp();
            if (lane == 0) mbar_arrive(bar_cand);
            STAMPIF(lane == 0, 26);
            mbar_wait(bar_order0);
        }

        float accA[64], accB[64];
        Ring ring = {bar_dummy, wg};
        {
            run_entries<0, 0>(ring, wg * 16, wg ? GU0 : RE0, accA, accB, facc, true);
            if (wg == 0) {
                float racc[4];
                mbar_wait(bar_vec);
                run_entries<0, 1>(ring, RE0, RE0 + 4, accA, accB, racc, false, true);
                mbar_wait(bar_init2);
                const uint32_t red = sb + OFF_RED + 4 * (w * 32 + (c >> 1) * 16 + g);
                run_entries<0, 0>(ring, RE0 + 4, RE0 + 5, accA, accB, facc, false, false, [&]() {
                    pin4(racc);
                    asm volatile("{ .reg .pred p; setp.ne.u32 p, %3, 0; @p st.shared.f32 [%0], %1; @p st.shared.f32 [%0 + 32], %2; }" ::"r"(red),
                                 "f"((w & 1) ? racc[1] : racc[0]), "f"((w & 1) ? racc[3] : racc[2]), "r"((uint32_t)((c & 1) == (w >> 1))) : "memory");
                    __syncwarp();
                    if (lane == 0) mbar_arrive(bar_rdone);
                    STAMPIF(lane == 0, 5);
                });
                run_entries<0, 0>(ring, RE0 + 5, 16, accA, accB, facc);
                if (lane == 0) mbar_arrive(bar_order0);
                mbar_wait(bar_init3);
                load_const();
                named_bar(3, 128);
            } else {
#pragma unroll
                for (int u = 0; u < 2; u++) {
                    mbar_wait(u ? bar_xs : bar_xs0);
                    run_entries<0, 2>(ring, GU0 + 8 * u, u ? 32 : GU0 + 8, accA, accB, facc, false, u == 0);
                }
                if (lane == 0) mbar_arrive(bar_order1);
            }
        }
        const uint32_t tag = *reinterpret_cast<volatile uint32_t*>(smem + OFF_EPOCH) + 1;
        const float2 a64[2] = {cmul(a32[0], a32[0]), cmul(a32[1], a32[1])};
        wgmma_wait<0>();
        pin64(accA); pin64(accB); pin4(facc);
        if (lane == 0) mbar_arrive(ring.prev);
        STAMPIF(at == 0, 28 + wg);
        GSTAMP(tid == 0, 1);

        const int tl = 32 * (g >> 1) + (g & 1) + 4 * w + 16 * wg, t0 = chunk * 128 + tl;
        float* op = prm.out + (size_t)t0 * D_ + dt * 128 + 4 * c;
        uint2 xv[8][2], dk[8];
        uint32_t gp[2], om[2], routed[2];
        auto row_setup = [&]() {
            const uint4 sa = *reinterpret_cast<const uint4*>(smem + OFF_SEL), sc = *reinterpret_cast<const uint4*>(smem + OFF_SEL + 16);
#pragma unroll
            for (int r = 0; r < 2; r++) {
                const uint32_t id = 0x8000u + 2047u - (uint32_t)(t0 + 2 * r);
                routed[r] = (uint16_t)sa.x == id || (uint16_t)sa.y == id || (uint16_t)sa.z == id || (uint16_t)sa.w == id ||
                            (uint16_t)sc.x == id || (uint16_t)sc.y == id || (uint16_t)sc.z == id || (uint16_t)sc.w == id;
                gp[r] = reinterpret_cast<const uint16_t*>(smem + OFF_G)[tl + 2 * r] * 0x00010001u;
                om[r] = pack_bf(1.0f - bf_hi(gp[r]), 1.0f - bf_hi(gp[r]));
            }
#pragma unroll
            for (int j = 0; j < 8; j++) dk[j] = lds64(sb + OFF_DK + 32 * j + 8 * c);
        };
        auto release = [&](uint32_t bar) {
            asm volatile("fence.proxy.async.shared::cta;" ::: "memory");
            __syncwarp();
            if (lane == 0) mbar_arrive(bar);
        };

        {
            const uint32_t t2 = tag & 3u;
            float2* cslot = &prm.s->carry[(wg * 512 + dt * 32 + w * 8 + g) * 4];
            const int j1 = chunk - 1 - c;
            unsigned long long v[2][4] = {{t2, t2, t2, t2}, {t2, t2, t2, t2}};
            auto poll = [&](int h) {
#pragma unroll
                for (int m = 0; m < 4; m++)
                    asm volatile("{ .reg .pred p; setp.ge.s32 p, %2, %3; @p ld.relaxed.gpu.global.b64 %0, [%1]; }"
                                 : "+l"(v[h][m]) : "l"(cslot + (j1 >> 2) * 4096 + c - m * 4096 + h * 1024), "r"(j1), "r"(4 * m) : "memory");
            };
            float2 e[2], w0[2];
            auto chain = [&](int h, int s0, int s1) {
                float (&acc)[64] = h ? accB : accA;
                if (s0 == 1) e[h] = make_float2(acc[0], acc[2]);
#pragma unroll
                for (int s = s0; s < s1; s++) {
                    const int i0 = 4 * (s >> 1) + (s & 1);
                    e[h] = cfma(make_float2(a[h].x, -a[h].y), e[h], make_float2(acc[i0], acc[i0 + 2]));
                }
                asm volatile("" : "+f"(e[h].x), "+f"(e[h].y), "+f"(accB[0]), "+f"(accB[2]));
                gap();
            };
            auto publish = [&](int h) {
                float2 f = make_float2(fmaf(m0[h].x, e[h].x, m0[h].y * e[h].y), fmaf(-m0[h].x, e[h].y, m0[h].y * e[h].x));
                float2 y = make_float2(__shfl_up_sync(0xffffffffu, f.x, 1, 4), __shfl_up_sync(0xffffffffu, f.y, 1, 4));
                if (c >= 1) f = cfma(a32[h], y, f);
                y = make_float2(__shfl_up_sync(0xffffffffu, f.x, 2, 4), __shfl_up_sync(0xffffffffu, f.y, 2, 4));
                if (c >= 2) f = cfma(a64[h], y, f);
                asm volatile("{ .reg .pred p; .reg .b64 t; setp.eq.u32 p, %3, 3; mov.b64 t, {%1, %2}; @p st.relaxed.gpu.global.b64 [%0], t; }"
                             ::"l"(cslot + (chunk >> 2) * 4096 + (chunk & 3) + h * 1024), "r"((__float_as_uint(f.x) & ~3u) | t2), "r"(__float_as_uint(f.y)), "r"(c) : "memory");
                w0[h] = make_float2(__shfl_up_sync(0xffffffffu, f.x, 1, 4), __shfl_up_sync(0xffffffffu, f.y, 1, 4));
                if (c == 0) w0[h] = make_float2(0.f, 0.f);
            };
            auto scale = [&](int h, int n0, int n1) {
                float (&acc)[64] = h ? accB : accA;
#pragma unroll
                for (int n = n0; n < n1; n++) {
                    asm volatile("{ .reg .f32 a, b, c, d, n; neg.f32 n, %4; mul.f32 a, %1, %5; mul.f32 b, %0, %5; mul.f32 c, %3, %5; mul.f32 d, %2, %5;\n"
                                 "fma.rn.f32 %0, %0, %4, a; fma.rn.f32 %1, %1, n, b; fma.rn.f32 %2, %2, %4, c; fma.rn.f32 %3, %3, n, d; }"
                                 : "+f"(acc[4 * n]), "+f"(acc[4 * n + 2]), "+f"(acc[4 * n + 1]), "+f"(acc[4 * n + 3]) : "f"(m0[h].x), "f"(m0[h].y));
                    gap();
                }
            };
            auto carry = [&](int h) {
                const float2 one = make_float2(1.f, 0.f), a256 = cmul(a128[h], a128[h]);
                float2 a512 = cmul(a256, a256), pw128 = cmul((j1 & 1) ? a128[h] : one, (j1 & 2) ? a256 : one);
                float2 pw32 = cmul((c & 1) ? a32[h] : one, (c & 2) ? a64[h] : one);
                asm volatile("" : "+f"(a512.x), "+f"(a512.y), "+f"(pw128.x), "+f"(pw128.y), "+f"(pw32.x), "+f"(pw32.y));
                STAMPIF(lane == 0 && !h, 34 + 2 * wg);
                uint32_t it = 0;
                while (!__all_sync(0xffffffffu, ((((uint32_t)v[h][0] ^ t2) | ((uint32_t)v[h][1] ^ t2) | ((uint32_t)v[h][2] ^ t2) | ((uint32_t)v[h][3] ^ t2)) & 3u) == 0)) {
                    poll(h);
                    if (++it > SPIN_LIMIT) __trap();
                }
                STAMPIF(lane == 0 && !h, 35 + 2 * wg);
                float2 hin = make_float2(__uint_as_float((uint32_t)v[h][3]), __uint_as_float((uint32_t)(v[h][3] >> 32)));
#pragma unroll
                for (int m = 2; m >= 0; m--) hin = cfma(a512, hin, make_float2(__uint_as_float((uint32_t)v[h][m]), __uint_as_float((uint32_t)(v[h][m] >> 32))));
                hin = cmul(pw128, hin);
                hin.x += __shfl_xor_sync(0xffffffffu, hin.x, 1); hin.y += __shfl_xor_sync(0xffffffffu, hin.y, 1);
                hin.x += __shfl_xor_sync(0xffffffffu, hin.x, 2); hin.y += __shfl_xor_sync(0xffffffffu, hin.y, 2);
                w0[h] = cfma(pw32, hin, w0[h]);
            };
            chain(0, 1, 32);
            publish(0);
            chain(1, 1, 8);
            STAMPIF(lane == 0, 30 + 2 * wg);
            chain(1, 8, 32);
            publish(1);
            gap();
            scale(0, 0, POLL_S);
            poll(0);
            scale(0, POLL_S, 16);
            carry(0);
            if (wg) mbar_wait(bar_out + 24);
            STAMPIF(lane == 0, 38 + 2 * wg);
            const uint32_t stg = sb + OFF_STG + prm.swapped * 8192 + w * 1024 + (lane & 7) * 128 + (((lane >> 3) ^ (lane & 7)) << 4);
            const uint32_t second = prm.swapped ? -8192 : 8192;
            uint32_t hold = prm.swapped >> 1, last[8];
            const uint32_t keep = c == (g >> 1) ? 0xFFFEFFFEu : 0xFFFFFFFFu, tagw = ((t2 & 1) | ((t2 & 2) << 15)) & ~keep;
#pragma unroll
            for (int h = 0; h < 2; h++) {
                float (&acc)[64] = h ? accB : accA;
                uint32_t ra[16], ia[16];
                if (h) {
                    scale(1, 0, 4);
#pragma unroll
                    for (int u = 0; u < 4; u++) asm volatile("lop3.b32 %0, %0, %1, %2, 0x80;" : "+r"(hold) : "r"(last[u]), "r"(last[4 + u]));
                    release(bar_st + 32 * wg + 8 + hold);
                    poll(1);
                    scale(1, 4, 16);
                    mbar_wait(bar_xs);
                    row_setup();
                    carry(1);
                }
                auto stage = [&](uint32_t (&r)[16], uint32_t base, int j) {
                    stsm4((base ^ ((j & 1) * 64)) + (j >> 1) * 4096, r[4 * j], r[4 * j + 1], r[4 * j + 2], r[4 * j + 3]);
                };
#pragma unroll
                for (int n = 0; n < 16; n++) {
                    const float2 y = cfma(a[h], w0[h], make_float2(acc[4 * n], acc[4 * n + 2]));
                    w0[h] = cfma(a[h], y, make_float2(acc[4 * n + 1], acc[4 * n + 3]));
                    ra[n] = pack_bf(y.x, w0[h].x);
                    ia[n] = pack_bf(y.y, w0[h].y);
                    if (!(n & 1)) { ra[n] = (ra[n] & keep) | tagw; ia[n] = (ia[n] & keep) | tagw; }
                    if (!h && (n & 3) == 3) {
                        if (n > 3) {
                            gap();
#pragma unroll
                            for (int u = n - 7; u < n - 3; u++) asm volatile("lop3.b32 %0, %0, %1, %2, 0x80;" : "+r"(hold) : "r"(ra[u]), "r"(ia[u]));
                        }
                        if (n == 15) {
#pragma unroll
                            for (int u = 0; u < 4; u++) { last[u] = ra[12 + u]; last[4 + u] = ia[12 + u]; }
                        }
                        if (n == 11) { asm volatile("" : "+r"(ra[n]), "+r"(ia[n])); gap(); release(bar_st + 32 * wg); }
                        stage(ra, stg, n >> 2); stage(ia, stg + second, n >> 2);
                        gap();
                    }
                }
                if (h) {
                    STAMPIF(lane == 0, 39 + 2 * wg);
                    mbar_wait(bar_out + 32 * wg);
                    if (prm.swapped) {
#pragma unroll
                        for (int n = 0; n < 16; n++) { const uint32_t t = ra[n]; ra[n] = ia[n]; ia[n] = t; }
                    }
                    const uint32_t st0 = stg - prm.swapped * 8192;
#pragma unroll
                    for (int j = 0; j < 4; j++) stage(ra, st0, j);
                    release(bar_st + 32 * wg + 16);
                    mbar_wait(bar_out + 32 * wg + 8);
#pragma unroll
                    for (int j = 0; j < 4; j++) stage(ia, st0 + 8192, j);
                    release(bar_st + 32 * wg + 24);
                }
                STAMPIF(lane == 0, 42 + 2 * wg + h);
            }
        }

        const uint32_t xr = 2 * (g & 3) + (g >> 2), xa = sb + (wg ? OFF_STG : OFF_W) + (16 * w + xr) * 128 + (((c >> 1) ^ xr) << 4) + (c & 1) * 8;
        auto handover = [&](uint32_t bar) {
            const uint4 z = ldsm4(sb + OFF_KEYS + 16);
            if (lane == 1) mbar_arrive(bar + z.x);
        };
        auto load_x = [&](int j0, int j1) {
#pragma unroll
            for (int j = j0; j < j1; j++)
#pragma unroll
                for (int r = 0; r < 2; r++) xv[j][r] = lds64((xa ^ (32 * (j & 3))) + (j >> 2) * ABYTES + r * 1024);
        };
        auto skip_term = [&](int j0, int j1) {
#pragma unroll
            for (int j = j0; j < j1; j++)
#pragma unroll
                for (int r = 0; r < 2; r++) {
                    xv[j][r].x = mul_bf2(xv[j][r].x, fma_bf2(gp[r], dk[j].x, om[r]));
                    xv[j][r].y = mul_bf2(xv[j][r].y, fma_bf2(gp[r], dk[j].y, om[r]));
                    asm volatile("" : "+r"(xv[j][r].x), "+r"(xv[j][r].y));
                }
        };
        auto finish = [&](float (&acc)[64], int j, bool gaps) {
#pragma unroll
            for (int r = 0; r < 2; r++) {
                const int o = 8 * j + 2 * r;
                const float gv = bf_hi(gp[r]);
                acc[o] = fmaf(gv, acc[o], bf_lo(xv[j][r].x)); acc[o + 1] = fmaf(gv, acc[o + 1], bf_hi(xv[j][r].x));
                acc[o + 4] = fmaf(gv, acc[o + 4], bf_lo(xv[j][r].y)); acc[o + 5] = fmaf(gv, acc[o + 5], bf_hi(xv[j][r].y));
                stg4_unless(op + r * 2 * D_ + 16 * j, acc[o], acc[o + 1], acc[o + 4], acc[o + 5], routed[r]);
                if (gaps) gap();
            }
        };
        auto finish_routed = [&](float (&acc)[64]) {
#pragma unroll
            for (int r = 0; r < 2; r++)
                if (routed[r]) {
#pragma unroll
                    for (int j = 0; j < 8; j++) red4(op + r * 2 * D_ + 16 * j, acc[8 * j + 2 * r], acc[8 * j + 2 * r + 1], acc[8 * j + 2 * r + 4], acc[8 * j + 2 * r + 5]);
                }
            __syncwarp();
        };
        const uint32_t xbuf = sb + slot_off(FIN) + w * 2048 + lane * 16;

        if (wg == 1) {
            float outB[64];
            const uint32_t tagw = (tag & 1) | ((tag & 2) << 15);
            mbar_wait(bar_fp);
            {
                const float4 o4 = lds128f(sb + OFF_XS + at * 16);
                const float o[4] = {o4.x, o4.y, o4.z, o4.w};
                float v[4];
#pragma unroll
                for (int u = 0; u < 4; u++) {
                    v[u] = rbf(facc[u] + o[u]);
                    if (!(cta & 1)) v[u] = __fdividef(v[u], 1.0f + __expf(-v[u]));
                }
                uint32_t w0 = pack_bf(v[0], v[1]), w1 = pack_bf(v[2], v[3]), cell[4];
                if (c == (g & 3)) { w0 = (w0 & 0xFFFEFFFEu) | tagw; w1 = (w1 & 0xFFFEFFFEu) | tagw; }
#pragma unroll
                for (int u = 0; u < 4; u++) {
                    const uint32_t s0 = __shfl_sync(0xffffffffu, w0, u, 4), s1 = __shfl_sync(0xffffffffu, w1, u, 4);
                    cell[u] = (c & 1) ? s1 : s0;
                }
                st_cell(prm.s->hid + (cta & 1) * F_ + (cta >> 1) * 64 - 512 + w * 16 + g + 8 * c, cell[0], cell[1], cell[2], cell[3], has_gu && c < 2);
            }
            release(bar_hpub);
            STAMPIF(lane == 0, 47);
            mbar_wait(bar_xb);
            load_x(0, 8);
            release(bar_xbfree);
            skip_term(0, 8);
            STAMPIF(lane == 0, 46);
            {
                uint4 hv[4], hu[4];
                const uint32_t ha = sb + OFF_XS + at * 16, hl = sb + OFF_XS + 6144 + (at & 63) * 16;
#pragma unroll 1
                for (uint32_t it = 0;; it++) {
                    mbar_wait(bar_hraw, it & 1);
                    uint32_t bad = 0;
#pragma unroll
                    for (int i = 0; i < 4; i++) {
                        hv[i] = lds128(i < 3 ? ha + i * 2048 : hl); hu[i] = lds128((i < 3 ? ha + i * 2048 : hl) + ABYTES);
                        bad |= (((c & 2) ? ((c & 1) ? hv[i].w : hv[i].z) : ((c & 1) ? hv[i].y : hv[i].x)) ^ tagw) |
                               (((c & 2) ? ((c & 1) ? hu[i].w : hu[i].z) : ((c & 1) ? hu[i].y : hu[i].x)) ^ tagw);
                    }
                    uint32_t again;
                    asm volatile("{ .reg .pred p, q; setp.ne.u32 q, %1, 0; barrier.red.or.pred.aligned p, 2, 128, q; selp.u32 %0, 1, 0, p; }" : "=r"(again) : "r"(bad & 0x00010001u) : "memory");
                    if (!uni(again)) break;
                    if (it > SPIN_LIMIT) __trap();
                    if (w == 0) load_hid();
                }
                STAMPIF(lane == 0, 48);
#pragma unroll
                for (int i = 0; i < 4; i++)
                    sts128(i < 3 ? ha + i * 2048 : hl, mul_bf2(hv[i].x, hu[i].x), mul_bf2(hv[i].y, hu[i].y), mul_bf2(hv[i].z, hu[i].z), mul_bf2(hv[i].w, hu[i].w));
                asm volatile("fence.proxy.async.shared::cta;" ::: "memory");
                __syncwarp();
                if (lane == 0) mbar_arrive(bar_hs);
                STAMPIF(lane == 0, 49);
            }
            mbar_wait(bar_order2);
            static_for<NENT - FIN>([&](auto u) {
                run_small<1, FIN + u>(outB);
                if (u == 2) { wgmma_wait<2>(); if (lane == 0) mbar_arrive(bar_fold); }
            });
            if (lane == 0) mbar_expect_tx(bar_dn, w ? 0 : 7 * ABYTES);
            wgmma_wait<0>();
            pin64(outB);
            KSTAMP(2 * NENT - FIN);
            STAMPIF(at == 0, 50);
#pragma unroll
            for (int q = 0; q < 2; q++) {
                uint4 pb[16];
                mbar_wait(bar_accb + 8 * q);
#pragma unroll
                for (int v = q * HP; v < (q ? 16 : HP); v++) pb[v] = ldsm4(xbuf + (v >> 2) * ABYTES + (v & 3) * 512);
#pragma unroll
                for (int v = q * HP; v < (q ? 16 : HP); v++) {
                    outB[4 * v] += __uint_as_float(pb[v].x); outB[4 * v + 1] += __uint_as_float(pb[v].y);
                    outB[4 * v + 2] += __uint_as_float(pb[v].z); outB[4 * v + 3] += __uint_as_float(pb[v].w);
                    if (v & 1) finish(outB, v >> 1, false);
                }
            }
            finish_routed(outB);
            STAMPIF(lane == 0, 51);
        } else {
            float outA[64], outB[64], gacc[4];
            ring.slot = 32 % NST;
            ring.prev = bar_dummy;
            mbar_wait(bar_order1);
            run_entries<1, 2>(ring, 32, GU0 + 32, outA, outB, gacc, true, true);
            run_entries<1, 0>(ring, GU0 + 32, GU0 + 33, outA, outB, gacc, false, false, [&]() {
                pin4(gacc);
                sts128(sb + OFF_XS + at * 16, __float_as_uint(gacc[0]), __float_as_uint(gacc[1]), __float_as_uint(gacc[2]), __float_as_uint(gacc[3]));
                __syncwarp();
                if (lane == 0) mbar_arrive(bar_fp);
            });
            mbar_wait(bar_xa);
            run_entries<1, 0>(ring, GU0 + 33, GU0 + 34, outA, outB, gacc, false, false, [&]() { load_x(0, 2); });
            load_x(2, 4);
            run_entries<1, 0>(ring, GU0 + 34, GU0 + 35, outA, outB, gacc, false, false, [&]() { load_x(4, 6); });
            load_x(6, 8);
            run_entries<1, 0>(ring, GU0 + 35, GU0 + 36, outA, outB, gacc, false, false, [&]() { release(bar_xafree); });
            run_entries<1, 0>(ring, GU0 + 36, FIN, outA, outB, gacc);
            static_for<NENT - FIN>([&](auto u) {
                mbar_wait(full + 8 * (FIN + u));
                run_small<0, FIN + u>(outA);
                if (u == 5 && lane == 0) mbar_arrive(bar_order2);
                wgmma_wait<1>();
                if (lane == 0) mbar_arrive(empty + 8 * (FIN + u - 1));
                if (u < 4) skip_term(2 * u, 2 * u + 2);
            });
            const uint2 sk = lds64(sb + OFF_SEL + 8 * c), fk = lds64(sb + OFF_FAC + 8 * c);
            float* y0 = prm.out + (~sk.x & 2047u) * D_ + (cta & 15) * 64 + w * 16 + g;
            float* y1 = prm.out + (~sk.y & 2047u) * D_ + (cta & 15) * 64 + w * 16 + g;
            asm volatile("" : "+l"(y0), "+l"(y1));
            mbar_wait(bar_zero);
            mbar_wait(empty + 8 * FIN);
            wgmma_wait<0>();
            pin64(outA); pin64(outB);
            STAMPIF(at == 0, 53);
            GSTAMP(at == 0, 2);
            auto dump = [&](int v) {
                if (v == 4) mbar_wait(bar_fold);
                stsm4(xbuf + (v >> 2) * ABYTES + (v & 3) * 512, __float_as_uint(outB[4 * v]), __float_as_uint(outB[4 * v + 1]), __float_as_uint(outB[4 * v + 2]),
                      __float_as_uint(outB[4 * v + 3]));
                if (v == HP - 1 || v == 15) handover(bar_accb + 8 * (v == 15));
            };
#pragma unroll
            for (int j = 0; j < 8; j++) {
                finish(outA, j, true);
#pragma unroll
                for (int v = j * NDUMP / 8; v < (j + 1) * NDUMP / 8; v++) dump(v);
            }
            STAMPIF(lane == 0, 54);
#pragma unroll
            for (int v = NDUMP; v < 16; v++) dump(v);
            STAMPIF(lane == 0, 55);
            float yacc[4];
            const uint64_t dw = make_desc(sb), dh = (uint64_t)(((sb + OFF_XS) & 0x3FFFF) >> 4) | ((uint64_t)8 << 16) | ((uint64_t)8 << 32);
            mbar_wait(bar_dn);
            STAMPIF(at == 0, 2);
            wgmma_fence();
#pragma unroll
            for (int n = 0; n < 28; n++) wgmma_n8<1, 1>(yacc, dw + (dn_off(n >> 2) >> 4) + (n & 3) * 128, dh + n * 16, n > 0);
            wgmma_commit();
            finish_routed(outA);
            wgmma_wait<0>();
            pin4(yacc);
            atomicAdd(y0, yacc[0] * __uint_as_float(fk.x)); atomicAdd(y1, yacc[1] * __uint_as_float(fk.y));
            atomicAdd(y0 + 8, yacc[2] * __uint_as_float(fk.x)); atomicAdd(y1 + 8, yacc[3] * __uint_as_float(fk.y));
            STAMPIF(lane == 0, 3);
        }
    }
}

typedef CUresult (*EncodeFn)(CUtensorMap*, CUtensorMapDataType, cuuint32_t, void*, const cuuint64_t*, const cuuint64_t*, const cuuint32_t*,
                             const cuuint32_t*, CUtensorMapInterleave, CUtensorMapSwizzle, CUtensorMapL2promotion, CUtensorMapFloatOOBfill);

bool encode(EncodeFn fn, CUtensorMap* m, const void* ptr, int rank, const cuuint64_t* dims, const cuuint64_t* strides, const cuuint32_t* box,
            CUtensorMapSwizzle sw = CU_TENSOR_MAP_SWIZZLE_128B, CUtensorMapL2promotion promo = CU_TENSOR_MAP_L2_PROMOTION_NONE) {
    const cuuint32_t es[5] = {1, 1, 1, 1, 1};
    return fn(m, CU_TENSOR_MAP_DATA_TYPE_BFLOAT16, rank, const_cast<void*>(ptr), dims, strides, box, es, CU_TENSOR_MAP_INTERLEAVE_NONE,
              sw, promo, CU_TENSOR_MAP_FLOAT_OOB_FILL_NONE) == CUDA_SUCCESS;
}

}

extern "C" void kernel_launch(void* const* d_in, const int* in_sizes, int n_in, void* d_out, int out_size) {
    (void)in_sizes; (void)n_in; (void)out_size;
    Params prm;
    prm.x = (const __nv_bfloat16*)d_in[0];
    prm.lam_re = (const __nv_bfloat16*)d_in[1];
    prm.lam_im = (const __nv_bfloat16*)d_in[2];
    prm.b_re = (const __nv_bfloat16*)d_in[3];
    prm.b_im = (const __nv_bfloat16*)d_in[4];
    prm.c_re = (const __nv_bfloat16*)d_in[5];
    prm.c_im = (const __nv_bfloat16*)d_in[6];
    prm.log_dt = (const __nv_bfloat16*)d_in[7];
    prm.dskip = (const __nv_bfloat16*)d_in[8];
    prm.w_r = (const __nv_bfloat16*)d_in[10];
    prm.gate_w = (const __nv_bfloat16*)d_in[14];
    prm.out = (float*)d_out;
    cudaGetSymbolAddress((void**)&prm.s, g_scratch);
    int dev = 0, sms = 0;
    cudaGetDevice(&dev);
    cudaDeviceGetAttribute(&sms, cudaDevAttrMultiProcessorCount, dev);
    prm.by_smid = sms == NGRID;
    prm.swapped = prm.b_im < prm.b_re;

    void* fnp = nullptr;
    cudaDriverEntryPointQueryResult qr;
    cudaGetDriverEntryPoint("cuTensorMapEncodeTiled", &fnp, cudaEnableDefault, &qr);
    EncodeFn fn = (EncodeFn)fnp;
    cudaFuncSetAttribute(fused_kernel, cudaFuncAttributeMaxDynamicSharedMemorySize, SMEM_BYTES);

    CUtensorMap mX, mB, mCre, mCim, mWg, mWu, mWd, mXr, mXe;
    const cuuint64_t row = 2048;
    {
        const cuuint64_t dims[4] = {1024, 2, 4, 976}, st[3] = {row, 32 * row, 2 * row};
        const cuuint32_t box[4] = {64, 2, 4, 16};
        encode(fn, &mX, prm.x, 4, dims, st, box, CU_TENSOR_MAP_SWIZZLE_128B, PROMO);
    }
    {
        const char *lo = (const char*)(prm.swapped ? prm.b_im : prm.b_re), *hi = (const char*)(prm.swapped ? prm.b_re : prm.b_im);
        const cuuint64_t dims[5] = {1024, 8, 2, 96, 2}, st[4] = {row, (cuuint64_t)(hi - lo), 8 * row, 256 * row};
        const cuuint32_t box[5] = {64, 8, 2, 4, 2};
        encode(fn, &mB, lo, 5, dims, st, box, CU_TENSOR_MAP_SWIZZLE_128B, PROMO);
    }
    {
        const cuuint64_t dims[5] = {1024, 2, 4, 2, 64}, st[4] = {row, 4 * row, 2 * row, 16 * row};
        const cuuint32_t box[5] = {64, 2, 4, 2, 8};
        encode(fn, &mCre, prm.c_re, 5, dims, st, box);
        encode(fn, &mCim, prm.c_im, 5, dims, st, box);
    }
    {
        const cuuint64_t dims[2] = {F_, D_}, st[1] = {F_ * 2}, dimsd[2] = {D_, F_}, std_[1] = {row};
        const cuuint32_t box[2] = {64, 32}, boxd[2] = {64, 64};
        encode(fn, &mWg, d_in[11], 2, dims, st, box, CU_TENSOR_MAP_SWIZZLE_128B, CU_TENSOR_MAP_L2_PROMOTION_NONE);
        encode(fn, &mWu, d_in[12], 2, dims, st, box, CU_TENSOR_MAP_SWIZZLE_128B, CU_TENSOR_MAP_L2_PROMOTION_NONE);
        encode(fn, &mWd, d_in[13], 2, dimsd, std_, boxd, CU_TENSOR_MAP_SWIZZLE_128B, CU_TENSOR_MAP_L2_PROMOTION_NONE);
    }
    {
        const cuuint64_t dims[3] = {D_ - 192, S_, 4}, st[2] = {row, 128};
        const cuuint32_t box[3] = {64, 16, 4};
        encode(fn, &mXr, prm.x, 3, dims, st, box, CU_TENSOR_MAP_SWIZZLE_128B, CU_TENSOR_MAP_L2_PROMOTION_NONE);
    }
    {
        const cuuint64_t dims[5] = {D_, 2, 2, 2, 976}, st[4] = {64 * row, row, 32 * row, 2 * row};
        const cuuint32_t box[5] = {64, 2, 2, 2, 8};
        encode(fn, &mXe, prm.x, 5, dims, st, box);
    }
    fused_kernel<<<NGRID, 384, SMEM_BYTES, cudaStreamPerThread>>>(prm, mX, mB, mCre, mCim, mWg, mWu, mWd, mXr, mXe);
}
```

```cpp
#include <cuda_runtime.h>
#include <cuda_bf16.h>
#include <cuda.h>
#include <stdint.h>

namespace {

constexpr int S_ = 2048, D_ = 1024, F_ = 3584;
constexpr int NCTA = 128, NGRID = 132;
#define XE_ 58
#define GU0_ 18
constexpr int NENT = 64, FIN = 58, XE = XE_;
constexpr int NST = 5;
constexpr int RE0 = 4;
constexpr int GU0 = GU0_;
constexpr uint32_t SLOT = 32768, ABYTES = 8192, WBYTES = 4096;
constexpr uint32_t OFF_XS = NST * SLOT;
constexpr uint32_t OFF_LIST = OFF_XS + 8192;
constexpr uint32_t OFF_W = OFF_XS + 16384;
constexpr uint32_t OFF_STG = OFF_W + 32768;
__host__ __device__ constexpr uint32_t slot_off(int i) { return i < XE ? (i % NST) * SLOT : i == XE ? OFF_W : ((i - 1) % NST) * SLOT; }
__host__ __device__ constexpr uint32_t dn_off(int u) { return u == 0 ? OFF_XS + ABYTES : u < 3 ? OFF_STG + (u - 1) * ABYTES : slot_off(FIN - 2 + u); }
constexpr uint32_t OFF_CONST = OFF_STG;
constexpr uint32_t OFF_RED = OFF_STG + 4096;
constexpr uint32_t OFF_FULL = OFF_STG + 16384;
constexpr uint32_t OFF_EMPTY = OFF_FULL + 120 * 8;
constexpr uint32_t OFF_G = OFF_EMPTY + 88 * 8;
constexpr uint32_t OFF_DK = OFF_G + 256;
constexpr uint32_t OFF_KEYS = OFF_DK + 256;
constexpr uint32_t OFF_SEL = OFF_KEYS + 32;
constexpr uint32_t OFF_FAC = OFF_SEL + 32;
constexpr uint32_t OFF_EPOCH = OFF_FAC + 32;
constexpr uint32_t OFF_PROF = OFF_EPOCH + 16;
constexpr uint32_t SMEM_BYTES = OFF_PROF + 768;
static_assert(SMEM_BYTES <= 232448, "smem");

constexpr uint32_t sb = 1024;
constexpr uint32_t SPIN_LIMIT = 1u << 18;

struct Scratch {
    unsigned int cnt[2 * 32];
    unsigned long long rpack[S_ / 2];
    unsigned long long gpack[S_ / 2];
    uint4 time[NCTA];
    float2 carry[16 * 1024];
    uint4 hid[F_];
    uint4 h[8 * 4 * 256 * 64];
};
__device__ __align__(128) Scratch g_scratch;
#define STAMPW(cond, w) do {} while (0)
#define LATE(i, tt) do {} while (0)
#define LANDED(i) do {} while (0)
#define GSTAMP(cond, w) do {} while (0)
#define STAMPIF(cond, i) STAMPW(cond, 72 + (i))
#define STAMP(i) STAMPW(1, 72 + (i))
#define KSTAMP(i) STAMPW((threadIdx.x & 127) == 0, i)

struct Params {
    const __nv_bfloat16 *x, *b_re, *b_im;
    int by_smid;
    int up_first;
    int swapped;
    const __nv_bfloat16 *lam_re, *lam_im, *c_re, *c_im, *log_dt, *dskip, *w_r, *gate_w;
    float* out;
    Scratch* s;
};

__device__ __forceinline__ uint32_t smem_u32(const void* p) { return (uint32_t)__cvta_generic_to_shared(p); }
__device__ __forceinline__ void mbar_init(uint32_t bar, uint32_t cnt) { asm volatile("mbarrier.init.shared::cta.b64 [%0], %1;" ::"r"(bar), "r"(cnt) : "memory"); }
__device__ __forceinline__ void mbar_expect_tx(uint32_t bar, uint32_t bytes) { asm volatile("mbarrier.arrive.expect_tx.shared::cta.b64 _, [%0], %1;" ::"r"(bar), "r"(bytes) : "memory"); }
__device__ __forceinline__ void mbar_arrive(uint32_t bar) { asm volatile("mbarrier.arrive.shared::cta.b64 _, [%0];" ::"r"(bar) : "memory"); }
__device__ __forceinline__ void mbar_wait(uint32_t bar, uint32_t parity = 0) {
    asm volatile("{ .reg .pred p; .reg .u32 n;\n"
                 "mbarrier.try_wait.parity.shared::cta.b64 p, [%0], %1;\n"
                 "@p bra.uni DONE;\n"
                 "mov.u32 n, 0;\n"
                 "AGAIN: mbarrier.try_wait.parity.shared::cta.b64 p, [%0], %1;\n"
                 "@p bra.uni DONE;\n"
                 "add.u32 n, n, 1;\n"
                 "setp.lt.u32 p, n, %2;\n"
                 "@p bra.uni AGAIN;\n"
                 "trap;\n"
                 "DONE: }" ::"r"(bar), "r"(parity), "n"(SPIN_LIMIT) : "memory");
}
__device__ __forceinline__ bool elect_one() {
    uint32_t pred;
    asm volatile("{ .reg .pred P; elect.sync _|P, 0xffffffff; selp.b32 %0, 1, 0, P; }" : "=r"(pred));
    return pred;
}
__device__ __forceinline__ void named_bar(int id, int n) { asm volatile("bar.sync %0, %1;" ::"r"(id), "r"(n) : "memory"); }

#define ONE "{ .reg .pred e; elect.sync _|e, 0xffffffff;\n@e "
template <int N> __device__ __forceinline__ void mbar_init_n(uint32_t bar, uint32_t cnt, uint32_t extra = 0) {
    if (elect_one()) {
#pragma unroll
        for (int i = 0; i < N; i++) mbar_init(bar + 8 * i, i == N - 1 ? cnt + extra : cnt);
        asm volatile("fence.mbarrier_init.release.cluster;" ::: "memory");
    }
    __syncwarp();
}
__device__ __forceinline__ void bulk_load(uint32_t dst, const void* src, uint32_t bytes, uint32_t bar) {
    asm volatile(ONE "cp.async.bulk.shared::cluster.global.mbarrier::complete_tx::bytes [%0], [%1], %2, [%3]; }" ::"r"(dst), "l"(src), "r"(bytes), "r"(bar) : "memory");
}
__device__ __forceinline__ void sts128(uint32_t a, uint32_t x, uint32_t y, uint32_t z, uint32_t w) {
    asm volatile("st.shared.v4.u32 [%0], {%1,%2,%3,%4};" ::"r"(a), "r"(x), "r"(y), "r"(z), "r"(w) : "memory");
}
__device__ __forceinline__ uint2 lds64(uint32_t a) {
    uint2 v;
    asm volatile("ld.shared.v2.u32 {%0,%1}, [%2];" : "=r"(v.x), "=r"(v.y) : "r"(a) : "memory");
    return v;
}
__device__ __forceinline__ uint32_t clk32() { uint32_t c; asm volatile("mov.u32 %0, %%clock;" : "=r"(c)); return c; }
__device__ __forceinline__ void gap() { asm volatile("pmevent 1;" ::: "memory"); }
__device__ __forceinline__ void pace_until(uint32_t t) { while ((int)(clk32() - t) < 0) {} }
#define SLEEP_MARGIN 200
__device__ __forceinline__ void sleep_until(uint32_t t) {
    while ((int)(clk32() + SLEEP_MARGIN - t) < 0) __nanosleep(40);
    pace_until(t);
}
__device__ __forceinline__ void tma2(uint32_t dst, const CUtensorMap* m, int c0, int c1, uint32_t bar, uint64_t pol) {
    asm volatile(ONE "cp.async.bulk.tensor.2d.shared::cluster.global.mbarrier::complete_tx::bytes.L2::cache_hint [%0], [%1, {%3, %4}], [%2], %5; }"
                 ::"r"(dst), "l"(m), "r"(bar), "r"(c0), "r"(c1), "l"(pol) : "memory");
}
__device__ __forceinline__ void tma3s(uint32_t dst, const CUtensorMap* m, int c0, int c1, uint32_t bar, uint64_t pol) {
    asm volatile(ONE "cp.async.bulk.tensor.3d.shared::cluster.global.mbarrier::complete_tx::bytes.L2::cache_hint [%0], [%1, {%3, %4, %5}], [%2], %6; }"
                 ::"r"(dst), "l"(m), "r"(bar), "r"(c0), "r"(c1), "r"(0), "l"(pol) : "memory");
}
__device__ __forceinline__ void tma3(uint32_t dst, const CUtensorMap* m, int c0, int c1, uint32_t bar) {
    asm volatile(ONE "cp.async.bulk.tensor.3d.shared::cluster.global.mbarrier::complete_tx::bytes [%0], [%1, {%3, %4, %5}], [%2]; }"
                 ::"r"(dst), "l"(m), "r"(bar), "r"(c0), "r"(c1), "r"(0) : "memory");
}
__device__ __forceinline__ void tma4(uint32_t dst, const CUtensorMap* m, int c0, int c3, uint32_t bar) {
    asm volatile(ONE "cp.async.bulk.tensor.4d.shared::cluster.global.mbarrier::complete_tx::bytes [%0], [%1, {%3, %5, %5, %4}], [%2]; }"
                 ::"r"(dst), "l"(m), "r"(bar), "r"(c0), "r"(c3), "r"(0) : "memory");
}
__device__ __forceinline__ void tma5(uint32_t dst, const CUtensorMap* m, int c0, int c4, uint32_t bar) {
    asm volatile(ONE "cp.async.bulk.tensor.5d.shared::cluster.global.mbarrier::complete_tx::bytes [%0], [%1, {%3, %5, %5, %5, %4}], [%2]; }"
                 ::"r"(dst), "l"(m), "r"(bar), "r"(c0), "r"(c4), "r"(0) : "memory");
}
__device__ __forceinline__ void tma5b(uint32_t dst, const CUtensorMap* m, int c0, int c3, uint32_t bar) {
    asm volatile(ONE "cp.async.bulk.tensor.5d.shared::cluster.global.mbarrier::complete_tx::bytes [%0], [%1, {%3, %5, %5, %4, %5}], [%2]; }"
                 ::"r"(dst), "l"(m), "r"(bar), "r"(c0), "r"(c3), "r"(0) : "memory");
}
__device__ __forceinline__ void prefetch_l2(const void* p) {
    asm volatile("cp.async.ca.shared.global.L2::256B [%0], [%1], 4;" ::"r"(sb + OFF_EPOCH + 12), "l"(p) : "memory");
}

__device__ __forceinline__ uint32_t lds32(uint32_t a) {
    uint32_t v;
    asm volatile("ld.volatile.shared.u32 %0, [%1];" : "=r"(v) : "r"(a) : "memory");
    return v;
}
__device__ __forceinline__ uint32_t uni(uint32_t v) { return __shfl_sync(0xffffffffu, v, 0); }   __device__ __forceinline__ uint32_t ld_acquire(const unsigned int* p) {
    uint32_t v;
    asm volatile("ld.acquire.gpu.global.u32 %0, [%1];" : "=r"(v) : "l"(p) : "memory");
    return v;
}
__device__ __forceinline__ void red_release(unsigned int* p) { asm volatile("red.release.gpu.global.add.u32 [%0], 1;" ::"l"(p) : "memory"); }
__device__ __forceinline__ void wait_count(const unsigned int* p, uint32_t target) {
#pragma unroll 1
    for (uint32_t it = 0; it < SPIN_LIMIT; ++it)
        if ((int)(ld_acquire(p) - target) >= 0) return;
    __trap();
}
__device__ __forceinline__ void wait_count_slow(const unsigned int* p, uint32_t target) {
#pragma unroll 1
    for (uint32_t it = 0; it < SPIN_LIMIT; ++it) {
        if ((int)(ld_acquire(p) - target) >= 0) return;
        __nanosleep(200);
    }
    __trap();
}
__device__ __forceinline__ unsigned long long ld_relaxed1(const void* p) {
    unsigned long long v;
    asm volatile("ld.relaxed.gpu.global.b64 %0, [%1];" : "=l"(v) : "l"(p) : "memory");
    return v;
}
__device__ __forceinline__ ulonglong2 ld_relaxed2(const void* p) {
    ulonglong2 v;
    asm volatile("ld.relaxed.gpu.global.v2.b64 {%0, %1}, [%2];" : "=l"(v.x), "=l"(v.y) : "l"(p) : "memory");
    return v;
}
__device__ __forceinline__ void ld_cell(uint32_t (&v)[4], const void* p, bool on = true) {
    asm volatile("{ .reg .pred p; .reg .b64 l, h; .reg .b128 t; setp.ne.u32 p, %5, 0; mov.b64 l, {%0, %1}; mov.b64 h, {%2, %3}; mov.b128 t, {l, h};\n"
                 "@p ld.relaxed.gpu.global.b128 t, [%4]; mov.b128 {l, h}, t; mov.b64 {%0, %1}, l; mov.b64 {%2, %3}, h; }"
                 : "+r"(v[0]), "+r"(v[1]), "+r"(v[2]), "+r"(v[3]) : "l"(p), "r"((uint32_t)on) : "memory");
}
__device__ __forceinline__ void st_cell(void* p, uint32_t a, uint32_t b, uint32_t c, uint32_t d, bool on) {
    asm volatile("{ .reg .pred p; .reg .b64 l, h; .reg .b128 t; setp.ne.u32 p, %5, 0; mov.b64 l, {%1, %2}; mov.b64 h, {%3, %4}; mov.b128 t, {l, h};\n"
                 "@p st.relaxed.gpu.global.b128 [%0], t; }" ::"l"(p), "r"(a), "r"(b), "r"(c), "r"(d), "r"((uint32_t)on) : "memory");
}

__device__ __forceinline__ uint64_t make_desc(uint32_t addr, uint32_t sbo = 1024) {
    return (uint64_t)((addr & 0x3FFFF) >> 4) | ((uint64_t)1 << 16) | ((uint64_t)(sbo >> 4) << 32) | ((uint64_t)1 << 62);
}
__device__ __forceinline__ void wgmma_fence() { asm volatile("wgmma.fence.sync.aligned;" ::: "memory"); }
__device__ __forceinline__ void wgmma_commit() { asm volatile("wgmma.commit_group.sync.aligned;" ::: "memory"); }
template <int N> __device__ __forceinline__ void wgmma_wait() { asm volatile("wgmma.wait_group.sync.aligned %0;" ::"n"(N) : "memory"); }

#define R8(d, i) "+f"(d[i]), "+f"(d[i + 1]), "+f"(d[i + 2]), "+f"(d[i + 3]), "+f"(d[i + 4]), "+f"(d[i + 5]), "+f"(d[i + 6]), "+f"(d[i + 7])
#define R64(d) R8(d, 0), R8(d, 8), R8(d, 16), R8(d, 24), R8(d, 32), R8(d, 40), R8(d, 48), R8(d, 56)
template <int TA>
__device__ __forceinline__ void wgmma_n128(float (&d)[64], uint64_t da, uint64_t db, int scale_d = 1) {
    asm volatile("{ .reg .pred p; setp.ne.b32 p, %66, 0;\n"
                 "wgmma.mma_async.sync.aligned.m64n128k16.f32.bf16.bf16 "
                 "{%0,%1,%2,%3,%4,%5,%6,%7,%8,%9,%10,%11,%12,%13,%14,%15,%16,%17,%18,%19,%20,%21,%22,%23,%24,%25,%26,%27,%28,%29,%30,%31,"
                 "%32,%33,%34,%35,%36,%37,%38,%39,%40,%41,%42,%43,%44,%45,%46,%47,%48,%49,%50,%51,%52,%53,%54,%55,%56,%57,%58,%59,%60,%61,%62,%63}, "
                 "%64, %65, p, 1, 1, %67, 0; }"
                 : R64(d)
                 : "l"(da), "l"(db), "r"(scale_d), "n"(TA));
}
__device__ __forceinline__ void pin4(float (&d)[4]) { asm volatile("" : "+f"(d[0]), "+f"(d[1]), "+f"(d[2]), "+f"(d[3])::"memory"); }
__device__ __forceinline__ void pin64(float (&d)[64]) { asm volatile("" : R64(d)::"memory"); }

template <int TA, int TB = 0>
__device__ __forceinline__ void wgmma_n8(float (&d)[4], uint64_t da, uint64_t db, int scale_d = 1) {
    asm volatile("{ .reg .pred p; setp.ne.b32 p, %7, 0;\n"
                 "wgmma.mma_async.sync.aligned.m64n8k16.f32.bf16.bf16 {%0,%1,%2,%3}, %4, %5, p, 1, 1, %6, %8; }"
                 : "+f"(d[0]), "+f"(d[1]), "+f"(d[2]), "+f"(d[3])
                 : "l"(da), "l"(db), "n"(TA), "r"(scale_d), "n"(TB));
}

__device__ __forceinline__ float bf_lo(uint32_t u) { return __uint_as_float(u << 16); }
__device__ __forceinline__ float bf_hi(uint32_t u) { return __uint_as_float(u & 0xFFFF0000u); }
__device__ __forceinline__ float rbf(float v) { return __bfloat162float(__float2bfloat16_rn(v)); }
__device__ __forceinline__ uint32_t pack_bf(float lo, float hi) {
    uint32_t r;
    asm("cvt.rn.bf16x2.f32 %0, %1, %2;" : "=r"(r) : "f"(hi), "f"(lo));
    return r;
}
__device__ __forceinline__ uint32_t mul_bf2(uint32_t a, uint32_t b) {
    __nv_bfloat162 r = __hmul2(*reinterpret_cast<__nv_bfloat162*>(&a), *reinterpret_cast<__nv_bfloat162*>(&b));
    return *reinterpret_cast<uint32_t*>(&r);
}
__device__ __forceinline__ uint32_t fma_bf2(uint32_t a, uint32_t b, uint32_t c) {
    uint32_t r;
    asm("fma.rn.bf16x2 %0, %1, %2, %3;" : "=r"(r) : "r"(a), "r"(b), "r"(c));
    return r;
}
__device__ __forceinline__ float2 cmul(float2 a, float2 b) { return make_float2(a.x * b.x - a.y * b.y, a.x * b.y + a.y * b.x); }
__device__ __forceinline__ float2 cfma(float2 a, float2 b, float2 c) {
    return make_float2(fmaf(a.x, b.x, fmaf(-a.y, b.y, c.x)), fmaf(a.x, b.y, fmaf(a.y, b.x, c.y)));
}
__device__ __forceinline__ float sigmoidf_(float v) { return __fdividef(1.0f, 1.0f + expf(-v)); }

__device__ __forceinline__ void bulk_prefetch(const void* src, uint32_t bytes) {
    asm volatile(ONE "cp.async.bulk.prefetch.L2.global [%0], %1; }" ::"l"(src), "r"(bytes) : "memory");
}
__device__ __forceinline__ void bulk_store(void* dst, uint32_t src, uint32_t bytes) {
    asm volatile(ONE "cp.async.bulk.global.shared::cta.bulk_group [%0], [%1], %2; }" ::"l"(dst), "r"(src), "r"(bytes) : "memory");
}
__device__ __forceinline__ void stsm4(uint32_t a, uint32_t x, uint32_t y, uint32_t z, uint32_t w) {
    asm volatile("stmatrix.sync.aligned.m8n8.x4.shared.b16 [%0], {%1,%2,%3,%4};" ::"r"(a), "r"(x), "r"(y), "r"(z), "r"(w) : "memory");
}
__device__ __forceinline__ uint4 ldsm4(uint32_t a) {
    uint4 v;
    asm volatile("ldmatrix.sync.aligned.m8n8.x4.shared.b16 {%0,%1,%2,%3}, [%4];" : "=r"(v.x), "=r"(v.y), "=r"(v.z), "=r"(v.w) : "r"(a) : "memory");
    return v;
}
__device__ __forceinline__ void stg4_unless(float* p, float a, float b, float c, float d, uint32_t skip) {
    asm volatile("{ .reg .pred p; setp.eq.u32 p, %5, 0; @p st.global.v4.f32 [%0], {%1,%2,%3,%4}; }" ::"l"(p), "f"(a), "f"(b), "f"(c), "f"(d), "r"(skip) : "memory");
}
__device__ __forceinline__ void red4(float* p, float a, float b, float c, float d) {
    asm volatile("red.global.add.v4.f32 [%0], {%1,%2,%3,%4};" ::"l"(p), "f"(a), "f"(b), "f"(c), "f"(d) : "memory");
}

#define TT0 3100
#define PER 516
#define PCUT 60
#define PFIN 400
#define PF0 1700
#define PFX_PACE 400
#define PFV 6
#define PFT 0
#define PF1 700
#define T2 400
#define P2 550
#define G0 450
#define R0 2300
#define R_PACE 350
#define W_SHIFT 250
#define PROMO CU_TENSOR_MAP_L2_PROMOTION_L2_256B
#define POLL_S 0
#define ST_TOL 100
#define ST_SHIFT 300
#define CLK_NS 420
#define MARGIN 200
#define BP1 10
#define NDUMP 4
#define HP NDUMP
#define DNL 1
#define AE 6
#define AG0 900
#define AB 16
#define HGE 39
constexpr uint32_t duration(int i) { return PER + (i >= RE0 && i < RE0 + 4 ? 72 : 0) + (i >= GU0 && i < GU0 + 32 ? 36 : 0); }
constexpr uint32_t cmax(uint32_t a, uint32_t b) { return a > b ? a : b; }
constexpr uint32_t issue_time(int i) {
    return i <= NST ? TT0 : i < XE ? issue_time(i - 1) + duration(i - NST) - (i >= XE - 3 && i > GU0 + 36 ? PCUT : 0) : issue_time(XE - 1) + cmax((i - XE + 1) * PFIN, (i - XE) * 512);
}
template <int I> struct Sched { static constexpr uint32_t t = issue_time(I); };
template <int LO, int HI, class F>
__device__ __forceinline__ void for_entries(uint32_t base, F body) {
    constexpr uint32_t per = Sched<LO + 1>::t - Sched<LO>::t;
    static_assert(Sched<HI - 1>::t - Sched<LO>::t == (HI - 1 - LO) * per, "period");
    uint32_t tt = base + Sched<LO>::t;
#pragma unroll 1
    for (int i = LO; i < HI; i++) {
        body(i, tt);
        tt += per;
    }
}

struct Ring { uint32_t prev; int slot; };
struct NoHook { __device__ void operator()() const {} };
template <int TA, int SM, class H = NoHook>
__device__ __forceinline__ void run_entries(Ring& r, int lo, int hi, float (&accA)[64], float (&accB)[64], float (&small)[4],
                                            bool fresh = false, bool sfresh = false, H released = H()) {
    const uint64_t d0 = make_desc(sb);
    const bool leader = (threadIdx.x & 31) == 0;
#pragma unroll 1
    for (int i = lo; i < hi; i++) {
        const uint32_t bar = sb + OFF_FULL + 8 * i;
        const uint64_t da = d0 + (uint64_t)(r.slot * (SLOT >> 4));
        const int n = i - (SM == 1 ? RE0 : GU0);
        const uint64_t dw = SM == 1 ? d0 + (uint64_t)((OFF_W >> 4) + n * 512)
                                    : (((uint64_t)2 << 62) | ((uint64_t)32 << 32) | (128u << 16) | ((sb + OFF_W) >> 4)) + (uint64_t)((n & 7) * 256);
        const uint64_t dt8 = d0 + (uint64_t)((OFF_XS >> 4) + (SM == 1 ? n * 64 : (n >> 1) * 64 + (n & 1) * 4));
        r.slot = r.slot == NST - 1 ? 0 : r.slot + 1;
        mbar_wait(bar);
        KSTAMP(i);
        wgmma_fence();
#pragma unroll
        for (int kk = 0; kk < 4; kk++) {
            wgmma_n128<TA>(accA, da + kk * (TA ? 128 : 2), da + 1024 + kk * 2, kk > 0 || !fresh);
            if (SM == 1) wgmma_n8<0>(small, dw + kk * 2, dt8 + kk * 2, kk > 0 || !sfresh);
            if (SM == 2 && (kk & 1)) wgmma_n8<1>(small, dw + (kk >> 1) * 64, dt8 + (kk >> 1) * 2, kk > 1 || !sfresh);
            wgmma_n128<TA>(accB, da + 512 + kk * (TA ? 128 : 2), da + 1024 + kk * 2, kk > 0 || !fresh);
            if (kk == 1) {
                wgmma_commit();
                wgmma_wait<1>();
                if (leader) mbar_arrive(r.prev);
                released();
            }
        }
        wgmma_commit();
        r.prev = bar + (OFF_EMPTY - OFF_FULL);
        fresh = sfresh = false;
    }
}
template <int HALF, int I>
__device__ __forceinline__ void run_small(float (&acc)[64]) {
    const uint64_t da = make_desc(sb) + (slot_off(I) >> 4);
    KSTAMP(I + HALF * (NENT - FIN));
    wgmma_fence();
#pragma unroll
    for (int kk = 0; kk < 4; kk++) wgmma_n128<1>(acc, da + HALF * 512 + kk * 128, da + 1024 + kk * 2, kk > 0 || !(HALF && I == FIN));
    wgmma_commit();
}
template <int V> struct Int { __host__ __device__ constexpr operator int() const { return V; } };
template <int N, class F> __device__ __forceinline__ void static_for(F f) {
    if constexpr (N > 0) { static_for<N - 1>(f); f(Int<N - 1>()); }
}

__global__ void __launch_bounds__(384, 1)
fused_kernel(const __grid_constant__ Params prm, const __grid_constant__ CUtensorMap mX, const __grid_constant__ CUtensorMap mB, const __grid_constant__ CUtensorMap mCre,
             const __grid_constant__ CUtensorMap mCim, const __grid_constant__ CUtensorMap mW,
             const __grid_constant__ CUtensorMap mWd, const __grid_constant__ CUtensorMap mXr, const __grid_constant__ CUtensorMap mXe) {
    extern __shared__ __align__(1024) uint8_t smem[];
    const uint32_t cstart = clk32();
    const int tid = threadIdx.x, lane = tid & 31;
    uint32_t smid;
    asm volatile("mov.u32 %0, %%smid;" : "=r"(smid));
    {
        const uint32_t b = blockIdx.x & 127, r = tid - PFT, o = (r >> 1) * 2048 + (r & 1) * 128;
#define PFS "@q prefetch.global.L2 [%1]; @p prefetch.global.L2 [%0]; @q prefetch.global.L2 [%2];"
        asm volatile("{ .reg .pred p, q; setp.lt.u32 p, %3, 32; setp.lt.u32 q, %3, 8;\n" PFS " }"
                     ::"l"((const char*)prm.x + (b * 32768 + o)), "l"((const char*)prm.b_re + (b * 8192 + o)), "l"((const char*)prm.b_im + (b * 8192 + o)), "r"(r),
                     "r"(sb + OFF_EPOCH + 12) : "memory");
        gap();
        STAMPIF(tid == PFT, 33);
    }
    const int warp = __shfl_sync(0xffffffffu, tid >> 5, 0);
    int cta;
    asm("{ .reg .pred p; .reg .u32 s, a, b, u, q;\n"
                 "mov.u32 s, %3;\n"
                 "and.b32 a, s, 14; shl.b32 a, a, 2; shr.u32 b, s, 4; add.u32 a, a, b;\n"
                 "sub.u32 u, s, 64; shr.u32 u, u, 1; mul.lo.u32 q, u, 37; shr.u32 q, q, 8; shl.b32 u, u, 3; mad.lo.u32 u, q, -55, u; add.u32 u, u, 12;\n"
                 "setp.lt.u32 p, s, 64; selp.u32 a, a, u, p; and.b32 b, s, 1; mad.lo.u32 a, a, 2, b;\n"
                 "setp.lt.u32 p, s, 124; selp.u32 b, 8, -116, p; add.u32 b, b, s; setp.lt.u32 p, s, 120; selp.u32 a, a, b, p;\n"
                 "setp.ne.u32 p, %2, 0; selp.u32 %0, a, %1, p; }" : "=r"(cta) : "r"(blockIdx.x), "r"(prm.by_smid), "r"(smid));
    const int chunk = (cta >> 5) * 4 + ((cta >> 2) & 3);
    const int dt = ((cta >> 4) & 1) * 4 + (cta & 3);
    asm volatile("{ .reg .pred e, p; elect.sync _|e, 0xffffffff; setp.eq.and.u32 p, %0, 5, e;\n"
                 "@p mbarrier.init.shared::cta.b64 [%1], 1; @p mbarrier.init.shared::cta.b64 [%1 + 8], 1;\n"
                 "fence.mbarrier_init.release.cluster; }" ::"r"(warp), "r"(sb + OFF_FULL) : "memory");
    if (warp == 5 && cta < NCTA) {
        tma5b(sb, &mB, 0, dt * 4, sb + OFF_FULL);
        tma4(sb + 2 * ABYTES, &mX, 0, chunk * 64, sb + OFF_FULL);
        STAMP(31);
        tma5b(sb + SLOT, &mB, 64, dt * 4, sb + OFF_FULL + 8);
        tma4(sb + SLOT + 2 * ABYTES, &mX, 64, chunk * 64, sb + OFF_FULL + 8);
    }
    if (cta >= NCTA) {
        if (smem_u32(smem) != sb) __trap();
        if (tid == 0) wait_count_slow(&prm.s->cnt[0], (atomicAdd(&prm.s->cnt[0], 1u) / NGRID + 1) * NGRID);
        return;
    }
    const bool has_gu = cta >= 16;
    constexpr uint32_t full = sb + OFF_FULL, empty = sb + OFF_EMPTY;
    constexpr uint32_t raw = full + 8 * 32;
    constexpr uint32_t bar_hraw = full + 8 * 97, bar_xs = full + 8 * 98, bar_xb = full + 8 * 100, bar_xa = full + 8 * 101,
        bar_retry = full + 8 * 102, bar_out = full + 8 * 104;
    constexpr uint32_t bar_base = empty - 64, bar_init3 = empty - 56, bar_rdone = empty - 48, bar_order0 = empty - 40, bar_init2 = empty - 32,
        bar_vec = empty - 24, bar_epoch = empty - 16, bar_dummy = empty - 8, bar_xs0 = empty + 8 * 69,
        bar_zero = empty + 8 * 70, bar_xafree = empty + 8 * 71, bar_order2 = empty + 8 * 72, bar_dn = empty + 8 * 73, bar_fp = empty + 8 * 74,
        bar_accb = empty + 8 * 76, bar_xbfree = empty + 8 * 78, bar_fold = empty + 8 * 79, bar_st = empty + 8 * 80,
        bar_order1 = empty + 8 * 67, bar_cand = empty + 8 * 68;

    if (warp == 5) {
        if (lane < 2) mbar_expect_tx(full + 8 * lane, SLOT);
        __syncwarp();
        named_bar(0, 256);
#pragma unroll 1
        for (int i = 2; i < NST; i++) {
            pace_until(cstart + T2 + i * P2);
            tma5b(sb + i * SLOT, &mB, i * 64, dt * 4, full + 8 * i);
            tma4(sb + i * SLOT + 2 * ABYTES, &mX, i * 64, chunk * 64, full + 8 * i);
            STAMPIF(i == 4, 1);
        }
    } else if (warp == 4) {
        mbar_init_n<12>(bar_init2, 4);
        asm volatile("bar.arrive 0, 256;" ::: "memory");
        mbar_init_n<4>(bar_base, 4);
        mbar_init_n<8>(empty + 64, 4);
        *reinterpret_cast<uint2*>(smem + OFF_KEYS + 16) = make_uint2(0, 0);
        asm volatile("bar.arrive 1, 64;" ::: "memory");
        asm volatile("bar.arrive 5, 96;" ::: "memory");
        asm volatile("bar.arrive 6, 96;" ::: "memory");
        mbar_init_n<32>(full + 256, 3);
        if (lane < 2) mbar_arrive(bar_init2);
    } else if ((warp >> 1) == 3) {
        if (warp == 6) {
            mbar_init_n<8>(full + 16, 1);
            if (lane >= 2 && lane < 10) mbar_expect_tx(full + 8 * lane, lane >= RE0 && lane < RE0 + 4 ? SLOT + ABYTES : SLOT);
            __syncwarp();
            asm volatile("bar.arrive 0, 256;" ::: "memory");
        }
        const char* pf0 = (warp & 1) ? (const char*)((cta & 64) ? prm.b_im : prm.b_re) + (cta & 63) * 16384 : (const char*)prm.x + cta * 32768;
        pace_until(cstart + PF1);
        asm volatile("prefetch.global.L2 [%0];" ::"l"(pf0 + (lane & (30 >> (warp & 1) & 30)) * 1024 + (lane & 1) * 128 + 256));
        const int i0 = warp == 6 ? 10 : 21;
        mbar_init_n<11>(full + 8 * i0, 1);
        if (lane >= i0 && lane < i0 + 11) mbar_expect_tx(full + 8 * lane, lane >= GU0 && has_gu ? SLOT + WBYTES : SLOT);
        mbar_init_n<24>(full + 512 + 192 * (warp & 1), 1);
        named_bar(5, 96);
        if (lane == 0) mbar_arrive(bar_init2);
        STAMP(21);
    }
    __syncwarp();

    if (warp >= 8) {
        asm volatile("setmaxnreg.dec.sync.aligned.u32 72;");
        const uint32_t c0 = cstart;
        uint64_t stream;
        asm volatile("createpolicy.fractional.L2::evict_first.b64 %0, 1.0;" : "=l"(stream));
        const int dc = (cta & 15) * 64, dr = (cta >> 4) * 448;
        auto gutile = [&](int i) {
            const int n = i + 3 - GU0;
            if (has_gu) tma3s(sb + OFF_W + (n & 7) * WBYTES, &mW, cta * 32 - 512, n * 32, full + 8 * (i + 3), stream);
        };
        if (warp == 8) {
            named_bar(0, 256);
            asm volatile("prefetch.tensormap [%0];" ::"l"(&mXr));
#pragma unroll 1
            for (int u = 0; u < 2; u++) {
                sleep_until(c0 + R0 + u * R_PACE);
                tma3(sb + OFF_W + u * ABYTES, &mXr, u * 256, cta * 16, full + 8 * (RE0 + u));
            }
            uint32_t dst = sb;
            auto gemm1 = [&](int i, uint32_t tt) {
                mbar_wait(empty + 8 * (i - NST));
                LATE(i, tt);
                pace_until(tt);
                tma5b(dst, &mB, (i & 15) * 64, (i >> 4) * 64 + dt * 4, full + 8 * i);
                tma4(dst + 2 * ABYTES, &mX, (i & 15) * 64, chunk * 64, full + 8 * i);
                dst = dst == sb + (NST - 1) * SLOT ? sb : dst + SLOT;
            };
            mbar_wait(bar_init2);
            uint32_t tt = c0 + TT0;
#pragma unroll 1
            for (int i = NST; i < AB; i++) {
                gemm1(i, tt);
                if (i < 7) tma3(sb + OFF_W + (i - 3) * ABYTES, &mXr, (i - 3) * 256, cta * 16, full + 8 * (i + 1));
                tt += (i & ~3) == RE0 + 4 ? PER + 72 : PER;
            }
            mbar_wait(bar_base);
            const uint32_t base = uni(lds32(sb + OFF_EPOCH + 8));
            tt = base + Sched<AB>::t;
#pragma unroll 1
            for (int i = AB; i < 32; i++) {
                gemm1(i, tt);
                tt += i >= GU0 + 4 ? PER + 36 : PER;
            }
            const char* hsrc = reinterpret_cast<const char*>(prm.s->h) + (size_t)chunk * 524288;
            auto gemm2 = [&](int i, uint32_t d, int freed, uint32_t tt) {
                mbar_wait(empty + 8 * freed);
                LATE(i, tt);
                pace_until(tt);
                bulk_load(d, hsrc, 2 * ABYTES, raw + 8 * i);
                tma5(d + 2 * ABYTES, (i & 4) ? &mCim : &mCre, ((i & 3) + ((i >> 1) & 12)) * 64, dt * 8, full + 8 * i);
                hsrc += 2 * ABYTES;
            };
            for_entries<32, GU0 + 29>(base, [&](int i, uint32_t tt) {
                gemm2(i, dst, i - NST, tt);
                gutile(i);
                dst = dst == sb + (NST - 1) * SLOT ? sb : dst + SLOT;
            });
            for_entries<GU0 + 29, GU0 + 37>(base, [&](int i, uint32_t tt) {
                gemm2(i, dst, i - NST, tt);
                const int n = i - GU0 - 29;
                if ((n & 5) == 1) tma5(sb + OFF_W + (n & 2) * (ABYTES / 2), &mXe, dt * 128 + (n & 2) * 32, chunk * 64, bar_xa);
                else if (n < 6) asm volatile(ONE "cp.async.bulk.prefetch.tensor.2d.L2.global [%0, {%1, %2}]; }" ::"l"(&mWd), "r"(dc), "r"(dr + 64 * (n < 4 ? 3 + n / 2 : n + 1)) : "memory");
                dst = dst == sb + (NST - 1) * SLOT ? sb : dst + SLOT;
            });
            static_for<NENT - GU0 - 37>([&](auto u) {
                constexpr int i = GU0 + 37 + u;
                if (i == 60) mbar_wait(bar_out + 56);
                gemm2(i, sb + slot_off(i), i < XE ? i - NST : i == XE ? 71   : i - NST - 1, base + Sched<i>::t);
            });
            STAMP(4);
        } else if (warp == 9) {
#pragma unroll
            for (int u = 0; u < 8; u++) {
                const int row = (u >> 2) * 4 + (lane >> 3);
                asm volatile("cp.async.cg.shared.global [%0], [%1], 16;" ::"r"(sb + OFF_XS + (u & 3) * 1024 + row * 128 + (((lane & 7) ^ row) << 4)),
                             "l"((const char*)(u < 4 ? prm.w_r : prm.gate_w) + (u & 3) * 512 + lane * 16) : "memory");
            }
            uint32_t ticket = 0;
            if (lane == 0) ticket = atomicAdd(&prm.s->cnt[0], 1u);
            named_bar(1, 64);
            if (lane == 0) *reinterpret_cast<volatile uint32_t*>(smem + OFF_EPOCH) = ticket / NGRID;
            __syncwarp();
            if (lane < 4) mbar_arrive(bar_epoch);
            asm volatile("cp.async.wait_all;" ::: "memory");
            asm volatile("fence.proxy.async.shared::cta;" ::: "memory");
            __syncwarp();
            if (lane < 4) mbar_arrive(bar_vec);
            STAMP(18);
#pragma unroll 1
            for (int i = 4; i < 22; i++) mbar_init_n<4>(empty + 32 * i, 4, i >= 6 && i < 13);
            if (lane < 2) mbar_arrive(bar_init3);
            STAMP(19);
            mbar_wait(bar_cand);
            {
                const uint32_t* list = reinterpret_cast<const uint32_t*>(smem + OFF_LIST);
                const int n = (int)lds32(sb + OFF_KEYS + 16);
#pragma unroll 1
                for (int i0 = 0; i0 < n; i0 += 32) {
                    const uint32_t k = list[i0 + lane];
                    int rank = 0;
#pragma unroll 2
                    for (int o = 0; o < n; o += 4) {
                        const uint4 l4 = *reinterpret_cast<const uint4*>(list + o);
                        rank += (l4.x > k) + (l4.y > k) + (l4.z > k) + (l4.w > k);
                    }
                    if (rank < 8) reinterpret_cast<uint32_t*>(smem + OFF_SEL)[rank] = k;
                }
                __syncwarp();
                STAMP(6);
                const uint32_t key = lds32(sb + OFF_SEL + 4 * (lane & 7)), tok = ~key & 2047u, tag = lds32(sb + OFF_EPOCH) + 1;
                const uint32_t ta = __shfl_sync(0xffffffffu, tok, lane >> 3), tb = __shfl_sync(0xffffffffu, tok, 4 + (lane >> 3));
                const uint32_t da = sb + OFF_XS + (lane >> 3) * 128 + (((lane & 7) ^ (lane >> 3)) << 4), db = (da ^ 64) + 512;
                const char *sa = (const char*)prm.x + ta * 2048 + (lane & 7) * 16, *sc = (const char*)prm.x + tb * 2048 + (lane & 7) * 16;
#pragma unroll
                for (int u = 0; u < 16; u++) {
                    asm volatile("cp.async.cg.shared.global [%0], [%1], 16;" ::"r"(da + u * 1024), "l"(sa + u * 128) : "memory");
                    asm volatile("cp.async.cg.shared.global [%0], [%1], 16;" ::"r"(db + u * 1024), "l"(sc + u * 128) : "memory");
                    if (u == 3) {
                        asm volatile("cp.async.wait_all;" ::: "memory");
                        asm volatile("fence.proxy.async.shared::cta;" ::: "memory");
                        __syncwarp();
                        if (lane < 4) mbar_arrive(bar_xs0);
                        STAMP(17);
                    }
                }
                if ((tok >> 7) == (uint32_t)chunk) {
                    float4* zp = reinterpret_cast<float4*>(prm.out + tok * D_ + dt * 128) + (lane >> 3) * 2;
#pragma unroll
                    for (int u = 0; u < 8; u++) zp[(u >> 1) * 8 + (u & 1)] = make_float4(0.f, 0.f, 0.f, 0.f);
                }
                uint32_t it = 0;
                unsigned long long u;
                do {
                    u = ld_relaxed1(&prm.s->gpack[tok >> 1]);
                    if (++it > SPIN_LIMIT) __trap();
                } while (!__all_sync(0xffffffffu, (uint32_t)(u >> 32) == tag));
                const uint32_t kb = key >> 16;
                const float r = bf_lo((kb & 0x8000u) ? (kb & 0x7FFFu) : (~kb & 0xFFFFu)), gv = (tok & 1) ? bf_hi((uint32_t)u) : bf_lo((uint32_t)u);
                reinterpret_cast<float*>(smem + OFF_FAC)[lane & 7] = rbf(1.0f - gv) * rbf(sigmoidf_(r));
                asm volatile("cp.async.wait_all;" ::: "memory");
                asm volatile("fence.proxy.async.shared::cta;" ::: "memory");
                __syncwarp();
                if (lane == 0) mbar_arrive(bar_xs);
                STAMP(7);
            }
            char* hd = reinterpret_cast<char*>(prm.s->h) + (size_t)chunk * 524288 + (dt >> 1) * 16384 + (dt & 1) * 4096;
            mbar_wait(bar_base);
            const uint32_t cb = uni(lds32(sb + OFF_EPOCH + 8)) + ST_SHIFT;
            uint32_t tt = cb + Sched<GU0 + 4>::t;
#pragma unroll 1
            for (int np = 0; np < 16; np++) {
                if (!(np & (np & 4 ? 1 : 2))) mbar_wait(bar_st + 4 * (np & 12) + ((np & 3) ? 8 : 0));
                const uint32_t now = clk32() - ST_TOL;
#pragma unroll 1
                while ((int)(tt - now) < 0) tt += PER + 36;
                const uint32_t src = sb + OFF_STG + (np & 3) * 4096;
                pace_until(tt);
                bulk_store(hd, src, 4096);
                asm volatile("cp.async.bulk.commit_group;" ::: "memory");
                if (np & 2) {
                    if (np & 1) asm volatile("cp.async.bulk.wait_group.read 0;" ::: "memory");
                    else asm volatile("cp.async.bulk.wait_group.read 1;" ::: "memory");
                    __syncwarp();
                    const uint32_t u8 = 4 * (np & 12) + 8 * (np & 1);
                    if (lane < 2) mbar_arrive(lane ? (np < 15 ? empty + 8 * 27 + 4 * u8 : bar_dummy) : bar_out + u8);
                }
                STAMPIF(np & 2, 8 + ((np >> 1) & 6) + (np & 1));
                hd += (np & 1) ? 65536 - 8192 : 8192;
                tt += PER + 36;
            }
#pragma unroll 1
            for (int u = 0; u < 2; u++) {
                pace_until(tt);
                tma5(sb + OFF_STG + u * ABYTES, &mXe, dt * 128 + u * 64, chunk * 64 + 8, bar_xb);
                tt += PER + 36;
            }
            wait_count(&prm.s->cnt[32], (lds32(sb + OFF_EPOCH) + 1) * NCTA);
            auto load_hid = [&]() {
                if (lane == 0) mbar_expect_tx(bar_hraw, 7168);
                bulk_load(sb + OFF_XS, prm.s->hid + dr, 7168, bar_hraw);
            };
            static_for<7>([&](auto u) {
                if (u != 2) mbar_wait(u == 1 ? bar_xbfree : empty + 8 * (u == 0 ? GU0 + 31 : u == 3 ? FIN + DNL : FIN - 2 + u));
                if (u < 3) sleep_until(cb + Sched<GU0 + HGE - 2 + u>::t);
                if (u == 2) load_hid();
                tma2(sb + dn_off(u), &mWd, dc, dr + u * 64, bar_dn, stream);
                if (u == 2) {
                    const uint32_t t2 = lds32(sb + OFF_EPOCH) + 1, tagw = (t2 & 1) | ((t2 & 2) << 15);
#pragma unroll 1
                    for (uint32_t it = 0;; it++) {
                        mbar_wait(bar_hraw, it & 1);
                        uint32_t bad = 0;
#pragma unroll
                        for (int i = 0; i < 14; i++) bad |= lds32(sb + OFF_XS + i * 512 + lane * 16 + (lane >> 3) * 4) ^ tagw;
                        if (__all_sync(0xffffffffu, (bad & 0x00010001u) == 0)) break;
                        if (it > SPIN_LIMIT) __trap();
                        load_hid();
                    }
                    if (lane < 4) mbar_arrive(bar_zero);
                    STAMP(48);
                }
            });
            STAMP(27);
        } else {
            named_bar(6, 96);
            if (warp == 10) {
                const char* pb = (const char*)((cta & 64) ? prm.b_im : prm.b_re) + (cta & 63) * 16384;
                const char* pf = (lane < 16 ? (const char*)prm.x + cta * 32768 : pb) + (lane & 15) * 2048 + 512;
#pragma unroll 1
                for (int k = 0; k < 11; k++) {
                    sleep_until(c0 + PF0 + k * PFX_PACE);
                    if (lane < 16 ? k < 6 : lane < 24 && !(k & 1)) prefetch_l2(pf + k * (lane < 16 ? 256 : 128));
                }
                static_for<12>([&](auto k) {
                    sleep_until(c0 + Sched<BP1 + k>::t + ST_SHIFT);
                    bulk_prefetch((k < 4 ? pb + 1048576 : (const char*)(k < 8 ? prm.c_re : prm.c_im) + cta * 16384) + (k & 3) * 4096, 4096);
                    if (k == 4) { mbar_wait(bar_init2); mbar_wait(bar_init3); }
                    if (k >= 4 && lane < 8) mbar_expect_tx(full + 8 * (8 * k + lane), 8 * k + lane < GU0 + 32 && has_gu ? 2 * ABYTES + WBYTES : 2 * ABYTES);
                });
                asm volatile("prefetch.tensormap [%0];" ::"l"(&mCre));
                asm volatile("prefetch.tensormap [%0];" ::"l"(&mCim));
                asm volatile("prefetch.tensormap [%0];" ::"l"(&mWd));
                asm volatile("prefetch.tensormap [%0];" ::"l"(&mXe));
                if (lane < 2) mbar_expect_tx(bar_xb + 8 * lane, 2 * ABYTES);
                mbar_wait(bar_xs);
                mbar_wait(bar_st);
                if (lane == 0) red_release(&prm.s->cnt[32]);
                __syncwarp();
                STAMP(22);
            } else {
                asm volatile("prefetch.tensormap [%0];" ::"l"(&mW));
                mbar_wait(bar_epoch);
                const uint32_t tag = lds32(sb + OFF_EPOCH) + 1;
                st_cell(prm.s->time + cta, 0, 0, 0, 0, lane == 0);
                mbar_wait(empty + 8 * AE);
                uint32_t gown, tm[4][4] = {}, it = 0;
                asm volatile("mov.u32 %0, %%globaltimer_lo;" : "=r"(gown));
                const uint32_t town = clk32();
                st_cell(prm.s->time + cta, tag, town, gown, 0, lane == 0);
                sleep_until(town + AG0);
                do {
#pragma unroll
                    for (int m = 0; m < 4; m++) ld_cell(tm[m], prm.s->time + ((cta & 96) ^ (32 * m)) + lane);
                    if (++it > SPIN_LIMIT) __trap();
                } while (!__all_sync(0xffffffffu, tm[0][0] == tag && tm[1][0] == tag && tm[2][0] == tag && tm[3][0] == tag));
                const int last = __reduce_max_sync(0xffffffffu, max(max((int)(tm[0][2] - gown), (int)(tm[1][2] - gown)), max((int)(tm[2][2] - gown), (int)(tm[3][2] - gown))));
                const uint32_t cand = tm[0][1] + ((min((int)(gown + last - tm[0][2]), 4000) * CLK_NS) >> 8);
                const uint32_t b0 = __shfl_sync(0xffffffffu, cand, cta & 16), b1 = __shfl_sync(0xffffffffu, cand, cta & 30);
                const uint32_t base = (b0 - b1 + 400u < 800u ? b0 : b1) + MARGIN - Sched<AE + NST>::t;
                *reinterpret_cast<volatile uint32_t*>(smem + OFF_EPOCH + 8) = base;
                mbar_wait(bar_init3);
                if (lane < 4) mbar_arrive(bar_base);
                STAMP(23);
                const uint32_t cb = base + W_SHIFT;
                auto early = [&](int i, uint32_t tt) {
                    mbar_wait(empty + 8 * (i - NST));
                    pace_until(tt);
                    gutile(i);
                };
                for_entries<GU0 - 3, GU0 + 4>(cb, early);
                for_entries<GU0 + 4, 32>(cb, early);
            }
            mbar_wait(bar_epoch);
            const uint32_t t2 = lds32(sb + OFF_EPOCH) + 1, tagw = (t2 & 1) | ((t2 & 2) << 15), half = (warp & 1) * ABYTES;
            const uint32_t lo = half + lane * 32 + (lane & 4) * 4 + (lane >> 3) * 4, retry = bar_retry + (warp & 1) * 8;
            const bool leader = lane == 0;
            uint32_t slot = sb + (32 % NST) * SLOT, rpar = 0;
#pragma unroll 1
            for (int i = 32; i < NENT; i++) {
                const uint32_t src = i == XE ? sb + OFF_W : slot;
                if (i != XE) slot = slot == sb + (NST - 1) * SLOT ? sb : slot + SLOT;
                auto current = [&]() {
                    uint32_t v[8];
#pragma unroll
                    for (int u = 0; u < 8; u++) v[u] = lds32(src + lo + u * 1024);
#pragma unroll
                    for (int u = 0; u < 8; u += 2) asm("lop3.b32 %0, %0, %1, %2, 0x7e;" : "+r"(v[u]) : "r"(v[u + 1]), "r"(tagw));
                    return __all_sync(0xffffffffu, ((v[0] | v[2] | v[4] | v[6]) & 0x00010001u) == 0);
                };
                mbar_wait(raw + 8 * i);
                if (!current()) {
#pragma unroll 1
                    for (uint32_t it = 0;; it++) {
                        if (it > SPIN_LIMIT) __trap();
                        STAMP(16);
                        if (leader) mbar_expect_tx(retry, ABYTES);
                        bulk_load(src + half, reinterpret_cast<const char*>(prm.s->h) + (size_t)chunk * 524288 + (i - 32) * 16384 + half, ABYTES, retry);
                        mbar_wait(retry, rpar);
                        rpar ^= 1;
                        if (current()) break;
                    }
                }
                if (leader) mbar_arrive(full + 8 * i);
            }
        }
    } else {
        asm volatile("setmaxnreg.inc.sync.aligned.u32 216;");
        const int wg = warp >> 2, w = warp & 3, g = lane >> 2, c = lane & 3, at = tid & 127;
        float facc[4];
        float2 a[2], m0[2], a32[2], a128[2];
        auto load_const = [&]() {
            const float2* cp = reinterpret_cast<const float2*>(smem + OFF_CONST) + wg * 64 + w * 8 + g;
#pragma unroll
            for (int h = 0; h < 2; h++) { a[h] = cp[32 * h]; m0[h] = cp[128 + 32 * h]; a32[h] = cp[256 + 32 * h]; a128[h] = cp[384 + 32 * h]; }
        };
        if (wg == 0) {
            named_bar(0, 256);
            STAMPIF(tid == 0, 20);
        } else {
            const int pc = (at >> 5) * 256 + dt * 32 + (at & 31);
            const float lr = __bfloat162float(prm.lam_re[pc]), li = __bfloat162float(prm.lam_im[pc]), ld = __bfloat162float(prm.log_dt[pc]);
            const uint32_t dk = __ldg(reinterpret_cast<const uint32_t*>(prm.dskip + dt * 128) + (at & 63));
#pragma unroll
            for (int i = 0; i < 4; i++) sts128(sb + OFF_LIST + i * 2048 + at * 16, 0u, 0u, 0u, 0u);

            {
                reinterpret_cast<uint32_t*>(smem + OFF_DK)[at & 63] = dk;
                const float dtv = rbf(expf(ld));
                const float er = expf(dtv * lr);
                float sn, cs;
                sincospif(dtv * li * 0.318309886183790672f, &sn, &cs);
                const float ar = er * cs, ai = er * sn;
                const float nr = ar - 1.0f, ni = ai;
                const bool big = fabsf(lr) >= fabsf(li);
                const float t = (big ? li : lr) / (big ? lr : li), dn = big ? lr + li * t : lr * t + li;
                const float cr = (big ? nr + ni * t : nr * t + ni) / dn, ci = (big ? ni - nr * t : ni * t - nr) / dn;
                float2* cp = reinterpret_cast<float2*>(smem + OFF_CONST) + at;
                float2 pw = make_float2(ar, prm.swapped ? ai : -ai);
                cp[0] = pw;
                cp[128] = make_float2(prm.swapped ? -2.f * cr : 2.f * cr, -2.f * ci);
#pragma unroll
                for (int i = 1; i <= 7; i++) {
                    pw = cmul(pw, pw);
                    if (i == 5) cp[256] = pw;
                    if (i == 7) cp[384] = pw;
                }
                __syncwarp();
            }
            named_bar(2, 128);
            load_const();
            mbar_wait(bar_epoch);
            const uint32_t tag = *reinterpret_cast<volatile uint32_t*>(smem + OFF_EPOCH) + 1;
            asm volatile("st.relaxed.gpu.global.b64 [%0], %1;" ::"l"(&prm.s->carry[(chunk >> 2) * 4096 + pc * 4 + (chunk & 3)]), "l"((unsigned long long)(tag + 2)) : "memory");
            if (w == 2) st_cell(lane < 4 ? (uint4*)prm.s->rpack + cta * 4 + lane : (uint4*)prm.s->gpack + cta * 4 + (lane & 3), 0, 0, 0, 0, lane < 8);
            {
                const uint32_t nt = ((tag & 1) | ((tag & 2) << 15)) ^ 0x00010001u;
                st_cell(prm.s->hid + cta * 32 - 512 + lane, nt, nt, nt, nt, has_gu && w == 3);
            }
            named_bar(2, 128);
            if (at < 2) mbar_arrive(bar_init3);
            unsigned long long* pub = (w ? prm.s->gpack : prm.s->rpack) + cta * 8 + lane;
            asm volatile("" : "+l"(pub));
            STAMPIF(lane == 0, 52);
            mbar_wait(bar_rdone);

            if (w < 2) {
                const float2* red = reinterpret_cast<const float2*>(smem + OFF_RED) + w * 8 + (lane & 7);
                const float2 r0 = red[0], r1 = red[16], r2 = red[32], r3 = red[48];
                const float v0 = (r0.x + r1.x) + (r2.x + r3.x), v1 = (r0.y + r1.y) + (r2.y + r3.y);
                uint32_t pk2;
                if (w == 0) {
                    pk2 = pack_bf(v0, v1);
                    pk2 ^= (((pk2 >> 15) & 0x00010001u) * 0x7FFFu) ^ 0x80008000u;
                } else pk2 = pack_bf(sigmoidf_(rbf(v0)), sigmoidf_(rbf(v1)));
                if (lane < 8) asm volatile("st.relaxed.gpu.global.b64 [%0], %1;" ::"l"(pub), "l"(((unsigned long long)tag << 32) | pk2) : "memory");
                __syncwarp();
            }
            STAMPIF(at == 0, 24);
            uint32_t it = 0, pr[8], g1;
            mbar_wait(bar_init3);
            sleep_until(clk32() + (w < 2 ? G0 : G0 + 250));
            while (true) {
                bool ok = true;
#pragma unroll
                for (int k = 0; k < 4; k++) {
                    const ulonglong2 u = ld_relaxed2(&prm.s->rpack[k * 256 + 2 * at]);
                    ok = ok && (uint32_t)(u.x >> 32) == tag && (uint32_t)(u.y >> 32) == tag;
                    pr[2 * k] = (uint32_t)u.x; pr[2 * k + 1] = (uint32_t)u.y;
                }
                const unsigned long long u1 = ld_relaxed1(&prm.s->gpack[chunk * 64 + (at & 63)]);
                ok = ok && (uint32_t)(u1 >> 32) == tag;
                g1 = (uint32_t)u1;
                if (__all_sync(0xffffffffu, ok)) break;
                if (++it > SPIN_LIMIT) __trap();
            }
            STAMPIF(lane == 0, 25);
            uint32_t m = __vmaxu2(__vimax3_u16x2(__vimax3_u16x2(pr[0], pr[1], pr[2]), pr[3], pr[4]), __vimax3_u16x2(pr[5], pr[6], pr[7]));
            m = (max(m, m << 16) & 0xFFFF0000u) | (uint32_t)lane;
            const uint32_t m1 = __reduce_max_sync(0xffffffffu, m), m2 = __reduce_max_sync(0xffffffffu, m == m1 ? 0u : m);
            uint32_t* keys = reinterpret_cast<uint32_t*>(smem + OFF_KEYS);
            if (lane == 0) keys[w] = m2;
            sts128(sb + OFF_XS + 4096 + at * 16, pr[0], pr[1], pr[2], pr[3]);
            sts128(sb + OFF_XS + 6144 + at * 16, pr[4], pr[5], pr[6], pr[7]);
            *reinterpret_cast<uint32_t*>(smem + OFF_G + 4 * (at & 63)) = g1;
            named_bar(2, 128);
            const uint4 th4 = *reinterpret_cast<const uint4*>(keys);
            const uint32_t th = (max(min(min(th4.x, th4.y), min(th4.z, th4.w)) >> 16, 1u) - 1u) * 0x00010001u;
            uint32_t mask = 0;
#pragma unroll
            for (int k = 7; k >= 0; k--) mask = mask * 2 + __vminu2(__vmaxu2(pr[k], th) ^ th, 0x00010001u);
            uint32_t pos = 0;
            asm volatile("{ .reg .pred p; setp.ne.u32 p, %2, 0; @p atom.shared.add.u32 %0, [%1], %2; }" : "+r"(pos) : "r"(sb + OFF_KEYS + 16), "r"(__popc(mask)) : "memory");
            while (mask) {
                const int bit = __ffs(mask) - 1, k = bit & 7, hi = bit >> 4;
                mask &= mask - 1;
                const uint32_t sc = *reinterpret_cast<const uint16_t*>(smem + OFF_XS + 4096 + (k >> 2) * 2048 + at * 16 + (k & 3) * 4 + hi * 2);
                *reinterpret_cast<uint32_t*>(smem + OFF_LIST + 4 * pos++) = (sc << 16) | (0x8000u + 2047u - (uint32_t)((k >> 1) * 512 + 4 * at + 2 * (k & 1) + hi));
            }
            __syncwarp();
            if (lane == 0) mbar_arrive(bar_cand);
            STAMPIF(lane == 0, 26);
            mbar_wait(bar_order0);
        }

        float accA[64], accB[64];
        Ring ring = {bar_dummy, wg};
        {
            run_entries<0, 0>(ring, wg * 16, wg ? GU0 : RE0, accA, accB, facc, true);
            if (wg == 0) {
                float racc[4];
                mbar_wait(bar_vec);
                run_entries<0, 1>(ring, RE0, RE0 + 4, accA, accB, racc, false, true);
                mbar_wait(bar_init2);
                const uint32_t red = sb + OFF_RED + 4 * (w * 32 + (c >> 1) * 16 + g);
                run_entries<0, 0>(ring, RE0 + 4, RE0 + 5, accA, accB, facc, false, false, [&]() {
                    pin4(racc);
                    asm volatile("{ .reg .pred p; setp.ne.u32 p, %3, 0; @p st.shared.f32 [%0], %1; @p st.shared.f32 [%0 + 32], %2; }" ::"r"(red),
                                 "f"((w & 1) ? racc[1] : racc[0]), "f"((w & 1) ? racc[3] : racc[2]), "r"((uint32_t)((c & 1) == (w >> 1))) : "memory");
                    __syncwarp();
                    if (lane == 0) mbar_arrive(bar_rdone);
                    STAMPIF(lane == 0, 5);
                });
                run_entries<0, 0>(ring, RE0 + 5, 16, accA, accB, facc);
                if (lane == 0) mbar_arrive(bar_order0);
                mbar_wait(bar_init3);
                load_const();
                named_bar(3, 128);
            } else {
#pragma unroll
                for (int u = 0; u < 2; u++) {
                    mbar_wait(u ? bar_xs : bar_xs0);
                    run_entries<0, 2>(ring, GU0 + 8 * u, u ? 32 : GU0 + 8, accA, accB, facc, false, u == 0);
                }
                if (lane == 0) mbar_arrive(bar_order1);
            }
        }
        const uint32_t tag = *reinterpret_cast<volatile uint32_t*>(smem + OFF_EPOCH) + 1;
        const float2 a64[2] = {cmul(a32[0], a32[0]), cmul(a32[1], a32[1])};
        wgmma_wait<0>();
        pin64(accA); pin64(accB); pin4(facc);
        if (lane == 0) mbar_arrive(ring.prev);
        STAMPIF(at == 0, 28 + wg);
        GSTAMP(tid == 0, 1);

        const int tl = 32 * (g >> 1) + (g & 1) + 4 * w + 16 * wg, t0 = chunk * 128 + tl;
        float* op = prm.out + (size_t)t0 * D_ + dt * 128 + 4 * c;
        uint2 xv[8][2], dk[8];
        uint32_t gp[2], om[2], routed[2];
        auto row_setup = [&]() {
            const uint4 sa = *reinterpret_cast<const uint4*>(smem + OFF_SEL), sc = *reinterpret_cast<const uint4*>(smem + OFF_SEL + 16);
#pragma unroll
            for (int r = 0; r < 2; r++) {
                const uint32_t id = 0x8000u + 2047u - (uint32_t)(t0 + 2 * r);
                routed[r] = (uint16_t)sa.x == id || (uint16_t)sa.y == id || (uint16_t)sa.z == id || (uint16_t)sa.w == id ||
                            (uint16_t)sc.x == id || (uint16_t)sc.y == id || (uint16_t)sc.z == id || (uint16_t)sc.w == id;
                gp[r] = reinterpret_cast<const uint16_t*>(smem + OFF_G)[tl + 2 * r] * 0x00010001u;
                om[r] = pack_bf(1.0f - bf_hi(gp[r]), 1.0f - bf_hi(gp[r]));
            }
#pragma unroll
            for (int j = 0; j < 8; j++) dk[j] = lds64(sb + OFF_DK + 32 * j + 8 * c);
        };
        auto release = [&](uint32_t bar) {
            asm volatile("fence.proxy.async.shared::cta;" ::: "memory");
            __syncwarp();
            if (lane == 0) mbar_arrive(bar);
        };

        {
            const uint32_t t2 = tag & 3u;
            float2* cslot = &prm.s->carry[(wg * 512 + dt * 32 + w * 8 + g) * 4];
            const int j1 = chunk - 1 - c;
            unsigned long long v[2][4] = {{t2, t2, t2, t2}, {t2, t2, t2, t2}};
            auto poll = [&](int h) {
#pragma unroll
                for (int m = 0; m < 4; m++)
                    asm volatile("{ .reg .pred p; setp.ge.s32 p, %2, %3; @p ld.relaxed.gpu.global.b64 %0, [%1]; }"
                                 : "+l"(v[h][m]) : "l"(cslot + (j1 >> 2) * 4096 + c - m * 4096 + h * 1024), "r"(j1), "r"(4 * m) : "memory");
            };
            float2 e[2], w0[2];
            auto chain = [&](int h, int s0, int s1) {
                float (&acc)[64] = h ? accB : accA;
                if (s0 == 1) e[h] = make_float2(acc[0], acc[2]);
#pragma unroll
                for (int s = s0; s < s1; s++) {
                    const int i0 = 4 * (s >> 1) + (s & 1);
                    e[h] = cfma(make_float2(a[h].x, -a[h].y), e[h], make_float2(acc[i0], acc[i0 + 2]));
                }
                asm volatile("" : "+f"(e[h].x), "+f"(e[h].y), "+f"(accB[0]), "+f"(accB[2]));
                gap();
            };
            auto publish = [&](int h) {
                float2 f = make_float2(fmaf(m0[h].x, e[h].x, m0[h].y * e[h].y), fmaf(-m0[h].x, e[h].y, m0[h].y * e[h].x));
                float2 y = make_float2(__shfl_up_sync(0xffffffffu, f.x, 1, 4), __shfl_up_sync(0xffffffffu, f.y, 1, 4));
                if (c >= 1) f = cfma(a32[h], y, f);
                y = make_float2(__shfl_up_sync(0xffffffffu, f.x, 2, 4), __shfl_up_sync(0xffffffffu, f.y, 2, 4));
                if (c >= 2) f = cfma(a64[h], y, f);
                asm volatile("{ .reg .pred p; .reg .b64 t; setp.eq.u32 p, %3, 3; mov.b64 t, {%1, %2}; @p st.relaxed.gpu.global.b64 [%0], t; }"
                             ::"l"(cslot + (chunk >> 2) * 4096 + (chunk & 3) + h * 1024), "r"((__float_as_uint(f.x) & ~3u) | t2), "r"(__float_as_uint(f.y)), "r"(c) : "memory");
                w0[h] = make_float2(__shfl_up_sync(0xffffffffu, f.x, 1, 4), __shfl_up_sync(0xffffffffu, f.y, 1, 4));
                if (c == 0) w0[h] = make_float2(0.f, 0.f);
            };
            auto scale = [&](int h, int n0, int n1) {
                float (&acc)[64] = h ? accB : accA;
#pragma unroll
                for (int n = n0; n < n1; n++) {
                    asm volatile("{ .reg .f32 a, b, c, d, n; neg.f32 n, %4; mul.f32 a, %1, %5; mul.f32 b, %0, %5; mul.f32 c, %3, %5; mul.f32 d, %2, %5;\n"
                                 "fma.rn.f32 %0, %0, %4, a; fma.rn.f32 %1, %1, n, b; fma.rn.f32 %2, %2, %4, c; fma.rn.f32 %3, %3, n, d; }"
                                 : "+f"(acc[4 * n]), "+f"(acc[4 * n + 2]), "+f"(acc[4 * n + 1]), "+f"(acc[4 * n + 3]) : "f"(m0[h].x), "f"(m0[h].y));
                    gap();
                }
            };
            auto carry = [&](int h) {
                const float2 one = make_float2(1.f, 0.f), a256 = cmul(a128[h], a128[h]);
                float2 a512 = cmul(a256, a256), pw128 = cmul((j1 & 1) ? a128[h] : one, (j1 & 2) ? a256 : one);
                float2 pw32 = cmul((c & 1) ? a32[h] : one, (c & 2) ? a64[h] : one);
                asm volatile("" : "+f"(a512.x), "+f"(a512.y), "+f"(pw128.x), "+f"(pw128.y), "+f"(pw32.x), "+f"(pw32.y));
                STAMPIF(lane == 0 && !h, 34 + 2 * wg);
                uint32_t it = 0;
                while (!__all_sync(0xffffffffu, ((((uint32_t)v[h][0] ^ t2) | ((uint32_t)v[h][1] ^ t2) | ((uint32_t)v[h][2] ^ t2) | ((uint32_t)v[h][3] ^ t2)) & 3u) == 0)) {
                    poll(h);
                    if (++it > SPIN_LIMIT) __trap();
                }
                STAMPIF(lane == 0 && !h, 35 + 2 * wg);
                float2 hin = make_float2(__uint_as_float((uint32_t)v[h][3]), __uint_as_float((uint32_t)(v[h][3] >> 32)));
#pragma unroll
                for (int m = 2; m >= 0; m--) hin = cfma(a512, hin, make_float2(__uint_as_float((uint32_t)v[h][m]), __uint_as_float((uint32_t)(v[h][m] >> 32))));
                hin = cmul(pw128, hin);
                hin.x += __shfl_xor_sync(0xffffffffu, hin.x, 1); hin.y += __shfl_xor_sync(0xffffffffu, hin.y, 1);
                hin.x += __shfl_xor_sync(0xffffffffu, hin.x, 2); hin.y += __shfl_xor_sync(0xffffffffu, hin.y, 2);
                w0[h] = cfma(pw32, hin, w0[h]);
            };
            chain(0, 1, 32);
            publish(0);
            chain(1, 1, 8);
            STAMPIF(lane == 0, 30 + 2 * wg);
            chain(1, 8, 32);
            publish(1);
            gap();
            scale(0, 0, POLL_S);
            poll(0);
            scale(0, POLL_S, 16);
            carry(0);
            if (wg) mbar_wait(bar_out + 24);
            STAMPIF(lane == 0, 38 + 2 * wg);
            const uint32_t stg = sb + OFF_STG + prm.swapped * 8192 + w * 1024 + (lane & 7) * 128 + (((lane >> 3) ^ (lane & 7)) << 4);
            const uint32_t second = prm.swapped ? -8192 : 8192;
            uint32_t hold = prm.swapped >> 1, last[8];
            const uint32_t keep = c == (g >> 1) ? 0xFFFEFFFEu : 0xFFFFFFFFu, tagw = ((t2 & 1) | ((t2 & 2) << 15)) & ~keep;
#pragma unroll
            for (int h = 0; h < 2; h++) {
                float (&acc)[64] = h ? accB : accA;
                uint32_t ra[16], ia[16];
                if (h) {
                    scale(1, 0, 4);
#pragma unroll
                    for (int u = 0; u < 4; u++) asm volatile("lop3.b32 %0, %0, %1, %2, 0x80;" : "+r"(hold) : "r"(last[u]), "r"(last[4 + u]));
                    release(bar_st + 32 * wg + 8 + hold);
                    poll(1);
                    scale(1, 4, 16);
                    mbar_wait(bar_xs);
                    row_setup();
                    carry(1);
                }
                auto stage = [&](uint32_t (&r)[16], uint32_t base, int j) {
                    stsm4((base ^ ((j & 1) * 64)) + (j >> 1) * 4096, r[4 * j], r[4 * j + 1], r[4 * j + 2], r[4 * j + 3]);
                };
#pragma unroll
                for (int n = 0; n < 16; n++) {
                    const float2 y = cfma(a[h], w0[h], make_float2(acc[4 * n], acc[4 * n + 2]));
                    w0[h] = cfma(a[h], y, make_float2(acc[4 * n + 1], acc[4 * n + 3]));
                    ra[n] = pack_bf(y.x, w0[h].x);
                    ia[n] = pack_bf(y.y, w0[h].y);
                    if (!(n & 1)) { ra[n] = (ra[n] & keep) | tagw; ia[n] = (ia[n] & keep) | tagw; }
                    if (!h && (n & 3) == 3) {
                        if (n > 3) {
                            gap();
#pragma unroll
                            for (int u = n - 7; u < n - 3; u++) asm volatile("lop3.b32 %0, %0, %1, %2, 0x80;" : "+r"(hold) : "r"(ra[u]), "r"(ia[u]));
                        }
                        if (n == 15) {
#pragma unroll
                            for (int u = 0; u < 4; u++) { last[u] = ra[12 + u]; last[4 + u] = ia[12 + u]; }
                        }
                        if (n == 11) { asm volatile("" : "+r"(ra[n]), "+r"(ia[n])); gap(); release(bar_st + 32 * wg); }
                        stage(ra, stg, n >> 2); stage(ia, stg + second, n >> 2);
                        gap();
                    }
                }
                if (h) {
                    STAMPIF(lane == 0, 39 + 2 * wg);
                    mbar_wait(bar_out + 32 * wg);
                    if (prm.swapped) {
#pragma unroll
                        for (int n = 0; n < 16; n++) { const uint32_t t = ra[n]; ra[n] = ia[n]; ia[n] = t; }
                    }
                    const uint32_t st0 = stg - prm.swapped * 8192;
#pragma unroll
                    for (int j = 0; j < 4; j++) stage(ra, st0, j);
                    release(bar_st + 32 * wg + 16);
                    mbar_wait(bar_out + 32 * wg + 8);
#pragma unroll
                    for (int j = 0; j < 4; j++) stage(ia, st0 + 8192, j);
                    release(bar_st + 32 * wg + 24);
                }
                STAMPIF(lane == 0, 42 + 2 * wg + h);
            }
        }

        const uint32_t xr = 2 * (g & 3) + (g >> 2), xa = sb + (wg ? OFF_STG : OFF_W) + (16 * w + xr) * 128 + (((c >> 1) ^ xr) << 4) + (c & 1) * 8;
        auto handover = [&](uint32_t bar) {
            const uint4 z = ldsm4(sb + OFF_KEYS + 16);
            if (lane == 1) mbar_arrive(bar + z.x);
        };
        auto load_x = [&](int j0, int j1) {
#pragma unroll
            for (int j = j0; j < j1; j++)
#pragma unroll
                for (int r = 0; r < 2; r++) xv[j][r] = lds64((xa ^ (32 * (j & 3))) + (j >> 2) * ABYTES + r * 1024);
        };
        auto skip_term = [&](int j0, int j1) {
#pragma unroll
            for (int j = j0; j < j1; j++)
#pragma unroll
                for (int r = 0; r < 2; r++) {
                    xv[j][r].x = mul_bf2(xv[j][r].x, fma_bf2(gp[r], dk[j].x, om[r]));
                    xv[j][r].y = mul_bf2(xv[j][r].y, fma_bf2(gp[r], dk[j].y, om[r]));
                    asm volatile("" : "+r"(xv[j][r].x), "+r"(xv[j][r].y));
                }
        };
        auto finish = [&](float (&acc)[64], int j, bool gaps) {
#pragma unroll
            for (int r = 0; r < 2; r++) {
                const int o = 8 * j + 2 * r;
                const float gv = bf_hi(gp[r]);
                acc[o] = fmaf(gv, acc[o], bf_lo(xv[j][r].x)); acc[o + 1] = fmaf(gv, acc[o + 1], bf_hi(xv[j][r].x));
                acc[o + 4] = fmaf(gv, acc[o + 4], bf_lo(xv[j][r].y)); acc[o + 5] = fmaf(gv, acc[o + 5], bf_hi(xv[j][r].y));
                stg4_unless(op + r * 2 * D_ + 16 * j, acc[o], acc[o + 1], acc[o + 4], acc[o + 5], routed[r]);
                if (gaps) gap();
            }
        };
        auto finish_routed = [&](float (&acc)[64]) {
#pragma unroll
            for (int r = 0; r < 2; r++)
                if (routed[r]) {
#pragma unroll
                    for (int j = 0; j < 8; j++) red4(op + r * 2 * D_ + 16 * j, acc[8 * j + 2 * r], acc[8 * j + 2 * r + 1], acc[8 * j + 2 * r + 4], acc[8 * j + 2 * r + 5]);
                }
            __syncwarp();
        };
        const uint32_t xbuf = sb + slot_off(FIN) + w * 2048 + lane * 16;

        if (wg == 1) {
            float outB[64];
            {
                sts128(sb + OFF_XS + at * 16, __float_as_uint(facc[0]), __float_as_uint(facc[1]), __float_as_uint(facc[2]), __float_as_uint(facc[3]));
                named_bar(2, 128);
                const uint32_t pg = sb + OFF_XS + prm.up_first * 1024 + (at & 63) * 16 + (w >> 1) * 8, pu = pg + 1024 - prm.up_first * 2048;
                const uint2 g1 = lds64(pg), u1 = lds64(pu);
                uint4* hp = prm.s->hid + cta * 32 - 512 + 16 * (w & 1) + 8 * (w >> 1) + g;
                asm volatile("" : "+l"(hp));
                mbar_wait(bar_fp);
                const uint2 g2 = lds64(pg + 2048), u2 = lds64(pu + 2048);
                const float ga = rbf(__uint_as_float(g1.x) + __uint_as_float(g2.x)), gb = rbf(__uint_as_float(g1.y) + __uint_as_float(g2.y));
                uint32_t hw = mul_bf2(pack_bf(__fdividef(ga, 1.0f + __expf(-ga)), __fdividef(gb, 1.0f + __expf(-gb))),
                                      pack_bf(__uint_as_float(u1.x) + __uint_as_float(u2.x), __uint_as_float(u1.y) + __uint_as_float(u2.y)));
                if (c == 2 * (w & 1) + (w >> 1)) hw = (hw & 0xFFFEFFFEu) | (tag & 1) | ((tag & 2) << 15);
                st_cell(hp, hw, __shfl_down_sync(0xffffffffu, hw, 1), __shfl_down_sync(0xffffffffu, hw, 2), __shfl_down_sync(0xffffffffu, hw, 3), has_gu && c == 0);
            }
            STAMPIF(lane == 0, 47);
            mbar_wait(bar_xb);
            load_x(0, 8);
            release(bar_xbfree);
            skip_term(0, 8);
            STAMPIF(lane == 0, 46);
            mbar_wait(bar_order2);
            static_for<NENT - FIN>([&](auto u) {
                run_small<1, FIN + u>(outB);
                if (u == 2) { wgmma_wait<2>(); if (lane == 0) mbar_arrive(bar_fold); }
            });
            if (lane == 0) mbar_expect_tx(bar_dn, w ? 0 : 7 * ABYTES);
            wgmma_wait<0>();
            pin64(outB);
            KSTAMP(2 * NENT - FIN);
            STAMPIF(at == 0, 50);
#pragma unroll
            for (int q = 0; q < 2; q++) {
                uint4 pb[16];
                mbar_wait(bar_accb + 8 * q);
#pragma unroll
                for (int v = q * HP; v < (q ? 16 : HP); v++) pb[v] = ldsm4(xbuf + (v >> 2) * ABYTES + (v & 3) * 512);
#pragma unroll
                for (int v = q * HP; v < (q ? 16 : HP); v++) {
                    outB[4 * v] += __uint_as_float(pb[v].x); outB[4 * v + 1] += __uint_as_float(pb[v].y);
                    outB[4 * v + 2] += __uint_as_float(pb[v].z); outB[4 * v + 3] += __uint_as_float(pb[v].w);
                    if (v & 1) finish(outB, v >> 1, false);
                }
            }
            finish_routed(outB);
            STAMPIF(lane == 0, 51);
        } else {
            float outA[64], outB[64], gacc[4];
            ring.slot = 32 % NST;
            ring.prev = bar_dummy;
            mbar_wait(bar_order1);
            run_entries<1, 2>(ring, 32, GU0 + 32, outA, outB, gacc, true, true);
            run_entries<1, 0>(ring, GU0 + 32, GU0 + 33, outA, outB, gacc, false, false, [&]() {
                pin4(gacc);
                sts128(sb + OFF_XS + 2048 + at * 16, __float_as_uint(gacc[0]), __float_as_uint(gacc[1]), __float_as_uint(gacc[2]), __float_as_uint(gacc[3]));
                __syncwarp();
                if (lane == 0) mbar_arrive(bar_fp);
            });
            mbar_wait(bar_xa);
            run_entries<1, 0>(ring, GU0 + 33, GU0 + 34, outA, outB, gacc, false, false, [&]() { load_x(0, 2); });
            load_x(2, 4);
            run_entries<1, 0>(ring, GU0 + 34, GU0 + 35, outA, outB, gacc, false, false, [&]() { load_x(4, 6); });
            load_x(6, 8);
            run_entries<1, 0>(ring, GU0 + 35, GU0 + 36, outA, outB, gacc, false, false, [&]() { release(bar_xafree); });
            run_entries<1, 0>(ring, GU0 + 36, FIN, outA, outB, gacc);
            static_for<NENT - FIN>([&](auto u) {
                mbar_wait(full + 8 * (FIN + u));
                run_small<0, FIN + u>(outA);
                if (u == 5 && lane == 0) mbar_arrive(bar_order2);
                wgmma_wait<1>();
                if (lane == 0) mbar_arrive(empty + 8 * (FIN + u - 1));
                if (u < 4) skip_term(2 * u, 2 * u + 2);
            });
            const uint2 sk = lds64(sb + OFF_SEL + 8 * c), fk = lds64(sb + OFF_FAC + 8 * c);
            float* y0 = prm.out + (~sk.x & 2047u) * D_ + (cta & 15) * 64 + w * 16 + g;
            float* y1 = prm.out + (~sk.y & 2047u) * D_ + (cta & 15) * 64 + w * 16 + g;
            asm volatile("" : "+l"(y0), "+l"(y1));
            mbar_wait(empty + 8 * FIN);
            wgmma_wait<0>();
            pin64(outA); pin64(outB);
            STAMPIF(at == 0, 53);
            GSTAMP(at == 0, 2);
            auto dump = [&](int v) {
                if (v == 4) mbar_wait(bar_fold);
                stsm4(xbuf + (v >> 2) * ABYTES + (v & 3) * 512, __float_as_uint(outB[4 * v]), __float_as_uint(outB[4 * v + 1]), __float_as_uint(outB[4 * v + 2]),
                      __float_as_uint(outB[4 * v + 3]));
                if (v == HP - 1 || v == 15) handover(bar_accb + 8 * (v == 15));
            };
#pragma unroll
            for (int j = 0; j < 8; j++) {
                finish(outA, j, true);
#pragma unroll
                for (int v = j * NDUMP / 8; v < (j + 1) * NDUMP / 8; v++) dump(v);
            }
            STAMPIF(lane == 0, 54);
#pragma unroll
            for (int v = NDUMP; v < 16; v++) dump(v);
            STAMPIF(lane == 0, 55);
            float yacc[4];
            const uint64_t dw = make_desc(sb), dh = (uint64_t)(((sb + OFF_XS) & 0x3FFFF) >> 4) | ((uint64_t)8 << 16) | ((uint64_t)8 << 32);
            mbar_wait(bar_zero);
            mbar_wait(bar_dn);
            STAMPIF(at == 0, 2);
            wgmma_fence();
#pragma unroll
            for (int n = 0; n < 28; n++) wgmma_n8<1, 1>(yacc, dw + (dn_off(n >> 2) >> 4) + (n & 3) * 128, dh + n * 16, n > 0);
            wgmma_commit();
            finish_routed(outA);
            wgmma_wait<0>();
            pin4(yacc);
            atomicAdd(y0, yacc[0] * __uint_as_float(fk.x)); atomicAdd(y1, yacc[1] * __uint_as_float(fk.y));
            atomicAdd(y0 + 8, yacc[2] * __uint_as_float(fk.x)); atomicAdd(y1 + 8, yacc[3] * __uint_as_float(fk.y));
            STAMPIF(lane == 0, 3);
        }
    }
}

typedef CUresult (*EncodeFn)(CUtensorMap*, CUtensorMapDataType, cuuint32_t, void*, const cuuint64_t*, const cuuint64_t*, const cuuint32_t*,
                             const cuuint32_t*, CUtensorMapInterleave, CUtensorMapSwizzle, CUtensorMapL2promotion, CUtensorMapFloatOOBfill);

bool encode(EncodeFn fn, CUtensorMap* m, const void* ptr, int rank, const cuuint64_t* dims, const cuuint64_t* strides, const cuuint32_t* box,
            CUtensorMapSwizzle sw = CU_TENSOR_MAP_SWIZZLE_128B, CUtensorMapL2promotion promo = CU_TENSOR_MAP_L2_PROMOTION_NONE) {
    const cuuint32_t es[5] = {1, 1, 1, 1, 1};
    return fn(m, CU_TENSOR_MAP_DATA_TYPE_BFLOAT16, rank, const_cast<void*>(ptr), dims, strides, box, es, CU_TENSOR_MAP_INTERLEAVE_NONE,
              sw, promo, CU_TENSOR_MAP_FLOAT_OOB_FILL_NONE) == CUDA_SUCCESS;
}

}

extern "C" void kernel_launch(void* const* d_in, const int* in_sizes, int n_in, void* d_out, int out_size) {
    (void)in_sizes; (void)n_in; (void)out_size;
    Params prm;
    prm.x = (const __nv_bfloat16*)d_in[0];
    prm.lam_re = (const __nv_bfloat16*)d_in[1];
    prm.lam_im = (const __nv_bfloat16*)d_in[2];
    prm.b_re = (const __nv_bfloat16*)d_in[3];
    prm.b_im = (const __nv_bfloat16*)d_in[4];
    prm.c_re = (const __nv_bfloat16*)d_in[5];
    prm.c_im = (const __nv_bfloat16*)d_in[6];
    prm.log_dt = (const __nv_bfloat16*)d_in[7];
    prm.dskip = (const __nv_bfloat16*)d_in[8];
    prm.w_r = (const __nv_bfloat16*)d_in[10];
    prm.gate_w = (const __nv_bfloat16*)d_in[14];
    prm.out = (float*)d_out;
    cudaGetSymbolAddress((void**)&prm.s, g_scratch);
    int dev = 0, sms = 0;
    cudaGetDevice(&dev);
    cudaDeviceGetAttribute(&sms, cudaDevAttrMultiProcessorCount, dev);
    prm.by_smid = sms == NGRID;
    prm.swapped = prm.b_im < prm.b_re;

    void* fnp = nullptr;
    cudaDriverEntryPointQueryResult qr;
    cudaGetDriverEntryPoint("cuTensorMapEncodeTiled", &fnp, cudaEnableDefault, &qr);
    EncodeFn fn = (EncodeFn)fnp;
    cudaFuncSetAttribute(fused_kernel, cudaFuncAttributeMaxDynamicSharedMemorySize, SMEM_BYTES);

    CUtensorMap mX, mB, mCre, mCim, mW, mWd, mXr, mXe;
    const cuuint64_t row = 2048;
    {
        const cuuint64_t dims[4] = {1024, 2, 4, 976}, st[3] = {row, 32 * row, 2 * row};
        const cuuint32_t box[4] = {64, 2, 4, 16};
        encode(fn, &mX, prm.x, 4, dims, st, box, CU_TENSOR_MAP_SWIZZLE_128B, PROMO);
    }
    {
        const char *lo = (const char*)(prm.swapped ? prm.b_im : prm.b_re), *hi = (const char*)(prm.swapped ? prm.b_re : prm.b_im);
        const cuuint64_t dims[5] = {1024, 8, 2, 96, 2}, st[4] = {row, (cuuint64_t)(hi - lo), 8 * row, 256 * row};
        const cuuint32_t box[5] = {64, 8, 2, 4, 2};
        encode(fn, &mB, lo, 5, dims, st, box, CU_TENSOR_MAP_SWIZZLE_128B, PROMO);
    }
    {
        const cuuint64_t dims[5] = {1024, 2, 4, 2, 64}, st[4] = {row, 4 * row, 2 * row, 16 * row};
        const cuuint32_t box[5] = {64, 2, 4, 2, 8};
        encode(fn, &mCre, prm.c_re, 5, dims, st, box);
        encode(fn, &mCim, prm.c_im, 5, dims, st, box);
    }
    {
        const char *pg = (const char*)d_in[11], *pu = (const char*)d_in[12];
        prm.up_first = pu < pg;
        const cuuint64_t dims[3] = {F_, D_, 2}, st[2] = {F_ * 2, (cuuint64_t)(pu < pg ? pg - pu : pu - pg)}, dimsd[2] = {D_, F_}, std_[1] = {row};
        const cuuint32_t box[3] = {32, 32, 2}, boxd[2] = {64, 64};
        encode(fn, &mW, pu < pg ? pu : pg, 3, dims, st, box, CU_TENSOR_MAP_SWIZZLE_64B, CU_TENSOR_MAP_L2_PROMOTION_NONE);
        encode(fn, &mWd, d_in[13], 2, dimsd, std_, boxd, CU_TENSOR_MAP_SWIZZLE_128B, CU_TENSOR_MAP_L2_PROMOTION_NONE);
    }
    {
        const cuuint64_t dims[3] = {D_ - 192, S_, 4}, st[2] = {row, 128};
        const cuuint32_t box[3] = {64, 16, 4};
        encode(fn, &mXr, prm.x, 3, dims, st, box, CU_TENSOR_MAP_SWIZZLE_128B, CU_TENSOR_MAP_L2_PROMOTION_NONE);
    }
    {
        const cuuint64_t dims[5] = {D_, 2, 2, 2, 976}, st[4] = {64 * row, row, 32 * row, 2 * row};
        const cuuint32_t box[5] = {64, 2, 2, 2, 8};
        encode(fn, &mXe, prm.x, 5, dims, st, box);
    }
    fused_kernel<<<NGRID, 384, SMEM_BYTES, cudaStreamPerThread>>>(prm, mX, mB, mCre, mCim, mW, mWd, mXr, mXe);
}
```

```cpp
#include <cuda_runtime.h>
#include <cuda_bf16.h>
#include <cuda.h>
#include <stdint.h>

namespace {

constexpr int S_ = 2048, D_ = 1024, F_ = 3584;
constexpr int NCTA = 128, NGRID = 132;
#define XE_ 58
#define GU0_ 18
constexpr int NENT = 64, FIN = 58, XE = XE_;
constexpr int NST = 5;
constexpr int RE0 = 4;
constexpr int GU0 = GU0_;
constexpr uint32_t SLOT = 32768, ABYTES = 8192, WBYTES = 4096;
constexpr uint32_t OFF_XS = NST * SLOT;
constexpr uint32_t OFF_LIST = OFF_XS + 8192;
constexpr uint32_t OFF_W = OFF_XS + 16384;
constexpr uint32_t OFF_STG = OFF_W + 32768;
__host__ __device__ constexpr uint32_t slot_off(int i) { return i < XE ? (i % NST) * SLOT : i == XE ? OFF_W : ((i - 1) % NST) * SLOT; }
__host__ __device__ constexpr uint32_t dn_off(int u) { return u == 0 ? OFF_XS + ABYTES : u < 3 ? OFF_STG + (u - 1) * ABYTES : slot_off(FIN - 2 + u); }
constexpr uint32_t OFF_CONST = OFF_STG;
constexpr uint32_t OFF_RED = OFF_STG + 4096;
constexpr uint32_t OFF_FULL = OFF_STG + 16384;
constexpr uint32_t OFF_EMPTY = OFF_FULL + 120 * 8;
constexpr uint32_t OFF_G = OFF_EMPTY + 88 * 8;
constexpr uint32_t OFF_DK = OFF_G + 256;
constexpr uint32_t OFF_KEYS = OFF_DK + 256;
constexpr uint32_t OFF_SEL = OFF_KEYS + 32;
constexpr uint32_t OFF_FAC = OFF_SEL + 32;
constexpr uint32_t OFF_EPOCH = OFF_FAC + 32;
constexpr uint32_t OFF_PROF = OFF_EPOCH + 16;
constexpr uint32_t SMEM_BYTES = OFF_PROF + 768;
static_assert(SMEM_BYTES <= 232448, "smem");

constexpr uint32_t sb = 1024;
constexpr uint32_t SPIN_LIMIT = 1u << 18;

struct Scratch {
    unsigned int cnt[2 * 32];
    unsigned long long rpack[S_ / 2];
    unsigned long long gpack[S_ / 2];
    uint4 time[NCTA];
    float2 carry[16 * 1024];
    uint4 hid[F_];
    uint4 h[8 * 4 * 256 * 64];
};
__device__ __align__(128) Scratch g_scratch;
#define STAMPW(cond, w) do {} while (0)
#define LATE(i, tt) do {} while (0)
#define LANDED(i) do {} while (0)
#define GSTAMP(cond, w) do {} while (0)
#define STAMPIF(cond, i) STAMPW(cond, 72 + (i))
#define STAMP(i) STAMPW(1, 72 + (i))
#define KSTAMP(i) STAMPW((threadIdx.x & 127) == 0, i)

struct Params {
    const __nv_bfloat16 *x, *b_re, *b_im;
    Scratch* s;
    int up_first;
    int swapped;
    const __nv_bfloat16 *lam_re, *lam_im, *c_re, *c_im, *log_dt, *dskip, *w_r, *gate_w;
    float* out;
};

__device__ __forceinline__ uint32_t smem_u32(const void* p) { return (uint32_t)__cvta_generic_to_shared(p); }
__device__ __forceinline__ void mbar_init(uint32_t bar, uint32_t cnt) { asm volatile("mbarrier.init.shared::cta.b64 [%0], %1;" ::"r"(bar), "r"(cnt) : "memory"); }
__device__ __forceinline__ void mbar_expect_tx(uint32_t bar, uint32_t bytes) { asm volatile("mbarrier.arrive.expect_tx.shared::cta.b64 _, [%0], %1;" ::"r"(bar), "r"(bytes) : "memory"); }
__device__ __forceinline__ void mbar_arrive(uint32_t bar) { asm volatile("mbarrier.arrive.shared::cta.b64 _, [%0];" ::"r"(bar) : "memory"); }
__device__ __forceinline__ void mbar_wait(uint32_t bar, uint32_t parity = 0) {
    asm volatile("{ .reg .pred p; .reg .u32 n;\n"
                 "mbarrier.try_wait.parity.shared::cta.b64 p, [%0], %1;\n"
                 "@p bra.uni DONE;\n"
                 "mov.u32 n, 0;\n"
                 "AGAIN: mbarrier.try_wait.parity.shared::cta.b64 p, [%0], %1;\n"
                 "@p bra.uni DONE;\n"
                 "add.u32 n, n, 1;\n"
                 "setp.lt.u32 p, n, %2;\n"
                 "@p bra.uni AGAIN;\n"
                 "trap;\n"
                 "DONE: }" ::"r"(bar), "r"(parity), "n"(SPIN_LIMIT) : "memory");
}
__device__ __forceinline__ bool elect_one() {
    uint32_t pred;
    asm volatile("{ .reg .pred P; elect.sync _|P, 0xffffffff; selp.b32 %0, 1, 0, P; }" : "=r"(pred));
    return pred;
}
__device__ __forceinline__ void named_bar(int id, int n) { asm volatile("bar.sync %0, %1;" ::"r"(id), "r"(n) : "memory"); }

#define ONE "{ .reg .pred e; elect.sync _|e, 0xffffffff;\n@e "
template <int N> __device__ __forceinline__ void mbar_init_n(uint32_t bar, uint32_t cnt, uint32_t extra = 0) {
    if (elect_one()) {
#pragma unroll
        for (int i = 0; i < N; i++) mbar_init(bar + 8 * i, i == N - 1 ? cnt + extra : cnt);
        asm volatile("fence.mbarrier_init.release.cluster;" ::: "memory");
    }
    __syncwarp();
}
__device__ __forceinline__ void bulk_load(uint32_t dst, const void* src, uint32_t bytes, uint32_t bar) {
    asm volatile(ONE "cp.async.bulk.shared::cluster.global.mbarrier::complete_tx::bytes [%0], [%1], %2, [%3]; }" ::"r"(dst), "l"(src), "r"(bytes), "r"(bar) : "memory");
}
__device__ __forceinline__ void sts128(uint32_t a, uint32_t x, uint32_t y, uint32_t z, uint32_t w) {
    asm volatile("st.shared.v4.u32 [%0], {%1,%2,%3,%4};" ::"r"(a), "r"(x), "r"(y), "r"(z), "r"(w) : "memory");
}
__device__ __forceinline__ uint2 lds64(uint32_t a) {
    uint2 v;
    asm volatile("ld.shared.v2.u32 {%0,%1}, [%2];" : "=r"(v.x), "=r"(v.y) : "r"(a) : "memory");
    return v;
}
__device__ __forceinline__ uint32_t clk32() { uint32_t c; asm volatile("mov.u32 %0, %%clock;" : "=r"(c)); return c; }
__device__ __forceinline__ void gap() { asm volatile("pmevent 1;" ::: "memory"); }
__device__ __forceinline__ void pace_until(uint32_t t) { while ((int)(clk32() - t) < 0) {} }
#define SLEEP_MARGIN 200
__device__ __forceinline__ void sleep_until(uint32_t t) {
    while ((int)(clk32() + SLEEP_MARGIN - t) < 0) __nanosleep(40);
    pace_until(t);
}
__device__ __forceinline__ void tma2(uint32_t dst, const CUtensorMap* m, int c0, int c1, uint32_t bar, uint64_t pol) {
    asm volatile(ONE "cp.async.bulk.tensor.2d.shared::cluster.global.mbarrier::complete_tx::bytes.L2::cache_hint [%0], [%1, {%3, %4}], [%2], %5; }"
                 ::"r"(dst), "l"(m), "r"(bar), "r"(c0), "r"(c1), "l"(pol) : "memory");
}
__device__ __forceinline__ void tma3s(uint32_t dst, const CUtensorMap* m, int c0, int c1, uint32_t bar, uint64_t pol) {
    asm volatile(ONE "cp.async.bulk.tensor.3d.shared::cluster.global.mbarrier::complete_tx::bytes.L2::cache_hint [%0], [%1, {%3, %4, %5}], [%2], %6; }"
                 ::"r"(dst), "l"(m), "r"(bar), "r"(c0), "r"(c1), "r"(0), "l"(pol) : "memory");
}
__device__ __forceinline__ void tma3(uint32_t dst, const CUtensorMap* m, int c0, int c1, uint32_t bar) {
    asm volatile(ONE "cp.async.bulk.tensor.3d.shared::cluster.global.mbarrier::complete_tx::bytes [%0], [%1, {%3, %4, %5}], [%2]; }"
                 ::"r"(dst), "l"(m), "r"(bar), "r"(c0), "r"(c1), "r"(0) : "memory");
}
__device__ __forceinline__ void tma4(uint32_t dst, const CUtensorMap* m, int c0, int c3, uint32_t bar) {
    asm volatile(ONE "cp.async.bulk.tensor.4d.shared::cluster.global.mbarrier::complete_tx::bytes [%0], [%1, {%3, %5, %5, %4}], [%2]; }"
                 ::"r"(dst), "l"(m), "r"(bar), "r"(c0), "r"(c3), "r"(0) : "memory");
}
__device__ __forceinline__ void tma5(uint32_t dst, const CUtensorMap* m, int c0, int c4, uint32_t bar) {
    asm volatile(ONE "cp.async.bulk.tensor.5d.shared::cluster.global.mbarrier::complete_tx::bytes [%0], [%1, {%3, %5, %5, %5, %4}], [%2]; }"
                 ::"r"(dst), "l"(m), "r"(bar), "r"(c0), "r"(c4), "r"(0) : "memory");
}
__device__ __forceinline__ void tma5b(uint32_t dst, const CUtensorMap* m, int c0, int c3, uint32_t bar) {
    asm volatile(ONE "cp.async.bulk.tensor.5d.shared::cluster.global.mbarrier::complete_tx::bytes [%0], [%1, {%3, %5, %5, %4, %5}], [%2]; }"
                 ::"r"(dst), "l"(m), "r"(bar), "r"(c0), "r"(c3), "r"(0) : "memory");
}
__device__ __forceinline__ void prefetch_l2(const void* p) {
    asm volatile("cp.async.ca.shared.global.L2::256B [%0], [%1], 4;" ::"r"(sb + OFF_EPOCH + 12), "l"(p) : "memory");
}

__device__ __forceinline__ uint32_t lds32(uint32_t a) {
    uint32_t v;
    asm volatile("ld.volatile.shared.u32 %0, [%1];" : "=r"(v) : "r"(a) : "memory");
    return v;
}
__device__ __forceinline__ uint32_t uni(uint32_t v) { return __shfl_sync(0xffffffffu, v, 0); }   __device__ __forceinline__ uint32_t ld_acquire(const unsigned int* p) {
    uint32_t v;
    asm volatile("ld.acquire.gpu.global.u32 %0, [%1];" : "=r"(v) : "l"(p) : "memory");
    return v;
}
__device__ __forceinline__ void red_release(unsigned int* p) { asm volatile("red.release.gpu.global.add.u32 [%0], 1;" ::"l"(p) : "memory"); }
__device__ __forceinline__ void wait_count(const unsigned int* p, uint32_t target) {
#pragma unroll 1
    for (uint32_t it = 0; it < SPIN_LIMIT; ++it)
        if ((int)(ld_acquire(p) - target) >= 0) return;
    __trap();
}
__device__ __forceinline__ void wait_count_slow(const unsigned int* p, uint32_t target) {
#pragma unroll 1
    for (uint32_t it = 0; it < SPIN_LIMIT; ++it) {
        if ((int)(ld_acquire(p) - target) >= 0) return;
        __nanosleep(200);
    }
    __trap();
}
__device__ __forceinline__ unsigned long long ld_relaxed1(const void* p) {
    unsigned long long v;
    asm volatile("ld.relaxed.gpu.global.b64 %0, [%1];" : "=l"(v) : "l"(p) : "memory");
    return v;
}
__device__ __forceinline__ ulonglong2 ld_relaxed2(const void* p) {
    ulonglong2 v;
    asm volatile("ld.relaxed.gpu.global.v2.b64 {%0, %1}, [%2];" : "=l"(v.x), "=l"(v.y) : "l"(p) : "memory");
    return v;
}
__device__ __forceinline__ void ld_cell(uint32_t (&v)[4], const void* p, bool on = true) {
    asm volatile("{ .reg .pred p; .reg .b64 l, h; .reg .b128 t; setp.ne.u32 p, %5, 0; mov.b64 l, {%0, %1}; mov.b64 h, {%2, %3}; mov.b128 t, {l, h};\n"
                 "@p ld.relaxed.gpu.global.b128 t, [%4]; mov.b128 {l, h}, t; mov.b64 {%0, %1}, l; mov.b64 {%2, %3}, h; }"
                 : "+r"(v[0]), "+r"(v[1]), "+r"(v[2]), "+r"(v[3]) : "l"(p), "r"((uint32_t)on) : "memory");
}
__device__ __forceinline__ void st_cell(void* p, uint32_t a, uint32_t b, uint32_t c, uint32_t d, bool on) {
    asm volatile("{ .reg .pred p; .reg .b64 l, h; .reg .b128 t; setp.ne.u32 p, %5, 0; mov.b64 l, {%1, %2}; mov.b64 h, {%3, %4}; mov.b128 t, {l, h};\n"
                 "@p st.relaxed.gpu.global.b128 [%0], t; }" ::"l"(p), "r"(a), "r"(b), "r"(c), "r"(d), "r"((uint32_t)on) : "memory");
}

__device__ __forceinline__ uint64_t make_desc(uint32_t addr, uint32_t sbo = 1024) {
    return (uint64_t)((addr & 0x3FFFF) >> 4) | ((uint64_t)1 << 16) | ((uint64_t)(sbo >> 4) << 32) | ((uint64_t)1 << 62);
}
__device__ __forceinline__ void wgmma_fence() { asm volatile("wgmma.fence.sync.aligned;" ::: "memory"); }
__device__ __forceinline__ void wgmma_commit() { asm volatile("wgmma.commit_group.sync.aligned;" ::: "memory"); }
template <int N> __device__ __forceinline__ void wgmma_wait() { asm volatile("wgmma.wait_group.sync.aligned %0;" ::"n"(N) : "memory"); }

#define R8(d, i) "+f"(d[i]), "+f"(d[i + 1]), "+f"(d[i + 2]), "+f"(d[i + 3]), "+f"(d[i + 4]), "+f"(d[i + 5]), "+f"(d[i + 6]), "+f"(d[i + 7])
#define R64(d) R8(d, 0), R8(d, 8), R8(d, 16), R8(d, 24), R8(d, 32), R8(d, 40), R8(d, 48), R8(d, 56)
template <int TA>
__device__ __forceinline__ void wgmma_n128(float (&d)[64], uint64_t da, uint64_t db, int scale_d = 1) {
    asm volatile("{ .reg .pred p; setp.ne.b32 p, %66, 0;\n"
                 "wgmma.mma_async.sync.aligned.m64n128k16.f32.bf16.bf16 "
                 "{%0,%1,%2,%3,%4,%5,%6,%7,%8,%9,%10,%11,%12,%13,%14,%15,%16,%17,%18,%19,%20,%21,%22,%23,%24,%25,%26,%27,%28,%29,%30,%31,"
                 "%32,%33,%34,%35,%36,%37,%38,%39,%40,%41,%42,%43,%44,%45,%46,%47,%48,%49,%50,%51,%52,%53,%54,%55,%56,%57,%58,%59,%60,%61,%62,%63}, "
                 "%64, %65, p, 1, 1, %67, 0; }"
                 : R64(d)
                 : "l"(da), "l"(db), "r"(scale_d), "n"(TA));
}
__device__ __forceinline__ void pin4(float (&d)[4]) { asm volatile("" : "+f"(d[0]), "+f"(d[1]), "+f"(d[2]), "+f"(d[3])::"memory"); }
__device__ __forceinline__ void pin64(float (&d)[64]) { asm volatile("" : R64(d)::"memory"); }

template <int TA, int TB = 0>
__device__ __forceinline__ void wgmma_n8(float (&d)[4], uint64_t da, uint64_t db, int scale_d = 1) {
    asm volatile("{ .reg .pred p; setp.ne.b32 p, %7, 0;\n"
                 "wgmma.mma_async.sync.aligned.m64n8k16.f32.bf16.bf16 {%0,%1,%2,%3}, %4, %5, p, 1, 1, %6, %8; }"
                 : "+f"(d[0]), "+f"(d[1]), "+f"(d[2]), "+f"(d[3])
                 : "l"(da), "l"(db), "n"(TA), "r"(scale_d), "n"(TB));
}

__device__ __forceinline__ float bf_lo(uint32_t u) { return __uint_as_float(u << 16); }
__device__ __forceinline__ float bf_hi(uint32_t u) { return __uint_as_float(u & 0xFFFF0000u); }
__device__ __forceinline__ float rbf(float v) { return __bfloat162float(__float2bfloat16_rn(v)); }
__device__ __forceinline__ uint32_t pack_bf(float lo, float hi) {
    uint32_t r;
    asm("cvt.rn.bf16x2.f32 %0, %1, %2;" : "=r"(r) : "f"(hi), "f"(lo));
    return r;
}
__device__ __forceinline__ uint32_t mul_bf2(uint32_t a, uint32_t b) {
    __nv_bfloat162 r = __hmul2(*reinterpret_cast<__nv_bfloat162*>(&a), *reinterpret_cast<__nv_bfloat162*>(&b));
    return *reinterpret_cast<uint32_t*>(&r);
}
__device__ __forceinline__ uint32_t fma_bf2(uint32_t a, uint32_t b, uint32_t c) {
    uint32_t r;
    asm("fma.rn.bf16x2 %0, %1, %2, %3;" : "=r"(r) : "r"(a), "r"(b), "r"(c));
    return r;
}
__device__ __forceinline__ float2 cmul(float2 a, float2 b) { return make_float2(a.x * b.x - a.y * b.y, a.x * b.y + a.y * b.x); }
__device__ __forceinline__ float2 cfma(float2 a, float2 b, float2 c) {
    return make_float2(fmaf(a.x, b.x, fmaf(-a.y, b.y, c.x)), fmaf(a.x, b.y, fmaf(a.y, b.x, c.y)));
}
__device__ __forceinline__ float sigmoidf_(float v) { return __fdividef(1.0f, 1.0f + expf(-v)); }

__device__ __forceinline__ void bulk_prefetch(const void* src, uint32_t bytes) {
    asm volatile(ONE "cp.async.bulk.prefetch.L2.global [%0], %1; }" ::"l"(src), "r"(bytes) : "memory");
}
__device__ __forceinline__ void bulk_store(void* dst, uint32_t src, uint32_t bytes) {
    asm volatile(ONE "cp.async.bulk.global.shared::cta.bulk_group [%0], [%1], %2; }" ::"l"(dst), "r"(src), "r"(bytes) : "memory");
}
__device__ __forceinline__ void stsm4(uint32_t a, uint32_t x, uint32_t y, uint32_t z, uint32_t w) {
    asm volatile("stmatrix.sync.aligned.m8n8.x4.shared.b16 [%0], {%1,%2,%3,%4};" ::"r"(a), "r"(x), "r"(y), "r"(z), "r"(w) : "memory");
}
__device__ __forceinline__ uint4 ldsm4(uint32_t a) {
    uint4 v;
    asm volatile("ldmatrix.sync.aligned.m8n8.x4.shared.b16 {%0,%1,%2,%3}, [%4];" : "=r"(v.x), "=r"(v.y), "=r"(v.z), "=r"(v.w) : "r"(a) : "memory");
    return v;
}
__device__ __forceinline__ void stg4_unless(float* p, float a, float b, float c, float d, uint32_t skip) {
    asm volatile("{ .reg .pred p; setp.eq.u32 p, %5, 0; @p st.global.v4.f32 [%0], {%1,%2,%3,%4}; }" ::"l"(p), "f"(a), "f"(b), "f"(c), "f"(d), "r"(skip) : "memory");
}
__device__ __forceinline__ void red4(float* p, float a, float b, float c, float d) {
    asm volatile("red.global.add.v4.f32 [%0], {%1,%2,%3,%4};" ::"l"(p), "f"(a), "f"(b), "f"(c), "f"(d) : "memory");
}

#define TT0 2900
#define PER 514
#define PCUT 60
#define PFIN 360
#define PF0 1500
#define PFX_PACE 400
#define PF1 700
#define T2 300
#define P2 520
#define G0 450
#define R0 2100
#define R_PACE 350
#define W_SHIFT 250
#define PROMO CU_TENSOR_MAP_L2_PROMOTION_L2_256B
#define POLL_S 0
#define ST_TOL 100
#define ST_SHIFT 300
#define CLK_NS 420
#define MARGIN 150
#define BP1 10
#define NDUMP 4
#define HP NDUMP
#define DNL 1
#define AE 6
#define AG0 900
#define AB 16
#define HGE 39
constexpr uint32_t duration(int i) { return PER + (i >= RE0 && i < RE0 + 4 ? 72 : 0) + (i >= GU0 && i < GU0 + 32 ? 36 : 0); }
constexpr uint32_t cmax(uint32_t a, uint32_t b) { return a > b ? a : b; }
constexpr uint32_t issue_time(int i) {
    return i <= NST ? TT0 : i < XE ? issue_time(i - 1) + duration(i - NST) - (i >= XE - 3 && i > GU0 + 36 ? PCUT : 0) : issue_time(XE - 1) + cmax((i - XE + 1) * PFIN, (i - XE) * 512);
}
template <int I> struct Sched { static constexpr uint32_t t = issue_time(I); };
template <int LO, int HI, class F>
__device__ __forceinline__ void for_entries(uint32_t base, F body) {
    constexpr uint32_t per = Sched<LO + 1>::t - Sched<LO>::t;
    static_assert(Sched<HI - 1>::t - Sched<LO>::t == (HI - 1 - LO) * per, "period");
    uint32_t tt = base + Sched<LO>::t;
#pragma unroll 1
    for (int i = LO; i < HI; i++) {
        body(i, tt);
        tt += per;
    }
}

struct Ring { uint32_t prev; int slot; };
struct NoHook { __device__ void operator()() const {} };
template <int TA, int SM, class H = NoHook>
__device__ __forceinline__ void run_entries(Ring& r, int lo, int hi, float (&accA)[64], float (&accB)[64], float (&small)[4],
                                            bool fresh = false, bool sfresh = false, H released = H()) {
    const uint64_t d0 = make_desc(sb);
    const bool leader = (threadIdx.x & 31) == 0;
#pragma unroll 1
    for (int i = lo; i < hi; i++) {
        const uint32_t bar = sb + OFF_FULL + 8 * i;
        const uint64_t da = d0 + (uint64_t)(r.slot * (SLOT >> 4));
        const int n = i - (SM == 1 ? RE0 : GU0);
        const uint64_t dw = SM == 1 ? d0 + (uint64_t)((OFF_W >> 4) + n * 512)
                                    : (((uint64_t)2 << 62) | ((uint64_t)32 << 32) | (128u << 16) | ((sb + OFF_W) >> 4)) + (uint64_t)((n & 7) * 256);
        const uint64_t dt8 = d0 + (uint64_t)((OFF_XS >> 4) + (SM == 1 ? n * 64 : (n >> 1) * 64 + (n & 1) * 4));
        r.slot = r.slot == NST - 1 ? 0 : r.slot + 1;
        mbar_wait(bar);
        KSTAMP(i);
        wgmma_fence();
#pragma unroll
        for (int kk = 0; kk < 4; kk++) {
            wgmma_n128<TA>(accA, da + kk * (TA ? 128 : 2), da + 1024 + kk * 2, kk > 0 || !fresh);
            if (SM == 1) wgmma_n8<0>(small, dw + kk * 2, dt8 + kk * 2, kk > 0 || !sfresh);
            if (SM == 2 && (kk & 1)) wgmma_n8<1>(small, dw + (kk >> 1) * 64, dt8 + (kk >> 1) * 2, kk > 1 || !sfresh);
            wgmma_n128<TA>(accB, da + 512 + kk * (TA ? 128 : 2), da + 1024 + kk * 2, kk > 0 || !fresh);
            if (kk == 1) {
                wgmma_commit();
                wgmma_wait<1>();
                if (leader) mbar_arrive(r.prev);
                released();
            }
        }
        wgmma_commit();
        r.prev = bar + (OFF_EMPTY - OFF_FULL);
        fresh = sfresh = false;
    }
}
template <int HALF, int I>
__device__ __forceinline__ void run_small(float (&acc)[64]) {
    const uint64_t da = make_desc(sb) + (slot_off(I) >> 4);
    KSTAMP(I + HALF * (NENT - FIN));
    wgmma_fence();
#pragma unroll
    for (int kk = 0; kk < 4; kk++) wgmma_n128<1>(acc, da + HALF * 512 + kk * 128, da + 1024 + kk * 2, kk > 0 || !(HALF && I == FIN));
    wgmma_commit();
}
template <int V> struct Int { __host__ __device__ constexpr operator int() const { return V; } };
template <int N, class F> __device__ __forceinline__ void static_for(F f) {
    if constexpr (N > 0) { static_for<N - 1>(f); f(Int<N - 1>()); }
}

template <bool BY_SMID>
__global__ void __launch_bounds__(384, 1)
fused_kernel(const __grid_constant__ Params prm, const __grid_constant__ CUtensorMap mX, const __grid_constant__ CUtensorMap mB, const __grid_constant__ CUtensorMap mCre,
             const __grid_constant__ CUtensorMap mCim, const __grid_constant__ CUtensorMap mW,
             const __grid_constant__ CUtensorMap mWd, const __grid_constant__ CUtensorMap mXr, const __grid_constant__ CUtensorMap mXe) {
    extern __shared__ __align__(1024) uint8_t smem[];
    const uint32_t cstart = clk32();
    const int tid = threadIdx.x, lane = tid & 31;
    uint32_t id = blockIdx.x;
    if (BY_SMID) asm volatile("mov.u32 %0, %%smid;" : "=r"(id));
    {
        const uint32_t o = (tid * 2056) & 0x7880, b = (id & 127) * 8192;
        asm volatile("{ .reg .pred p, q; setp.lt.u32 p, %3, 32; setp.eq.u32 q, %4, 0;\n"
                     "@q prefetch.global.L2 [%1]; @p prefetch.global.L2 [%0]; @q prefetch.global.L2 [%2]; }"
                     ::"l"((const char*)prm.x + (b * 4 + o)), "l"((const char*)prm.b_re + (b + o)), "l"((const char*)prm.b_im + (b + o)), "r"(tid), "r"(tid & ~19) : "memory");
    }
    const int warp = __shfl_sync(0xffffffffu, tid >> 5, 0);
    gap();
    int cta;
    asm("{ .reg .pred p; .reg .u32 a, b, u, q;\n"
        "and.b32 a, %1, 14; shl.b32 a, a, 3; shr.u32 b, %1, 3; and.b32 b, b, 6; add.u32 a, a, b;\n"
        "and.b32 u, %1, 62; mul.lo.u32 q, u, 37; shr.u32 q, q, 9; shl.b32 u, u, 3; mad.lo.u32 u, q, -110, u; add.u32 u, u, 24;\n"
        "setp.lt.u32 p, %1, 64; selp.u32 a, a, u, p; lop3.b32 a, a, %1, 1, 0xF8;\n"
        "setp.lt.u32 p, %1, 124; selp.u32 b, 8, -116, p; add.u32 b, b, %1; setp.lt.u32 p, %1, 120; selp.u32 %0, a, b, p; }" : "=r"(cta) : "r"(id));
    const int chunk = (cta >> 5) * 4 + ((cta >> 2) & 3);
    const int dt = ((cta >> 4) & 1) * 4 + (cta & 3);
    if ((warp | (cta & NCTA)) == 5) {
        mbar_init_n<2>(sb + OFF_FULL, 1);
        tma5b(sb, &mB, 0, dt * 4, sb + OFF_FULL);
        gap();
        tma4(sb + 2 * ABYTES, &mX, 0, chunk * 64, sb + OFF_FULL);
    }
    if (cta >= NCTA) {
        if (smem_u32(smem) != sb) __trap();
        if (tid == 0) wait_count_slow(&prm.s->cnt[0], (atomicAdd(&prm.s->cnt[0], 1u) / NGRID + 1) * NGRID);
        return;
    }
    const bool has_gu = cta >= 16;
    constexpr uint32_t full = sb + OFF_FULL, empty = sb + OFF_EMPTY;
    constexpr uint32_t raw = full + 8 * 32;
    constexpr uint32_t bar_hraw = full + 8 * 97, bar_xs = full + 8 * 98, bar_xb = full + 8 * 100, bar_xa = full + 8 * 101,
        bar_retry = full + 8 * 102, bar_out = full + 8 * 104;
    constexpr uint32_t bar_base = empty - 64, bar_init3 = empty - 56, bar_rdone = empty - 48, bar_order0 = empty - 40, bar_init2 = empty - 32,
        bar_vec = empty - 24, bar_epoch = empty - 16, bar_dummy = empty - 8, bar_xs0 = empty + 8 * 69,
        bar_zero = empty + 8 * 70, bar_xafree = empty + 8 * 71, bar_order2 = empty + 8 * 72, bar_dn = empty + 8 * 73, bar_fp = empty + 8 * 74,
        bar_accb = empty + 8 * 76, bar_xbfree = empty + 8 * 78, bar_fold = empty + 8 * 79, bar_st = empty + 8 * 80,
        bar_order1 = empty + 8 * 67, bar_cand = empty + 8 * 68;

    if (warp == 5) {
        tma5b(sb + SLOT, &mB, 64, dt * 4, full + 8);
        tma4(sb + SLOT + 2 * ABYTES, &mX, 64, chunk * 64, full + 8);
        STAMP(31);
        if (lane < 2) mbar_expect_tx(full + 8 * lane, SLOT);
        __syncwarp();
        named_bar(0, 256);
#pragma unroll 1
        for (int i = 2; i < NST; i++) {
            pace_until(cstart + T2 + i * P2);
            tma5b(sb + i * SLOT, &mB, i * 64, dt * 4, full + 8 * i);
            tma4(sb + i * SLOT + 2 * ABYTES, &mX, i * 64, chunk * 64, full + 8 * i);
            STAMPIF(i == 4, 1);
        }
    } else if (warp == 4) {
        mbar_init_n<12>(bar_init2, 4);
        asm volatile("bar.arrive 0, 256;" ::: "memory");
        mbar_init_n<4>(bar_base, 4);
        mbar_init_n<8>(empty + 64, 4);
        *reinterpret_cast<uint2*>(smem + OFF_KEYS + 16) = make_uint2(0, 0);
        asm volatile("bar.arrive 1, 64;" ::: "memory");
        asm volatile("bar.arrive 5, 96;" ::: "memory");
        asm volatile("bar.arrive 6, 96;" ::: "memory");
        mbar_init_n<32>(full + 256, 3);
        if (lane < 2) mbar_arrive(bar_init2);
    } else if ((warp >> 1) == 3) {
        if (warp == 6) {
            mbar_init_n<8>(full + 16, 1);
            if (lane >= 2 && lane < 10) mbar_expect_tx(full + 8 * lane, lane >= RE0 && lane < RE0 + 4 ? SLOT + ABYTES : SLOT);
            __syncwarp();
            asm volatile("bar.arrive 0, 256;" ::: "memory");
        }
        const char* pf0 = (warp & 1) ? (const char*)((cta & 64) ? prm.b_im : prm.b_re) + (cta & 63) * 16384 : (const char*)prm.x + cta * 32768;
        pace_until(cstart + PF1);
        asm volatile("prefetch.global.L2 [%0];" ::"l"(pf0 + (lane & (30 >> (warp & 1) & 30)) * 1024 + (lane & 1) * 128 + 256));
        const int i0 = warp == 6 ? 10 : 21;
        mbar_init_n<11>(full + 8 * i0, 1);
        if (lane >= i0 && lane < i0 + 11) mbar_expect_tx(full + 8 * lane, lane >= GU0 && has_gu ? SLOT + WBYTES : SLOT);
        mbar_init_n<24>(full + 512 + 192 * (warp & 1), 1);
        named_bar(5, 96);
        if (lane == 0) mbar_arrive(bar_init2);
        STAMP(21);
    }
    __syncwarp();

    if (warp >= 8) {
        asm volatile("setmaxnreg.dec.sync.aligned.u32 72;");
        const uint32_t c0 = cstart;
        uint64_t stream;
        asm volatile("createpolicy.fractional.L2::evict_first.b64 %0, 1.0;" : "=l"(stream));
        const int dc = (cta & 15) * 64, dr = (cta >> 4) * 448;
        auto gutile = [&](int i) {
            const int n = i + 3 - GU0;
            if (has_gu) tma3s(sb + OFF_W + (n & 7) * WBYTES, &mW, cta * 32 - 512, n * 32, full + 8 * (i + 3), stream);
        };
        if (warp == 8) {
            named_bar(0, 256);
            asm volatile("prefetch.tensormap [%0];" ::"l"(&mXr));
#pragma unroll 1
            for (int u = 0; u < 2; u++) {
                sleep_until(c0 + R0 + u * R_PACE);
                tma3(sb + OFF_W + u * ABYTES, &mXr, u * 256, cta * 16, full + 8 * (RE0 + u));
            }
            uint32_t dst = sb;
            auto gemm1 = [&](int i, uint32_t tt) {
                mbar_wait(empty + 8 * (i - NST));
                LATE(i, tt);
                pace_until(tt);
                tma5b(dst, &mB, (i & 15) * 64, (i >> 4) * 64 + dt * 4, full + 8 * i);
                tma4(dst + 2 * ABYTES, &mX, (i & 15) * 64, chunk * 64, full + 8 * i);
                dst = dst == sb + (NST - 1) * SLOT ? sb : dst + SLOT;
            };
            mbar_wait(bar_init2);
            uint32_t tt = c0 + TT0;
#pragma unroll 1
            for (int i = NST; i < AB; i++) {
                gemm1(i, tt);
                if (i < 7) tma3(sb + OFF_W + (i - 3) * ABYTES, &mXr, (i - 3) * 256, cta * 16, full + 8 * (i + 1));
                tt += (i & ~3) == RE0 + 4 ? PER + 72 : PER;
            }
            mbar_wait(bar_base);
            const uint32_t base = uni(lds32(sb + OFF_EPOCH + 8));
            tt = base + Sched<AB>::t;
#pragma unroll 1
            for (int i = AB; i < 32; i++) {
                gemm1(i, tt);
                tt += i >= GU0 + 4 ? PER + 36 : PER;
            }
            const char* hsrc = reinterpret_cast<const char*>(prm.s->h) + (size_t)chunk * 524288;
            auto gemm2 = [&](int i, uint32_t d, int freed, uint32_t tt) {
                mbar_wait(empty + 8 * freed);
                LATE(i, tt);
                pace_until(tt);
                bulk_load(d, hsrc, 2 * ABYTES, raw + 8 * i);
                tma5(d + 2 * ABYTES, (i & 4) ? &mCim : &mCre, ((i & 3) + ((i >> 1) & 12)) * 64, dt * 8, full + 8 * i);
                hsrc += 2 * ABYTES;
            };
            for_entries<32, GU0 + 29>(base, [&](int i, uint32_t tt) {
                gemm2(i, dst, i - NST, tt);
                gutile(i);
                dst = dst == sb + (NST - 1) * SLOT ? sb : dst + SLOT;
            });
            for_entries<GU0 + 29, GU0 + 37>(base, [&](int i, uint32_t tt) {
                gemm2(i, dst, i - NST, tt);
                const int n = i - GU0 - 29;
                if ((n & 5) == 1) tma5(sb + OFF_W + (n & 2) * (ABYTES / 2), &mXe, dt * 128 + (n & 2) * 32, chunk * 64, bar_xa);
                else if (n < 6) asm volatile(ONE "cp.async.bulk.prefetch.tensor.2d.L2.global [%0, {%1, %2}]; }" ::"l"(&mWd), "r"(dc), "r"(dr + 64 * (n < 4 ? 3 + n / 2 : n + 1)) : "memory");
                dst = dst == sb + (NST - 1) * SLOT ? sb : dst + SLOT;
            });
            static_for<NENT - GU0 - 37>([&](auto u) {
                constexpr int i = GU0 + 37 + u;
                if (i == 60) mbar_wait(bar_out + 56);
                gemm2(i, sb + slot_off(i), i < XE ? i - NST : i == XE ? 71   : i - NST - 1, base + Sched<i>::t);
            });
            STAMP(4);
        } else if (warp == 9) {
#pragma unroll
            for (int u = 0; u < 8; u++) {
                const int row = (u >> 2) * 4 + (lane >> 3);
                asm volatile("cp.async.cg.shared.global [%0], [%1], 16;" ::"r"(sb + OFF_XS + (u & 3) * 1024 + row * 128 + (((lane & 7) ^ row) << 4)),
                             "l"((const char*)(u < 4 ? prm.w_r : prm.gate_w) + (u & 3) * 512 + lane * 16) : "memory");
            }
            uint32_t ticket = 0;
            if (lane == 0) ticket = atomicAdd(&prm.s->cnt[0], 1u);
            named_bar(1, 64);
            if (lane == 0) *reinterpret_cast<volatile uint32_t*>(smem + OFF_EPOCH) = ticket / NGRID;
            __syncwarp();
            if (lane < 4) mbar_arrive(bar_epoch);
            asm volatile("cp.async.wait_all;" ::: "memory");
            asm volatile("fence.proxy.async.shared::cta;" ::: "memory");
            __syncwarp();
            if (lane < 4) mbar_arrive(bar_vec);
            STAMP(18);
#pragma unroll 1
            for (int i = 4; i < 22; i++) mbar_init_n<4>(empty + 32 * i, 4, i >= 6 && i < 13);
            if (lane < 2) mbar_arrive(bar_init3);
            STAMP(19);
            mbar_wait(bar_cand);
            {
                const uint32_t* list = reinterpret_cast<const uint32_t*>(smem + OFF_LIST);
                const int n = (int)lds32(sb + OFF_KEYS + 16);
#pragma unroll 1
                for (int i0 = 0; i0 < n; i0 += 32) {
                    const uint32_t k = list[i0 + lane];
                    int rank = 0;
#pragma unroll 2
                    for (int o = 0; o < n; o += 4) {
                        const uint4 l4 = *reinterpret_cast<const uint4*>(list + o);
                        rank += (l4.x > k) + (l4.y > k) + (l4.z > k) + (l4.w > k);
                    }
                    if (rank < 8) reinterpret_cast<uint32_t*>(smem + OFF_SEL)[rank] = k;
                }
                __syncwarp();
                STAMP(6);
                const uint32_t key = lds32(sb + OFF_SEL + 4 * (lane & 7)), tok = ~key & 2047u, tag = lds32(sb + OFF_EPOCH) + 1;
                const uint32_t ta = __shfl_sync(0xffffffffu, tok, lane >> 3), tb = __shfl_sync(0xffffffffu, tok, 4 + (lane >> 3));
                const uint32_t da = sb + OFF_XS + (lane >> 3) * 128 + (((lane & 7) ^ (lane >> 3)) << 4), db = (da ^ 64) + 512;
                const char *sa = (const char*)prm.x + ta * 2048 + (lane & 7) * 16, *sc = (const char*)prm.x + tb * 2048 + (lane & 7) * 16;
#pragma unroll
                for (int u = 0; u < 16; u++) {
                    asm volatile("cp.async.cg.shared.global [%0], [%1], 16;" ::"r"(da + u * 1024), "l"(sa + u * 128) : "memory");
                    asm volatile("cp.async.cg.shared.global [%0], [%1], 16;" ::"r"(db + u * 1024), "l"(sc + u * 128) : "memory");
                    if (u == 3) {
                        asm volatile("cp.async.wait_all;" ::: "memory");
                        asm volatile("fence.proxy.async.shared::cta;" ::: "memory");
                        __syncwarp();
                        if (lane < 4) mbar_arrive(bar_xs0);
                        STAMP(17);
                    }
                }
                if ((tok >> 7) == (uint32_t)chunk) {
                    float4* zp = reinterpret_cast<float4*>(prm.out + tok * D_ + dt * 128) + (lane >> 3) * 2;
#pragma unroll
                    for (int u = 0; u < 8; u++) zp[(u >> 1) * 8 + (u & 1)] = make_float4(0.f, 0.f, 0.f, 0.f);
                }
                uint32_t it = 0;
                unsigned long long u;
                do {
                    u = ld_relaxed1(&prm.s->gpack[tok >> 1]);
                    if (++it > SPIN_LIMIT) __trap();
                } while (!__all_sync(0xffffffffu, (uint32_t)(u >> 32) == tag));
                const uint32_t kb = key >> 16;
                const float r = bf_lo((kb & 0x8000u) ? (kb & 0x7FFFu) : (~kb & 0xFFFFu)), gv = (tok & 1) ? bf_hi((uint32_t)u) : bf_lo((uint32_t)u);
                reinterpret_cast<float*>(smem + OFF_FAC)[lane & 7] = rbf(1.0f - gv) * rbf(sigmoidf_(r));
                asm volatile("cp.async.wait_all;" ::: "memory");
                asm volatile("fence.proxy.async.shared::cta;" ::: "memory");
                __syncwarp();
                if (lane == 0) mbar_arrive(bar_xs);
                STAMP(7);
            }
            char* hd = reinterpret_cast<char*>(prm.s->h) + (size_t)chunk * 524288 + (dt >> 1) * 16384 + (dt & 1) * 4096;
            mbar_wait(bar_base);
            const uint32_t cb = uni(lds32(sb + OFF_EPOCH + 8)) + ST_SHIFT;
            uint32_t tt = cb + Sched<GU0 + 4>::t;
#pragma unroll 1
            for (int np = 0; np < 16; np++) {
                if (!(np & (np & 4 ? 1 : 2))) mbar_wait(bar_st + 4 * (np & 12) + ((np & 3) ? 8 : 0));
                const uint32_t now = clk32() - ST_TOL;
#pragma unroll 1
                while ((int)(tt - now) < 0) tt += PER + 36;
                const uint32_t src = sb + OFF_STG + (np & 3) * 4096;
                pace_until(tt);
                bulk_store(hd, src, 4096);
                asm volatile("cp.async.bulk.commit_group;" ::: "memory");
                if (np & 2) {
                    if (np & 1) asm volatile("cp.async.bulk.wait_group.read 0;" ::: "memory");
                    else asm volatile("cp.async.bulk.wait_group.read 1;" ::: "memory");
                    __syncwarp();
                    const uint32_t u8 = 4 * (np & 12) + 8 * (np & 1);
                    if (lane < 2) mbar_arrive(lane ? (np < 15 ? empty + 8 * 27 + 4 * u8 : bar_dummy) : bar_out + u8);
                }
                STAMPIF(np & 2, 8 + ((np >> 1) & 6) + (np & 1));
                hd += (np & 1) ? 65536 - 8192 : 8192;
                tt += PER + 36;
            }
#pragma unroll 1
            for (int u = 0; u < 2; u++) {
                pace_until(tt);
                tma5(sb + OFF_STG + u * ABYTES, &mXe, dt * 128 + u * 64, chunk * 64 + 8, bar_xb);
                tt += PER + 36;
            }
            wait_count(&prm.s->cnt[32], (lds32(sb + OFF_EPOCH) + 1) * NCTA);
            auto load_hid = [&]() {
                if (lane == 0) mbar_expect_tx(bar_hraw, 7168);
                bulk_load(sb + OFF_XS, prm.s->hid + dr, 7168, bar_hraw);
            };
            static_for<7>([&](auto u) {
                if (u != 2) mbar_wait(u == 1 ? bar_xbfree : empty + 8 * (u == 0 ? GU0 + 31 : u == 3 ? FIN + DNL : FIN - 2 + u));
                if (u < 3) sleep_until(cb + Sched<GU0 + HGE - 2 + u>::t);
                if (u == 2) load_hid();
                tma2(sb + dn_off(u), &mWd, dc, dr + u * 64, bar_dn, stream);
                if (u == 2) {
                    const uint32_t t2 = lds32(sb + OFF_EPOCH) + 1, tagw = (t2 & 1) | ((t2 & 2) << 15);
#pragma unroll 1
                    for (uint32_t it = 0;; it++) {
                        mbar_wait(bar_hraw, it & 1);
                        uint32_t bad = 0;
#pragma unroll
                        for (int i = 0; i < 14; i++) bad |= lds32(sb + OFF_XS + i * 512 + lane * 16 + (lane >> 3) * 4) ^ tagw;
                        if (__all_sync(0xffffffffu, (bad & 0x00010001u) == 0)) break;
                        if (it > SPIN_LIMIT) __trap();
                        load_hid();
                    }
                    if (lane < 4) mbar_arrive(bar_zero);
                    STAMP(48);
                }
            });
            STAMP(27);
        } else {
            named_bar(6, 96);
            if (warp == 10) {
                const char* pb = (const char*)((cta & 64) ? prm.b_im : prm.b_re) + (cta & 63) * 16384;
                const char* pf = (lane < 16 ? (const char*)prm.x + cta * 32768 : pb) + (lane & 15) * 2048 + 512;
#pragma unroll 1
                for (int k = 0; k < 11; k++) {
                    sleep_until(c0 + PF0 + k * PFX_PACE);
                    if (lane < 16 ? k < 6 : lane < 24 && !(k & 1)) prefetch_l2(pf + k * (lane < 16 ? 256 : 128));
                }
                static_for<12>([&](auto k) {
                    sleep_until(c0 + Sched<BP1 + k>::t + ST_SHIFT);
                    bulk_prefetch((k < 4 ? pb + 1048576 : (const char*)(k < 8 ? prm.c_re : prm.c_im) + cta * 16384) + (k & 3) * 4096, 4096);
                    if (k == 4) { mbar_wait(bar_init2); mbar_wait(bar_init3); }
                    if (k >= 4 && lane < 8) mbar_expect_tx(full + 8 * (8 * k + lane), 8 * k + lane < GU0 + 32 && has_gu ? 2 * ABYTES + WBYTES : 2 * ABYTES);
                });
                asm volatile("prefetch.tensormap [%0];" ::"l"(&mCre));
                asm volatile("prefetch.tensormap [%0];" ::"l"(&mCim));
                asm volatile("prefetch.tensormap [%0];" ::"l"(&mWd));
                asm volatile("prefetch.tensormap [%0];" ::"l"(&mXe));
                if (lane < 2) mbar_expect_tx(bar_xb + 8 * lane, 2 * ABYTES);
                mbar_wait(bar_xs);
                mbar_wait(bar_st);
                if (lane == 0) red_release(&prm.s->cnt[32]);
                __syncwarp();
                STAMP(22);
            } else {
                asm volatile("prefetch.tensormap [%0];" ::"l"(&mW));
                mbar_wait(bar_epoch);
                const uint32_t tag = lds32(sb + OFF_EPOCH) + 1;
                st_cell(prm.s->time + cta, 0, 0, 0, 0, lane == 0);
                mbar_wait(empty + 8 * AE);
                uint32_t gown, tm[4][4] = {}, it = 0;
                asm volatile("mov.u32 %0, %%globaltimer_lo;" : "=r"(gown));
                const uint32_t town = clk32();
                st_cell(prm.s->time + cta, tag, town, gown, 0, lane == 0);
                sleep_until(town + AG0);
                do {
#pragma unroll
                    for (int m = 0; m < 4; m++) ld_cell(tm[m], prm.s->time + ((cta & 96) ^ (32 * m)) + lane);
                    if (++it > SPIN_LIMIT) __trap();
                } while (!__all_sync(0xffffffffu, tm[0][0] == tag && tm[1][0] == tag && tm[2][0] == tag && tm[3][0] == tag));
                const int last = __reduce_max_sync(0xffffffffu, max(max((int)(tm[0][2] - gown), (int)(tm[1][2] - gown)), max((int)(tm[2][2] - gown), (int)(tm[3][2] - gown))));
                const uint32_t cand = tm[0][1] + ((min((int)(gown + last - tm[0][2]), 4000) * CLK_NS) >> 8);
                const uint32_t b0 = __shfl_sync(0xffffffffu, cand, cta & 16), b1 = __shfl_sync(0xffffffffu, cand, cta & 30);
                const uint32_t base = (b0 - b1 + 400u < 800u ? b0 : b1) + MARGIN - Sched<AE + NST>::t;
                *reinterpret_cast<volatile uint32_t*>(smem + OFF_EPOCH + 8) = base;
                mbar_wait(bar_init3);
                if (lane < 4) mbar_arrive(bar_base);
                STAMP(23);
                const uint32_t cb = base + W_SHIFT;
                auto early = [&](int i, uint32_t tt) {
                    mbar_wait(empty + 8 * (i - NST));
                    pace_until(tt);
                    gutile(i);
                };
                for_entries<GU0 - 3, GU0 + 4>(cb, early);
                for_entries<GU0 + 4, 32>(cb, early);
            }
            mbar_wait(bar_epoch);
            const uint32_t t2 = lds32(sb + OFF_EPOCH) + 1, tagw = (t2 & 1) | ((t2 & 2) << 15), half = (warp & 1) * ABYTES;
            const uint32_t lo = half + lane * 32 + (lane & 4) * 4 + (lane >> 3) * 4, retry = bar_retry + (warp & 1) * 8;
            const bool leader = lane == 0;
            uint32_t slot = sb + (32 % NST) * SLOT, rpar = 0;
#pragma unroll 1
            for (int i = 32; i < NENT; i++) {
                const uint32_t src = i == XE ? sb + OFF_W : slot;
                if (i != XE) slot = slot == sb + (NST - 1) * SLOT ? sb : slot + SLOT;
                auto current = [&]() {
                    uint32_t v[8];
#pragma unroll
                    for (int u = 0; u < 8; u++) v[u] = lds32(src + lo + u * 1024);
#pragma unroll
                    for (int u = 0; u < 8; u += 2) asm("lop3.b32 %0, %0, %1, %2, 0x7e;" : "+r"(v[u]) : "r"(v[u + 1]), "r"(tagw));
                    return __all_sync(0xffffffffu, ((v[0] | v[2] | v[4] | v[6]) & 0x00010001u) == 0);
                };
                mbar_wait(raw + 8 * i);
                if (!current()) {
#pragma unroll 1
                    for (uint32_t it = 0;; it++) {
                        if (it > SPIN_LIMIT) __trap();
                        STAMP(16);
                        if (leader) mbar_expect_tx(retry, ABYTES);
                        bulk_load(src + half, reinterpret_cast<const char*>(prm.s->h) + (size_t)chunk * 524288 + (i - 32) * 16384 + half, ABYTES, retry);
                        mbar_wait(retry, rpar);
                        rpar ^= 1;
                        if (current()) break;
                    }
                }
                if (leader) mbar_arrive(full + 8 * i);
            }
        }
    } else {
        asm volatile("setmaxnreg.inc.sync.aligned.u32 216;");
        const int wg = warp >> 2, w = warp & 3, g = lane >> 2, c = lane & 3, at = tid & 127;
        float facc[4];
        float2 a[2], m0[2], a32[2], a128[2];
        auto load_const = [&]() {
            const float2* cp = reinterpret_cast<const float2*>(smem + OFF_CONST) + wg * 64 + w * 8 + g;
#pragma unroll
            for (int h = 0; h < 2; h++) { a[h] = cp[32 * h]; m0[h] = cp[128 + 32 * h]; a32[h] = cp[256 + 32 * h]; a128[h] = cp[384 + 32 * h]; }
        };
        if (wg == 0) {
            named_bar(0, 256);
            STAMPIF(tid == 0, 20);
        } else {
            const int pc = (at >> 5) * 256 + dt * 32 + (at & 31);
            const float lr = __bfloat162float(prm.lam_re[pc]), li = __bfloat162float(prm.lam_im[pc]), ld = __bfloat162float(prm.log_dt[pc]);
            const uint32_t dk = __ldg(reinterpret_cast<const uint32_t*>(prm.dskip + dt * 128) + (at & 63));
#pragma unroll
            for (int i = 0; i < 4; i++) sts128(sb + OFF_LIST + i * 2048 + at * 16, 0u, 0u, 0u, 0u);

            {
                reinterpret_cast<uint32_t*>(smem + OFF_DK)[at & 63] = dk;
                const float dtv = rbf(expf(ld));
                const float er = expf(dtv * lr);
                float sn, cs;
                sincospif(dtv * li * 0.318309886183790672f, &sn, &cs);
                const float ar = er * cs, ai = er * sn;
                const float nr = ar - 1.0f, ni = ai;
                const bool big = fabsf(lr) >= fabsf(li);
                const float t = (big ? li : lr) / (big ? lr : li), dn = big ? lr + li * t : lr * t + li;
                const float cr = (big ? nr + ni * t : nr * t + ni) / dn, ci = (big ? ni - nr * t : ni * t - nr) / dn;
                float2* cp = reinterpret_cast<float2*>(smem + OFF_CONST) + at;
                float2 pw = make_float2(ar, prm.swapped ? ai : -ai);
                cp[0] = pw;
                cp[128] = make_float2(prm.swapped ? -2.f * cr : 2.f * cr, -2.f * ci);
#pragma unroll
                for (int i = 1; i <= 7; i++) {
                    pw = cmul(pw, pw);
                    if (i == 5) cp[256] = pw;
                    if (i == 7) cp[384] = pw;
                }
                __syncwarp();
            }
            named_bar(2, 128);
            load_const();
            mbar_wait(bar_epoch);
            const uint32_t tag = *reinterpret_cast<volatile uint32_t*>(smem + OFF_EPOCH) + 1;
            asm volatile("st.relaxed.gpu.global.b64 [%0], %1;" ::"l"(&prm.s->carry[(chunk >> 2) * 4096 + pc * 4 + (chunk & 3)]), "l"((unsigned long long)(tag + 2)) : "memory");
            if (w == 2) st_cell(lane < 4 ? (uint4*)prm.s->rpack + cta * 4 + lane : (uint4*)prm.s->gpack + cta * 4 + (lane & 3), 0, 0, 0, 0, lane < 8);
            {
                const uint32_t nt = ((tag & 1) | ((tag & 2) << 15)) ^ 0x00010001u;
                st_cell(prm.s->hid + cta * 32 - 512 + lane, nt, nt, nt, nt, has_gu && w == 3);
            }
            named_bar(2, 128);
            if (at < 2) mbar_arrive(bar_init3);
            unsigned long long* pub = (w ? prm.s->gpack : prm.s->rpack) + cta * 8 + lane;
            asm volatile("" : "+l"(pub));
            STAMPIF(lane == 0, 52);
            mbar_wait(bar_rdone);

            if (w < 2) {
                const float2* red = reinterpret_cast<const float2*>(smem + OFF_RED) + w * 8 + (lane & 7);
                const float2 r0 = red[0], r1 = red[16], r2 = red[32], r3 = red[48];
                const float v0 = (r0.x + r1.x) + (r2.x + r3.x), v1 = (r0.y + r1.y) + (r2.y + r3.y);
                uint32_t pk2;
                if (w == 0) {
                    pk2 = pack_bf(v0, v1);
                    pk2 ^= (((pk2 >> 15) & 0x00010001u) * 0x7FFFu) ^ 0x80008000u;
                } else pk2 = pack_bf(sigmoidf_(rbf(v0)), sigmoidf_(rbf(v1)));
                if (lane < 8) asm volatile("st.relaxed.gpu.global.b64 [%0], %1;" ::"l"(pub), "l"(((unsigned long long)tag << 32) | pk2) : "memory");
                __syncwarp();
            }
            STAMPIF(at == 0, 24);
            uint32_t it = 0, pr[8], g1;
            mbar_wait(bar_init3);
            sleep_until(clk32() + (w < 2 ? G0 : G0 + 250));
            while (true) {
                bool ok = true;
#pragma unroll
                for (int k = 0; k < 4; k++) {
                    const ulonglong2 u = ld_relaxed2(&prm.s->rpack[k * 256 + 2 * at]);
                    ok = ok && (uint32_t)(u.x >> 32) == tag && (uint32_t)(u.y >> 32) == tag;
                    pr[2 * k] = (uint32_t)u.x; pr[2 * k + 1] = (uint32_t)u.y;
                }
                const unsigned long long u1 = ld_relaxed1(&prm.s->gpack[chunk * 64 + (at & 63)]);
                ok = ok && (uint32_t)(u1 >> 32) == tag;
                g1 = (uint32_t)u1;
                if (__all_sync(0xffffffffu, ok)) break;
                if (++it > SPIN_LIMIT) __trap();
            }
            STAMPIF(lane == 0, 25);
            uint32_t m = __vmaxu2(__vimax3_u16x2(__vimax3_u16x2(pr[0], pr[1], pr[2]), pr[3], pr[4]), __vimax3_u16x2(pr[5], pr[6], pr[7]));
            m = (max(m, m << 16) & 0xFFFF0000u) | (uint32_t)lane;
            const uint32_t m1 = __reduce_max_sync(0xffffffffu, m), m2 = __reduce_max_sync(0xffffffffu, m == m1 ? 0u : m);
            uint32_t* keys = reinterpret_cast<uint32_t*>(smem + OFF_KEYS);
            if (lane == 0) keys[w] = m2;
            sts128(sb + OFF_XS + 4096 + at * 16, pr[0], pr[1], pr[2], pr[3]);
            sts128(sb + OFF_XS + 6144 + at * 16, pr[4], pr[5], pr[6], pr[7]);
            *reinterpret_cast<uint32_t*>(smem + OFF_G + 4 * (at & 63)) = g1;
            named_bar(2, 128);
            const uint4 th4 = *reinterpret_cast<const uint4*>(keys);
            const uint32_t th = (max(min(min(th4.x, th4.y), min(th4.z, th4.w)) >> 16, 1u) - 1u) * 0x00010001u;
            uint32_t mask = 0;
#pragma unroll
            for (int k = 7; k >= 0; k--) mask = mask * 2 + __vminu2(__vmaxu2(pr[k], th) ^ th, 0x00010001u);
            uint32_t pos = 0;
            asm volatile("{ .reg .pred p; setp.ne.u32 p, %2, 0; @p atom.shared.add.u32 %0, [%1], %2; }" : "+r"(pos) : "r"(sb + OFF_KEYS + 16), "r"(__popc(mask)) : "memory");
            while (mask) {
                const int bit = __ffs(mask) - 1, k = bit & 7, hi = bit >> 4;
                mask &= mask - 1;
                const uint32_t sc = *reinterpret_cast<const uint16_t*>(smem + OFF_XS + 4096 + (k >> 2) * 2048 + at * 16 + (k & 3) * 4 + hi * 2);
                *reinterpret_cast<uint32_t*>(smem + OFF_LIST + 4 * pos++) = (sc << 16) | (0x8000u + 2047u - (uint32_t)((k >> 1) * 512 + 4 * at + 2 * (k & 1) + hi));
            }
            __syncwarp();
            if (lane == 0) mbar_arrive(bar_cand);
            STAMPIF(lane == 0, 26);
            mbar_wait(bar_order0);
        }

        float accA[64], accB[64];
        Ring ring = {bar_dummy, wg};
        {
            run_entries<0, 0>(ring, wg * 16, wg ? GU0 : RE0, accA, accB, facc, true);
            if (wg == 0) {
                float racc[4];
                mbar_wait(bar_vec);
                run_entries<0, 1>(ring, RE0, RE0 + 4, accA, accB, racc, false, true);
                mbar_wait(bar_init2);
                const uint32_t red = sb + OFF_RED + 4 * (w * 32 + (c >> 1) * 16 + g);
                run_entries<0, 0>(ring, RE0 + 4, RE0 + 5, accA, accB, facc, false, false, [&]() {
                    pin4(racc);
                    asm volatile("{ .reg .pred p; setp.ne.u32 p, %3, 0; @p st.shared.f32 [%0], %1; @p st.shared.f32 [%0 + 32], %2; }" ::"r"(red),
                                 "f"((w & 1) ? racc[1] : racc[0]), "f"((w & 1) ? racc[3] : racc[2]), "r"((uint32_t)((c & 1) == (w >> 1))) : "memory");
                    __syncwarp();
                    if (lane == 0) mbar_arrive(bar_rdone);
                    STAMPIF(lane == 0, 5);
                });
                run_entries<0, 0>(ring, RE0 + 5, 16, accA, accB, facc);
                if (lane == 0) mbar_arrive(bar_order0);
                mbar_wait(bar_init3);
                load_const();
                named_bar(3, 128);
            } else {
#pragma unroll
                for (int u = 0; u < 2; u++) {
                    mbar_wait(u ? bar_xs : bar_xs0);
                    run_entries<0, 2>(ring, GU0 + 8 * u, u ? 32 : GU0 + 8, accA, accB, facc, false, u == 0);
                }
                if (lane == 0) mbar_arrive(bar_order1);
            }
        }
        const uint32_t tag = *reinterpret_cast<volatile uint32_t*>(smem + OFF_EPOCH) + 1;
        const float2 a64[2] = {cmul(a32[0], a32[0]), cmul(a32[1], a32[1])};
        wgmma_wait<0>();
        pin64(accA); pin64(accB); pin4(facc);
        if (lane == 0) mbar_arrive(ring.prev);
        STAMPIF(at == 0, 28 + wg);
        GSTAMP(tid == 0, 1);

        const int tl = 32 * (g >> 1) + (g & 1) + 4 * w + 16 * wg, t0 = chunk * 128 + tl;
        float* op = prm.out + (size_t)t0 * D_ + dt * 128 + 4 * c;
        uint2 xv[8][2], dk[8];
        uint32_t gp[2], om[2], routed[2];
        auto row_setup = [&]() {
            const uint4 sa = *reinterpret_cast<const uint4*>(smem + OFF_SEL), sc = *reinterpret_cast<const uint4*>(smem + OFF_SEL + 16);
#pragma unroll
            for (int r = 0; r < 2; r++) {
                const uint32_t id = 0x8000u + 2047u - (uint32_t)(t0 + 2 * r);
                routed[r] = (uint16_t)sa.x == id || (uint16_t)sa.y == id || (uint16_t)sa.z == id || (uint16_t)sa.w == id ||
                            (uint16_t)sc.x == id || (uint16_t)sc.y == id || (uint16_t)sc.z == id || (uint16_t)sc.w == id;
                gp[r] = reinterpret_cast<const uint16_t*>(smem + OFF_G)[tl + 2 * r] * 0x00010001u;
                om[r] = pack_bf(1.0f - bf_hi(gp[r]), 1.0f - bf_hi(gp[r]));
            }
#pragma unroll
            for (int j = 0; j < 8; j++) dk[j] = lds64(sb + OFF_DK + 32 * j + 8 * c);
        };
        auto release = [&](uint32_t bar) {
            asm volatile("fence.proxy.async.shared::cta;" ::: "memory");
            __syncwarp();
            if (lane == 0) mbar_arrive(bar);
        };

        {
            const uint32_t t2 = tag & 3u;
            float2* cslot = &prm.s->carry[(wg * 512 + dt * 32 + w * 8 + g) * 4];
            const int j1 = chunk - 1 - c;
            unsigned long long v[2][4] = {{t2, t2, t2, t2}, {t2, t2, t2, t2}};
            auto poll = [&](int h) {
#pragma unroll
                for (int m = 0; m < 4; m++)
                    asm volatile("{ .reg .pred p; setp.ge.s32 p, %2, %3; @p ld.relaxed.gpu.global.b64 %0, [%1]; }"
                                 : "+l"(v[h][m]) : "l"(cslot + (j1 >> 2) * 4096 + c - m * 4096 + h * 1024), "r"(j1), "r"(4 * m) : "memory");
            };
            float2 e[2], w0[2];
            auto chain = [&](int h, int s0, int s1) {
                float (&acc)[64] = h ? accB : accA;
                if (s0 == 1) e[h] = make_float2(acc[0], acc[2]);
#pragma unroll
                for (int s = s0; s < s1; s++) {
                    const int i0 = 4 * (s >> 1) + (s & 1);
                    e[h] = cfma(make_float2(a[h].x, -a[h].y), e[h], make_float2(acc[i0], acc[i0 + 2]));
                }
                asm volatile("" : "+f"(e[h].x), "+f"(e[h].y), "+f"(accB[0]), "+f"(accB[2]));
                gap();
            };
            auto publish = [&](int h) {
                float2 f = make_float2(fmaf(m0[h].x, e[h].x, m0[h].y * e[h].y), fmaf(-m0[h].x, e[h].y, m0[h].y * e[h].x));
                float2 y = make_float2(__shfl_up_sync(0xffffffffu, f.x, 1, 4), __shfl_up_sync(0xffffffffu, f.y, 1, 4));
                if (c >= 1) f = cfma(a32[h], y, f);
                y = make_float2(__shfl_up_sync(0xffffffffu, f.x, 2, 4), __shfl_up_sync(0xffffffffu, f.y, 2, 4));
                if (c >= 2) f = cfma(a64[h], y, f);
                asm volatile("{ .reg .pred p; .reg .b64 t; setp.eq.u32 p, %3, 3; mov.b64 t, {%1, %2}; @p st.relaxed.gpu.global.b64 [%0], t; }"
                             ::"l"(cslot + (chunk >> 2) * 4096 + (chunk & 3) + h * 1024), "r"((__float_as_uint(f.x) & ~3u) | t2), "r"(__float_as_uint(f.y)), "r"(c) : "memory");
                w0[h] = make_float2(__shfl_up_sync(0xffffffffu, f.x, 1, 4), __shfl_up_sync(0xffffffffu, f.y, 1, 4));
                if (c == 0) w0[h] = make_float2(0.f, 0.f);
            };
            auto scale = [&](int h, int n0, int n1) {
                float (&acc)[64] = h ? accB : accA;
#pragma unroll
                for (int n = n0; n < n1; n++) {
                    asm volatile("{ .reg .f32 a, b, c, d, n; neg.f32 n, %4; mul.f32 a, %1, %5; mul.f32 b, %0, %5; mul.f32 c, %3, %5; mul.f32 d, %2, %5;\n"
                                 "fma.rn.f32 %0, %0, %4, a; fma.rn.f32 %1, %1, n, b; fma.rn.f32 %2, %2, %4, c; fma.rn.f32 %3, %3, n, d; }"
                                 : "+f"(acc[4 * n]), "+f"(acc[4 * n + 2]), "+f"(acc[4 * n + 1]), "+f"(acc[4 * n + 3]) : "f"(m0[h].x), "f"(m0[h].y));
                    gap();
                }
            };
            auto carry = [&](int h) {
                const float2 one = make_float2(1.f, 0.f), a256 = cmul(a128[h], a128[h]);
                float2 a512 = cmul(a256, a256), pw128 = cmul((j1 & 1) ? a128[h] : one, (j1 & 2) ? a256 : one);
                float2 pw32 = cmul((c & 1) ? a32[h] : one, (c & 2) ? a64[h] : one);
                asm volatile("" : "+f"(a512.x), "+f"(a512.y), "+f"(pw128.x), "+f"(pw128.y), "+f"(pw32.x), "+f"(pw32.y));
                STAMPIF(lane == 0 && !h, 34 + 2 * wg);
                uint32_t it = 0;
                while (!__all_sync(0xffffffffu, ((((uint32_t)v[h][0] ^ t2) | ((uint32_t)v[h][1] ^ t2) | ((uint32_t)v[h][2] ^ t2) | ((uint32_t)v[h][3] ^ t2)) & 3u) == 0)) {
                    poll(h);
                    if (++it > SPIN_LIMIT) __trap();
                }
                STAMPIF(lane == 0 && !h, 35 + 2 * wg);
                float2 hin = make_float2(__uint_as_float((uint32_t)v[h][3]), __uint_as_float((uint32_t)(v[h][3] >> 32)));
#pragma unroll
                for (int m = 2; m >= 0; m--) hin = cfma(a512, hin, make_float2(__uint_as_float((uint32_t)v[h][m]), __uint_as_float((uint32_t)(v[h][m] >> 32))));
                hin = cmul(pw128, hin);
                hin.x += __shfl_xor_sync(0xffffffffu, hin.x, 1); hin.y += __shfl_xor_sync(0xffffffffu, hin.y, 1);
                hin.x += __shfl_xor_sync(0xffffffffu, hin.x, 2); hin.y += __shfl_xor_sync(0xffffffffu, hin.y, 2);
                w0[h] = cfma(pw32, hin, w0[h]);
            };
            chain(0, 1, 32);
            publish(0);
            chain(1, 1, 8);
            STAMPIF(lane == 0, 30 + 2 * wg);
            chain(1, 8, 32);
            publish(1);
            gap();
            scale(0, 0, POLL_S);
            poll(0);
            scale(0, POLL_S, 16);
            carry(0);
            if (wg) mbar_wait(bar_out + 24);
            STAMPIF(lane == 0, 38 + 2 * wg);
            const uint32_t stg = sb + OFF_STG + prm.swapped * 8192 + w * 1024 + (lane & 7) * 128 + (((lane >> 3) ^ (lane & 7)) << 4);
            const uint32_t second = prm.swapped ? -8192 : 8192;
            uint32_t hold = prm.swapped >> 1, last[8];
            const uint32_t keep = c == (g >> 1) ? 0xFFFEFFFEu : 0xFFFFFFFFu, tagw = ((t2 & 1) | ((t2 & 2) << 15)) & ~keep;
#pragma unroll
            for (int h = 0; h < 2; h++) {
                float (&acc)[64] = h ? accB : accA;
                uint32_t ra[16], ia[16];
                if (h) {
                    scale(1, 0, 4);
#pragma unroll
                    for (int u = 0; u < 4; u++) asm volatile("lop3.b32 %0, %0, %1, %2, 0x80;" : "+r"(hold) : "r"(last[u]), "r"(last[4 + u]));
                    release(bar_st + 32 * wg + 8 + hold);
                    poll(1);
                    scale(1, 4, 16);
                    mbar_wait(bar_xs);
                    row_setup();
                    carry(1);
                }
                auto stage = [&](uint32_t (&r)[16], uint32_t base, int j) {
                    stsm4((base ^ ((j & 1) * 64)) + (j >> 1) * 4096, r[4 * j], r[4 * j + 1], r[4 * j + 2], r[4 * j + 3]);
                };
#pragma unroll
                for (int n = 0; n < 16; n++) {
                    const float2 y = cfma(a[h], w0[h], make_float2(acc[4 * n], acc[4 * n + 2]));
                    w0[h] = cfma(a[h], y, make_float2(acc[4 * n + 1], acc[4 * n + 3]));
                    ra[n] = pack_bf(y.x, w0[h].x);
                    ia[n] = pack_bf(y.y, w0[h].y);
                    if (!(n & 1)) { ra[n] = (ra[n] & keep) | tagw; ia[n] = (ia[n] & keep) | tagw; }
                    if (!h && (n & 3) == 3) {
                        if (n > 3) {
                            gap();
#pragma unroll
                            for (int u = n - 7; u < n - 3; u++) asm volatile("lop3.b32 %0, %0, %1, %2, 0x80;" : "+r"(hold) : "r"(ra[u]), "r"(ia[u]));
                        }
                        if (n == 15) {
#pragma unroll
                            for (int u = 0; u < 4; u++) { last[u] = ra[12 + u]; last[4 + u] = ia[12 + u]; }
                        }
                        if (n == 11) { asm volatile("" : "+r"(ra[n]), "+r"(ia[n])); gap(); release(bar_st + 32 * wg); }
                        stage(ra, stg, n >> 2); stage(ia, stg + second, n >> 2);
                        gap();
                    }
                }
                if (h) {
                    STAMPIF(lane == 0, 39 + 2 * wg);
                    mbar_wait(bar_out + 32 * wg);
                    if (prm.swapped) {
#pragma unroll
                        for (int n = 0; n < 16; n++) { const uint32_t t = ra[n]; ra[n] = ia[n]; ia[n] = t; }
                    }
                    const uint32_t st0 = stg - prm.swapped * 8192;
#pragma unroll
                    for (int j = 0; j < 4; j++) stage(ra, st0, j);
                    release(bar_st + 32 * wg + 16);
                    mbar_wait(bar_out + 32 * wg + 8);
#pragma unroll
                    for (int j = 0; j < 4; j++) stage(ia, st0 + 8192, j);
                    release(bar_st + 32 * wg + 24);
                }
                STAMPIF(lane == 0, 42 + 2 * wg + h);
            }
        }

        const uint32_t xr = 2 * (g & 3) + (g >> 2), xa = sb + (wg ? OFF_STG : OFF_W) + (16 * w + xr) * 128 + (((c >> 1) ^ xr) << 4) + (c & 1) * 8;
        auto handover = [&](uint32_t bar) {
            const uint4 z = ldsm4(sb + OFF_KEYS + 16);
            if (lane == 1) mbar_arrive(bar + z.x);
        };
        auto load_x = [&](int j0, int j1) {
#pragma unroll
            for (int j = j0; j < j1; j++)
#pragma unroll
                for (int r = 0; r < 2; r++) xv[j][r] = lds64((xa ^ (32 * (j & 3))) + (j >> 2) * ABYTES + r * 1024);
        };
        auto skip_term = [&](int j0, int j1) {
#pragma unroll
            for (int j = j0; j < j1; j++)
#pragma unroll
                for (int r = 0; r < 2; r++) {
                    xv[j][r].x = mul_bf2(xv[j][r].x, fma_bf2(gp[r], dk[j].x, om[r]));
                    xv[j][r].y = mul_bf2(xv[j][r].y, fma_bf2(gp[r], dk[j].y, om[r]));
                    asm volatile("" : "+r"(xv[j][r].x), "+r"(xv[j][r].y));
                }
        };
        auto finish = [&](float (&acc)[64], int j, bool gaps) {
#pragma unroll
            for (int r = 0; r < 2; r++) {
                const int o = 8 * j + 2 * r;
                const float gv = bf_hi(gp[r]);
                acc[o] = fmaf(gv, acc[o], bf_lo(xv[j][r].x)); acc[o + 1] = fmaf(gv, acc[o + 1], bf_hi(xv[j][r].x));
                acc[o + 4] = fmaf(gv, acc[o + 4], bf_lo(xv[j][r].y)); acc[o + 5] = fmaf(gv, acc[o + 5], bf_hi(xv[j][r].y));
                stg4_unless(op + r * 2 * D_ + 16 * j, acc[o], acc[o + 1], acc[o + 4], acc[o + 5], routed[r]);
                if (gaps) gap();
            }
        };
        auto finish_routed = [&](float (&acc)[64]) {
#pragma unroll
            for (int r = 0; r < 2; r++)
                if (routed[r]) {
#pragma unroll
                    for (int j = 0; j < 8; j++) red4(op + r * 2 * D_ + 16 * j, acc[8 * j + 2 * r], acc[8 * j + 2 * r + 1], acc[8 * j + 2 * r + 4], acc[8 * j + 2 * r + 5]);
                }
            __syncwarp();
        };
        const uint32_t xbuf = sb + slot_off(FIN) + w * 2048 + lane * 16;

        if (wg == 1) {
            float outB[64];
            {
                sts128(sb + OFF_XS + at * 16, __float_as_uint(facc[0]), __float_as_uint(facc[1]), __float_as_uint(facc[2]), __float_as_uint(facc[3]));
                named_bar(2, 128);
                const uint32_t pg = sb + OFF_XS + prm.up_first * 1024 + (at & 63) * 16 + (w >> 1) * 8, pu = pg + 1024 - prm.up_first * 2048;
                const uint2 g1 = lds64(pg), u1 = lds64(pu);
                uint4* hp = prm.s->hid + cta * 32 - 512 + 16 * (w & 1) + 8 * (w >> 1) + g;
                asm volatile("" : "+l"(hp));
                mbar_wait(bar_fp);
                const uint2 g2 = lds64(pg + 2048), u2 = lds64(pu + 2048);
                const float ga = rbf(__uint_as_float(g1.x) + __uint_as_float(g2.x)), gb = rbf(__uint_as_float(g1.y) + __uint_as_float(g2.y));
                uint32_t hw = mul_bf2(pack_bf(__fdividef(ga, 1.0f + __expf(-ga)), __fdividef(gb, 1.0f + __expf(-gb))),
                                      pack_bf(__uint_as_float(u1.x) + __uint_as_float(u2.x), __uint_as_float(u1.y) + __uint_as_float(u2.y)));
                if (c == 2 * (w & 1) + (w >> 1)) hw = (hw & 0xFFFEFFFEu) | (tag & 1) | ((tag & 2) << 15);
                st_cell(hp, hw, __shfl_down_sync(0xffffffffu, hw, 1), __shfl_down_sync(0xffffffffu, hw, 2), __shfl_down_sync(0xffffffffu, hw, 3), has_gu && c == 0);
            }
            STAMPIF(lane == 0, 47);
            mbar_wait(bar_xb);
            load_x(0, 8);
            release(bar_xbfree);
            skip_term(0, 8);
            STAMPIF(lane == 0, 46);
            mbar_wait(bar_order2);
            static_for<NENT - FIN>([&](auto u) {
                run_small<1, FIN + u>(outB);
                if (u == 2) { wgmma_wait<2>(); if (lane == 0) mbar_arrive(bar_fold); }
            });
            if (lane == 0) mbar_expect_tx(bar_dn, w ? 0 : 7 * ABYTES);
            wgmma_wait<0>();
            pin64(outB);
            KSTAMP(2 * NENT - FIN);
            STAMPIF(at == 0, 50);
#pragma unroll
            for (int q = 0; q < 2; q++) {
                uint4 pb[16];
                mbar_wait(bar_accb + 8 * q);
#pragma unroll
                for (int v = q * HP; v < (q ? 16 : HP); v++) pb[v] = ldsm4(xbuf + (v >> 2) * ABYTES + (v & 3) * 512);
#pragma unroll
                for (int v = q * HP; v < (q ? 16 : HP); v++) {
                    outB[4 * v] += __uint_as_float(pb[v].x); outB[4 * v + 1] += __uint_as_float(pb[v].y);
                    outB[4 * v + 2] += __uint_as_float(pb[v].z); outB[4 * v + 3] += __uint_as_float(pb[v].w);
                    if (v & 1) finish(outB, v >> 1, false);
                }
            }
            finish_routed(outB);
            STAMPIF(lane == 0, 51);
        } else {
            float outA[64], outB[64], gacc[4];
            ring.slot = 32 % NST;
            ring.prev = bar_dummy;
            mbar_wait(bar_order1);
            run_entries<1, 2>(ring, 32, GU0 + 32, outA, outB, gacc, true, true);
            run_entries<1, 0>(ring, GU0 + 32, GU0 + 33, outA, outB, gacc, false, false, [&]() {
                pin4(gacc);
                sts128(sb + OFF_XS + 2048 + at * 16, __float_as_uint(gacc[0]), __float_as_uint(gacc[1]), __float_as_uint(gacc[2]), __float_as_uint(gacc[3]));
                __syncwarp();
                if (lane == 0) mbar_arrive(bar_fp);
            });
            mbar_wait(bar_xa);
            run_entries<1, 0>(ring, GU0 + 33, GU0 + 34, outA, outB, gacc, false, false, [&]() { load_x(0, 2); });
            load_x(2, 4);
            run_entries<1, 0>(ring, GU0 + 34, GU0 + 35, outA, outB, gacc, false, false, [&]() { load_x(4, 6); });
            load_x(6, 8);
            run_entries<1, 0>(ring, GU0 + 35, GU0 + 36, outA, outB, gacc, false, false, [&]() { release(bar_xafree); });
            run_entries<1, 0>(ring, GU0 + 36, FIN, outA, outB, gacc);
            static_for<NENT - FIN>([&](auto u) {
                mbar_wait(full + 8 * (FIN + u));
                run_small<0, FIN + u>(outA);
                if (u == 5 && lane == 0) mbar_arrive(bar_order2);
                wgmma_wait<1>();
                if (lane == 0) mbar_arrive(empty + 8 * (FIN + u - 1));
                if (u < 4) skip_term(2 * u, 2 * u + 2);
            });
            const uint2 sk = lds64(sb + OFF_SEL + 8 * c), fk = lds64(sb + OFF_FAC + 8 * c);
            float* y0 = prm.out + (~sk.x & 2047u) * D_ + (cta & 15) * 64 + w * 16 + g;
            float* y1 = prm.out + (~sk.y & 2047u) * D_ + (cta & 15) * 64 + w * 16 + g;
            asm volatile("" : "+l"(y0), "+l"(y1));
            mbar_wait(empty + 8 * FIN);
            wgmma_wait<0>();
            pin64(outA); pin64(outB);
            STAMPIF(at == 0, 53);
            GSTAMP(at == 0, 2);
            auto dump = [&](int v) {
                if (v == 4) mbar_wait(bar_fold);
                stsm4(xbuf + (v >> 2) * ABYTES + (v & 3) * 512, __float_as_uint(outB[4 * v]), __float_as_uint(outB[4 * v + 1]), __float_as_uint(outB[4 * v + 2]),
                      __float_as_uint(outB[4 * v + 3]));
                if (v == HP - 1 || v == 15) handover(bar_accb + 8 * (v == 15));
            };
#pragma unroll
            for (int j = 0; j < 8; j++) {
                finish(outA, j, true);
#pragma unroll
                for (int v = j * NDUMP / 8; v < (j + 1) * NDUMP / 8; v++) dump(v);
            }
            STAMPIF(lane == 0, 54);
#pragma unroll
            for (int v = NDUMP; v < 16; v++) dump(v);
            STAMPIF(lane == 0, 55);
            float yacc[4];
            const uint64_t dw = make_desc(sb), dh = (uint64_t)(((sb + OFF_XS) & 0x3FFFF) >> 4) | ((uint64_t)8 << 16) | ((uint64_t)8 << 32);
            mbar_wait(bar_zero);
            mbar_wait(bar_dn);
            STAMPIF(at == 0, 2);
            wgmma_fence();
#pragma unroll
            for (int n = 0; n < 28; n++) wgmma_n8<1, 1>(yacc, dw + (dn_off(n >> 2) >> 4) + (n & 3) * 128, dh + n * 16, n > 0);
            wgmma_commit();
            finish_routed(outA);
            wgmma_wait<0>();
            pin4(yacc);
            atomicAdd(y0, yacc[0] * __uint_as_float(fk.x)); atomicAdd(y1, yacc[1] * __uint_as_float(fk.y));
            atomicAdd(y0 + 8, yacc[2] * __uint_as_float(fk.x)); atomicAdd(y1 + 8, yacc[3] * __uint_as_float(fk.y));
            STAMPIF(lane == 0, 3);
        }
    }
}

typedef CUresult (*EncodeFn)(CUtensorMap*, CUtensorMapDataType, cuuint32_t, void*, const cuuint64_t*, const cuuint64_t*, const cuuint32_t*,
                             const cuuint32_t*, CUtensorMapInterleave, CUtensorMapSwizzle, CUtensorMapL2promotion, CUtensorMapFloatOOBfill);

bool encode(EncodeFn fn, CUtensorMap* m, const void* ptr, int rank, const cuuint64_t* dims, const cuuint64_t* strides, const cuuint32_t* box,
            CUtensorMapSwizzle sw = CU_TENSOR_MAP_SWIZZLE_128B, CUtensorMapL2promotion promo = CU_TENSOR_MAP_L2_PROMOTION_NONE) {
    const cuuint32_t es[5] = {1, 1, 1, 1, 1};
    return fn(m, CU_TENSOR_MAP_DATA_TYPE_BFLOAT16, rank, const_cast<void*>(ptr), dims, strides, box, es, CU_TENSOR_MAP_INTERLEAVE_NONE,
              sw, promo, CU_TENSOR_MAP_FLOAT_OOB_FILL_NONE) == CUDA_SUCCESS;
}

}

extern "C" void kernel_launch(void* const* d_in, const int* in_sizes, int n_in, void* d_out, int out_size) {
    (void)in_sizes; (void)n_in; (void)out_size;
    Params prm;
    prm.x = (const __nv_bfloat16*)d_in[0];
    prm.lam_re = (const __nv_bfloat16*)d_in[1];
    prm.lam_im = (const __nv_bfloat16*)d_in[2];
    prm.b_re = (const __nv_bfloat16*)d_in[3];
    prm.b_im = (const __nv_bfloat16*)d_in[4];
    prm.c_re = (const __nv_bfloat16*)d_in[5];
    prm.c_im = (const __nv_bfloat16*)d_in[6];
    prm.log_dt = (const __nv_bfloat16*)d_in[7];
    prm.dskip = (const __nv_bfloat16*)d_in[8];
    prm.w_r = (const __nv_bfloat16*)d_in[10];
    prm.gate_w = (const __nv_bfloat16*)d_in[14];
    prm.out = (float*)d_out;
    cudaGetSymbolAddress((void**)&prm.s, g_scratch);
    int dev = 0, sms = 0;
    cudaGetDevice(&dev);
    cudaDeviceGetAttribute(&sms, cudaDevAttrMultiProcessorCount, dev);
    auto kernel = sms == NGRID ? fused_kernel<true> : fused_kernel<false>;
    prm.swapped = prm.b_im < prm.b_re;

    void* fnp = nullptr;
    cudaDriverEntryPointQueryResult qr;
    cudaGetDriverEntryPoint("cuTensorMapEncodeTiled", &fnp, cudaEnableDefault, &qr);
    EncodeFn fn = (EncodeFn)fnp;
    cudaFuncSetAttribute(kernel, cudaFuncAttributeMaxDynamicSharedMemorySize, SMEM_BYTES);

    CUtensorMap mX, mB, mCre, mCim, mW, mWd, mXr, mXe;
    const cuuint64_t row = 2048;
    {
        const cuuint64_t dims[4] = {1024, 2, 4, 976}, st[3] = {row, 32 * row, 2 * row};
        const cuuint32_t box[4] = {64, 2, 4, 16};
        encode(fn, &mX, prm.x, 4, dims, st, box, CU_TENSOR_MAP_SWIZZLE_128B, PROMO);
    }
    {
        const char *lo = (const char*)(prm.swapped ? prm.b_im : prm.b_re), *hi = (const char*)(prm.swapped ? prm.b_re : prm.b_im);
        const cuuint64_t dims[5] = {1024, 8, 2, 96, 2}, st[4] = {row, (cuuint64_t)(hi - lo), 8 * row, 256 * row};
        const cuuint32_t box[5] = {64, 8, 2, 4, 2};
        encode(fn, &mB, lo, 5, dims, st, box, CU_TENSOR_MAP_SWIZZLE_128B, PROMO);
    }
    {
        const cuuint64_t dims[5] = {1024, 2, 4, 2, 64}, st[4] = {row, 4 * row, 2 * row, 16 * row};
        const cuuint32_t box[5] = {64, 2, 4, 2, 8};
        encode(fn, &mCre, prm.c_re, 5, dims, st, box);
        encode(fn, &mCim, prm.c_im, 5, dims, st, box);
    }
    {
        const char *pg = (const char*)d_in[11], *pu = (const char*)d_in[12];
        prm.up_first = pu < pg;
        const cuuint64_t dims[3] = {F_, D_, 2}, st[2] = {F_ * 2, (cuuint64_t)(pu < pg ? pg - pu : pu - pg)}, dimsd[2] = {D_, F_}, std_[1] = {row};
        const cuuint32_t box[3] = {32, 32, 2}, boxd[2] = {64, 64};
        encode(fn, &mW, pu < pg ? pu : pg, 3, dims, st, box, CU_TENSOR_MAP_SWIZZLE_64B, CU_TENSOR_MAP_L2_PROMOTION_NONE);
        encode(fn, &mWd, d_in[13], 2, dimsd, std_, boxd, CU_TENSOR_MAP_SWIZZLE_128B, CU_TENSOR_MAP_L2_PROMOTION_NONE);
    }
    {
        const cuuint64_t dims[3] = {D_ - 192, S_, 4}, st[2] = {row, 128};
        const cuuint32_t box[3] = {64, 16, 4};
        encode(fn, &mXr, prm.x, 3, dims, st, box, CU_TENSOR_MAP_SWIZZLE_128B, CU_TENSOR_MAP_L2_PROMOTION_NONE);
    }
    {
        const cuuint64_t dims[5] = {D_, 2, 2, 2, 976}, st[4] = {64 * row, row, 32 * row, 2 * row};
        const cuuint32_t box[5] = {64, 2, 2, 2, 8};
        encode(fn, &mXe, prm.x, 5, dims, st, box);
    }
    kernel<<<NGRID, 384, SMEM_BYTES, cudaStreamPerThread>>>(prm, mX, mB, mCre, mCim, mW, mWd, mXr, mXe);
}
```

```cpp
#include <cuda_runtime.h>
#include <cuda_bf16.h>
#include <cuda.h>
#include <stdint.h>

namespace {

constexpr int S_ = 2048, D_ = 1024, F_ = 3584;
constexpr int NCTA = 128, NGRID = 132;
#define XE_ 58
#define GU0_ 18
constexpr int NENT = 64, FIN = 58, XE = XE_;
constexpr int NST = 5;
constexpr int RE0 = 4;
constexpr int GU0 = GU0_;
constexpr uint32_t SLOT = 32768, ABYTES = 8192, WBYTES = 4096;
constexpr uint32_t OFF_XS = NST * SLOT;
constexpr uint32_t OFF_LIST = OFF_XS + 8192;
constexpr uint32_t OFF_W = OFF_XS + 16384;
constexpr uint32_t OFF_STG = OFF_W + 32768;
__host__ __device__ constexpr uint32_t slot_off(int i) { return i < XE ? (i % NST) * SLOT : i == XE ? OFF_W : ((i - 1) % NST) * SLOT; }
__host__ __device__ constexpr uint32_t dn_off(int u) { return u == 0 ? OFF_XS + ABYTES : u < 3 ? OFF_STG + (u - 1) * ABYTES : slot_off(FIN - 2 + u); }
constexpr uint32_t OFF_CONST = OFF_STG;
constexpr uint32_t OFF_RED = OFF_STG + 4096;
constexpr uint32_t OFF_FULL = OFF_STG + 16384;
constexpr uint32_t OFF_EMPTY = OFF_FULL + 120 * 8;
constexpr uint32_t OFF_G = OFF_EMPTY + 88 * 8;
constexpr uint32_t OFF_DK = OFF_G + 256;
constexpr uint32_t OFF_KEYS = OFF_DK + 256;
constexpr uint32_t OFF_SEL = OFF_KEYS + 32;
constexpr uint32_t OFF_FAC = OFF_SEL + 32;
constexpr uint32_t OFF_EPOCH = OFF_FAC + 32;
constexpr uint32_t OFF_PROF = OFF_EPOCH + 16;
constexpr uint32_t SMEM_BYTES = OFF_PROF + 768;
static_assert(SMEM_BYTES <= 232448, "smem");

constexpr uint32_t sb = 1024;
constexpr uint32_t SPIN_LIMIT = 1u << 18;

struct Scratch {
    unsigned int cnt[2 * 32];
    unsigned long long rpack[S_ / 2];
    unsigned long long gpack[S_ / 2];
    uint4 time[NCTA];
    float2 carry[16 * 1024];
    uint4 hid[F_];
    uint4 h[8 * 4 * 256 * 64];
};
__device__ __align__(128) Scratch g_scratch;
#define LT(i) do {} while (0)
#define STAMPW(cond, w) do {} while (0)
#define LATE(i, tt) do {} while (0)
#define LANDED(i) do {} while (0)
#define GSTAMP(cond, w) do {} while (0)
#define STAMPIF(cond, i) STAMPW(cond, 72 + (i))
#define STAMP(i) STAMPW(1, 72 + (i))
#define KSTAMP(i) STAMPW((threadIdx.x & 127) == 0, i)

struct Params {
    const __nv_bfloat16 *x, *b_re, *b_im;
    Scratch* s;
    int up_first;
    int swapped;
    const __nv_bfloat16 *lam_re, *lam_im, *c_re, *c_im, *log_dt, *dskip, *w_r, *gate_w;
    float* out;
};

__device__ __forceinline__ uint32_t smem_u32(const void* p) { return (uint32_t)__cvta_generic_to_shared(p); }
__device__ __forceinline__ void mbar_init(uint32_t bar, uint32_t cnt) { asm volatile("mbarrier.init.shared::cta.b64 [%0], %1;" ::"r"(bar), "r"(cnt) : "memory"); }
__device__ __forceinline__ void mbar_expect_tx(uint32_t bar, uint32_t bytes) { asm volatile("mbarrier.arrive.expect_tx.shared::cta.b64 _, [%0], %1;" ::"r"(bar), "r"(bytes) : "memory"); }
__device__ __forceinline__ void mbar_arrive(uint32_t bar) { asm volatile("mbarrier.arrive.shared::cta.b64 _, [%0];" ::"r"(bar) : "memory"); }
__device__ __forceinline__ void mbar_wait(uint32_t bar, uint32_t parity = 0) {
    asm volatile("{ .reg .pred p; .reg .u32 n;\n"
                 "mov.u32 n, 0;\n"
                 "AGAIN: mbarrier.try_wait.parity.shared::cta.b64 p, [%0], %1;\n"
                 "@p bra.uni DONE;\n"
                 "add.u32 n, n, 1;\n"
                 "setp.lt.u32 p, n, %2;\n"
                 "@p bra.uni AGAIN;\n"
                 "trap;\n"
                 "DONE: }" ::"r"(bar), "r"(parity), "n"(SPIN_LIMIT) : "memory");
}
__device__ __forceinline__ bool elect_one() {
    uint32_t pred;
    asm volatile("{ .reg .pred P; elect.sync _|P, 0xffffffff; selp.b32 %0, 1, 0, P; }" : "=r"(pred));
    return pred;
}
__device__ __forceinline__ void named_bar(int id, int n) { asm volatile("bar.sync %0, %1;" ::"r"(id), "r"(n) : "memory"); }

#define ONE "{ .reg .pred e; elect.sync _|e, 0xffffffff;\n@e "
template <int N> __device__ __forceinline__ void mbar_init_n(uint32_t bar, uint32_t cnt, uint32_t extra = 0) {
    if (elect_one()) {
#pragma unroll
        for (int i = 0; i < N; i++) mbar_init(bar + 8 * i, i == N - 1 ? cnt + extra : cnt);
        asm volatile("fence.mbarrier_init.release.cluster;" ::: "memory");
    }
    __syncwarp();
}
__device__ __forceinline__ void bulk_load(uint32_t dst, const void* src, uint32_t bytes, uint32_t bar) {
    asm volatile(ONE "cp.async.bulk.shared::cluster.global.mbarrier::complete_tx::bytes [%0], [%1], %2, [%3]; }" ::"r"(dst), "l"(src), "r"(bytes), "r"(bar) : "memory");
}
__device__ __forceinline__ void sts128(uint32_t a, uint32_t x, uint32_t y, uint32_t z, uint32_t w) {
    asm volatile("st.shared.v4.u32 [%0], {%1,%2,%3,%4};" ::"r"(a), "r"(x), "r"(y), "r"(z), "r"(w) : "memory");
}
__device__ __forceinline__ uint2 lds64(uint32_t a) {
    uint2 v;
    asm volatile("ld.shared.v2.u32 {%0,%1}, [%2];" : "=r"(v.x), "=r"(v.y) : "r"(a) : "memory");
    return v;
}
__device__ __forceinline__ uint32_t clk32() { uint32_t c; asm volatile("mov.u32 %0, %%clock;" : "=r"(c)); return c; }
__device__ __forceinline__ void gap() { asm volatile("pmevent 1;" ::: "memory"); }
__device__ __forceinline__ void pace_until(uint32_t t) { while ((int)(clk32() - t) < 0) {} }
#define SLEEP_MARGIN 200
__device__ __forceinline__ void sleep_until(uint32_t t) {
    while ((int)(clk32() + SLEEP_MARGIN - t) < 0) __nanosleep(40);
    pace_until(t);
}
__device__ __forceinline__ void tma2(uint32_t dst, const CUtensorMap* m, int c0, int c1, uint32_t bar, uint64_t pol) {
    asm volatile(ONE "cp.async.bulk.tensor.2d.shared::cluster.global.mbarrier::complete_tx::bytes.L2::cache_hint [%0], [%1, {%3, %4}], [%2], %5; }"
                 ::"r"(dst), "l"(m), "r"(bar), "r"(c0), "r"(c1), "l"(pol) : "memory");
}
__device__ __forceinline__ void tma3s(uint32_t dst, const CUtensorMap* m, int c0, int c1, uint32_t bar, uint64_t pol) {
    asm volatile(ONE "cp.async.bulk.tensor.3d.shared::cluster.global.mbarrier::complete_tx::bytes.L2::cache_hint [%0], [%1, {%3, %4, %5}], [%2], %6; }"
                 ::"r"(dst), "l"(m), "r"(bar), "r"(c0), "r"(c1), "r"(0), "l"(pol) : "memory");
}
__device__ __forceinline__ void tma3(uint32_t dst, const CUtensorMap* m, int c0, int c1, uint32_t bar) {
    asm volatile(ONE "cp.async.bulk.tensor.3d.shared::cluster.global.mbarrier::complete_tx::bytes [%0], [%1, {%3, %4, %5}], [%2]; }"
                 ::"r"(dst), "l"(m), "r"(bar), "r"(c0), "r"(c1), "r"(0) : "memory");
}
__device__ __forceinline__ void tma4(uint32_t dst, const CUtensorMap* m, int c0, int c3, uint32_t bar) {
    asm volatile(ONE "cp.async.bulk.tensor.4d.shared::cluster.global.mbarrier::complete_tx::bytes [%0], [%1, {%3, %5, %5, %4}], [%2]; }"
                 ::"r"(dst), "l"(m), "r"(bar), "r"(c0), "r"(c3), "r"(0) : "memory");
}
__device__ __forceinline__ void tma5(uint32_t dst, const CUtensorMap* m, int c0, int c4, uint32_t bar) {
    asm volatile(ONE "cp.async.bulk.tensor.5d.shared::cluster.global.mbarrier::complete_tx::bytes [%0], [%1, {%3, %5, %5, %5, %4}], [%2]; }"
                 ::"r"(dst), "l"(m), "r"(bar), "r"(c0), "r"(c4), "r"(0) : "memory");
}
__device__ __forceinline__ void tma5b(uint32_t dst, const CUtensorMap* m, int c0, int c3, uint32_t bar) {
    asm volatile(ONE "cp.async.bulk.tensor.5d.shared::cluster.global.mbarrier::complete_tx::bytes [%0], [%1, {%3, %5, %5, %4, %5}], [%2]; }"
                 ::"r"(dst), "l"(m), "r"(bar), "r"(c0), "r"(c3), "r"(0) : "memory");
}
__device__ __forceinline__ void prefetch_l2(const void* p) {
    asm volatile("cp.async.ca.shared.global.L2::256B [%0], [%1], 4;" ::"r"(sb + OFF_EPOCH + 12), "l"(p) : "memory");
}

__device__ __forceinline__ uint32_t lds32(uint32_t a) {
    uint32_t v;
    asm volatile("ld.volatile.shared.u32 %0, [%1];" : "=r"(v) : "r"(a) : "memory");
    return v;
}
__device__ __forceinline__ uint32_t uni(uint32_t v) { return __shfl_sync(0xffffffffu, v, 0); }   __device__ __forceinline__ uint32_t ld_acquire(const unsigned int* p) {
    uint32_t v;
    asm volatile("ld.acquire.gpu.global.u32 %0, [%1];" : "=r"(v) : "l"(p) : "memory");
    return v;
}
__device__ __forceinline__ void red_release(unsigned int* p) { asm volatile("red.release.gpu.global.add.u32 [%0], 1;" ::"l"(p) : "memory"); }
__device__ __forceinline__ void wait_count(const unsigned int* p, uint32_t target) {
#pragma unroll 1
    for (uint32_t it = 0; it < SPIN_LIMIT; ++it)
        if ((int)(ld_acquire(p) - target) >= 0) return;
    __trap();
}
__device__ __forceinline__ void wait_count_slow(const unsigned int* p, uint32_t target) {
#pragma unroll 1
    for (uint32_t it = 0; it < SPIN_LIMIT; ++it) {
        if ((int)(ld_acquire(p) - target) >= 0) return;
        __nanosleep(200);
    }
    __trap();
}
__device__ __forceinline__ unsigned long long ld_relaxed1(const void* p) {
    unsigned long long v;
    asm volatile("ld.relaxed.gpu.global.b64 %0, [%1];" : "=l"(v) : "l"(p) : "memory");
    return v;
}
__device__ __forceinline__ ulonglong2 ld_relaxed2(const void* p) {
    ulonglong2 v;
    asm volatile("ld.relaxed.gpu.global.v2.b64 {%0, %1}, [%2];" : "=l"(v.x), "=l"(v.y) : "l"(p) : "memory");
    return v;
}
__device__ __forceinline__ void ld_cell(uint32_t (&v)[4], const void* p, bool on = true) {
    asm volatile("{ .reg .pred p; .reg .b64 l, h; .reg .b128 t; setp.ne.u32 p, %5, 0; mov.b64 l, {%0, %1}; mov.b64 h, {%2, %3}; mov.b128 t, {l, h};\n"
                 "@p ld.relaxed.gpu.global.b128 t, [%4]; mov.b128 {l, h}, t; mov.b64 {%0, %1}, l; mov.b64 {%2, %3}, h; }"
                 : "+r"(v[0]), "+r"(v[1]), "+r"(v[2]), "+r"(v[3]) : "l"(p), "r"((uint32_t)on) : "memory");
}
__device__ __forceinline__ void st_cell(void* p, uint32_t a, uint32_t b, uint32_t c, uint32_t d, bool on) {
    asm volatile("{ .reg .pred p; .reg .b64 l, h; .reg .b128 t; setp.ne.u32 p, %5, 0; mov.b64 l, {%1, %2}; mov.b64 h, {%3, %4}; mov.b128 t, {l, h};\n"
                 "@p st.relaxed.gpu.global.b128 [%0], t; }" ::"l"(p), "r"(a), "r"(b), "r"(c), "r"(d), "r"((uint32_t)on) : "memory");
}

__device__ __forceinline__ uint64_t make_desc(uint32_t addr, uint32_t sbo = 1024) {
    return (uint64_t)((addr & 0x3FFFF) >> 4) | ((uint64_t)1 << 16) | ((uint64_t)(sbo >> 4) << 32) | ((uint64_t)1 << 62);
}
__device__ __forceinline__ void wgmma_fence() { asm volatile("wgmma.fence.sync.aligned;" ::: "memory"); }
__device__ __forceinline__ void wgmma_commit() { asm volatile("wgmma.commit_group.sync.aligned;" ::: "memory"); }
template <int N> __device__ __forceinline__ void wgmma_wait() { asm volatile("wgmma.wait_group.sync.aligned %0;" ::"n"(N) : "memory"); }

#define R8(d, i) "+f"(d[i]), "+f"(d[i + 1]), "+f"(d[i + 2]), "+f"(d[i + 3]), "+f"(d[i + 4]), "+f"(d[i + 5]), "+f"(d[i + 6]), "+f"(d[i + 7])
#define R64(d) R8(d, 0), R8(d, 8), R8(d, 16), R8(d, 24), R8(d, 32), R8(d, 40), R8(d, 48), R8(d, 56)
template <int TA>
__device__ __forceinline__ void wgmma_n128(float (&d)[64], uint64_t da, uint64_t db, int scale_d = 1) {
    asm volatile("{ .reg .pred p; setp.ne.b32 p, %66, 0;\n"
                 "wgmma.mma_async.sync.aligned.m64n128k16.f32.bf16.bf16 "
                 "{%0,%1,%2,%3,%4,%5,%6,%7,%8,%9,%10,%11,%12,%13,%14,%15,%16,%17,%18,%19,%20,%21,%22,%23,%24,%25,%26,%27,%28,%29,%30,%31,"
                 "%32,%33,%34,%35,%36,%37,%38,%39,%40,%41,%42,%43,%44,%45,%46,%47,%48,%49,%50,%51,%52,%53,%54,%55,%56,%57,%58,%59,%60,%61,%62,%63}, "
                 "%64, %65, p, 1, 1, %67, 0; }"
                 : R64(d)
                 : "l"(da), "l"(db), "r"(scale_d), "n"(TA));
}
__device__ __forceinline__ void pin4(float (&d)[4]) { asm volatile("" : "+f"(d[0]), "+f"(d[1]), "+f"(d[2]), "+f"(d[3])::"memory"); }
__device__ __forceinline__ void pin64(float (&d)[64]) { asm volatile("" : R64(d)::"memory"); }

template <int TA, int TB = 0>
__device__ __forceinline__ void wgmma_n8(float (&d)[4], uint64_t da, uint64_t db, int scale_d = 1) {
    asm volatile("{ .reg .pred p; setp.ne.b32 p, %7, 0;\n"
                 "wgmma.mma_async.sync.aligned.m64n8k16.f32.bf16.bf16 {%0,%1,%2,%3}, %4, %5, p, 1, 1, %6, %8; }"
                 : "+f"(d[0]), "+f"(d[1]), "+f"(d[2]), "+f"(d[3])
                 : "l"(da), "l"(db), "n"(TA), "r"(scale_d), "n"(TB));
}

__device__ __forceinline__ float bf_lo(uint32_t u) { return __uint_as_float(u << 16); }
__device__ __forceinline__ float bf_hi(uint32_t u) { return __uint_as_float(u & 0xFFFF0000u); }
__device__ __forceinline__ float rbf(float v) { return __bfloat162float(__float2bfloat16_rn(v)); }
__device__ __forceinline__ uint32_t pack_bf(float lo, float hi) {
    uint32_t r;
    asm("cvt.rn.bf16x2.f32 %0, %1, %2;" : "=r"(r) : "f"(hi), "f"(lo));
    return r;
}
__device__ __forceinline__ uint32_t mul_bf2(uint32_t a, uint32_t b) {
    __nv_bfloat162 r = __hmul2(*reinterpret_cast<__nv_bfloat162*>(&a), *reinterpret_cast<__nv_bfloat162*>(&b));
    return *reinterpret_cast<uint32_t*>(&r);
}
__device__ __forceinline__ uint32_t fma_bf2(uint32_t a, uint32_t b, uint32_t c) {
    uint32_t r;
    asm("fma.rn.bf16x2 %0, %1, %2, %3;" : "=r"(r) : "r"(a), "r"(b), "r"(c));
    return r;
}
__device__ __forceinline__ float2 cmul(float2 a, float2 b) { return make_float2(a.x * b.x - a.y * b.y, a.x * b.y + a.y * b.x); }
__device__ __forceinline__ float2 cfma(float2 a, float2 b, float2 c) {
    return make_float2(fmaf(a.x, b.x, fmaf(-a.y, b.y, c.x)), fmaf(a.x, b.y, fmaf(a.y, b.x, c.y)));
}
__device__ __forceinline__ float sigmoidf_(float v) { return __fdividef(1.0f, 1.0f + expf(-v)); }

__device__ __forceinline__ void bulk_prefetch(const void* src, uint32_t bytes) {
    asm volatile(ONE "cp.async.bulk.prefetch.L2.global [%0], %1; }" ::"l"(src), "r"(bytes) : "memory");
}
__device__ __forceinline__ void bulk_store(void* dst, uint32_t src, uint32_t bytes) {
    asm volatile(ONE "cp.async.bulk.global.shared::cta.bulk_group [%0], [%1], %2; }" ::"l"(dst), "r"(src), "r"(bytes) : "memory");
}
__device__ __forceinline__ void stsm4(uint32_t a, uint32_t x, uint32_t y, uint32_t z, uint32_t w) {
    asm volatile("stmatrix.sync.aligned.m8n8.x4.shared.b16 [%0], {%1,%2,%3,%4};" ::"r"(a), "r"(x), "r"(y), "r"(z), "r"(w) : "memory");
}
__device__ __forceinline__ uint4 ldsm4(uint32_t a) {
    uint4 v;
    asm volatile("ldmatrix.sync.aligned.m8n8.x4.shared.b16 {%0,%1,%2,%3}, [%4];" : "=r"(v.x), "=r"(v.y), "=r"(v.z), "=r"(v.w) : "r"(a) : "memory");
    return v;
}
__device__ __forceinline__ void stg4_unless(float* p, float a, float b, float c, float d, uint32_t skip) {
    asm volatile("{ .reg .pred p; setp.eq.u32 p, %5, 0; @p st.global.v4.f32 [%0], {%1,%2,%3,%4}; }" ::"l"(p), "f"(a), "f"(b), "f"(c), "f"(d), "r"(skip) : "memory");
}
__device__ __forceinline__ void red4(float* p, float a, float b, float c, float d) {
    asm volatile("red.global.add.v4.f32 [%0], {%1,%2,%3,%4};" ::"l"(p), "f"(a), "f"(b), "f"(c), "f"(d) : "memory");
}

#define TT0 2900
#define PER 514
#define PCUT 60
#define PFIN 360
#define PF0 1500
#define PFX_PACE 400
#define PF1 700
#define T2 300
#define P2 520
#define G0 450
#define R0 2100
#define R_PACE 350
#define W_SHIFT 250
#define PROMO CU_TENSOR_MAP_L2_PROMOTION_L2_256B
#define POLL_S 0
#define ST_TOL 100
#define ST_SHIFT 300
#define CLK_NS 420
#define MARGIN 150
#define BP1 12
#define NOST 0
#define DV 15
#define FAKE 0
#define FE 5
#define HP 4
#define DNL 1
#define AE 6
#define AG0 900
#define AB 16
#define HGE 39
constexpr uint32_t duration(int i) { return PER + (i >= RE0 && i < RE0 + 4 ? 72 : 0) + (i >= GU0 && i < GU0 + 32 ? 36 : 0); }
constexpr uint32_t cmax(uint32_t a, uint32_t b) { return a > b ? a : b; }
constexpr uint32_t issue_time(int i) {
    return i <= NST ? TT0 : i < XE ? issue_time(i - 1) + duration(i - NST) - (i >= XE - 3 && i > GU0 + 36 ? PCUT : 0) : issue_time(XE - 1) + cmax((i - XE + 1) * PFIN, (i - XE) * 512);
}
template <int I> struct Sched { static constexpr uint32_t t = issue_time(I); };
template <int LO, int HI, class F>
__device__ __forceinline__ void for_entries(uint32_t base, F body) {
    constexpr uint32_t per = Sched<LO + 1>::t - Sched<LO>::t;
    static_assert(Sched<HI - 1>::t - Sched<LO>::t == (HI - 1 - LO) * per, "period");
    uint32_t tt = base + Sched<LO>::t;
#pragma unroll 1
    for (int i = LO; i < HI; i++) {
        body(i, tt);
        tt += per;
    }
}

struct Ring { uint32_t prev; int slot; };
struct NoHook { __device__ void operator()() const {} };
template <int TA, int SM, class H = NoHook>
__device__ __forceinline__ void run_entries(Ring& r, int lo, int hi, float (&accA)[64], float (&accB)[64], float (&small)[4],
                                            bool fresh = false, bool sfresh = false, H released = H()) {
    const uint64_t d0 = make_desc(sb);
    const bool leader = (threadIdx.x & 31) == 0;
#pragma unroll 1
    for (int i = lo; i < hi; i++) {
        const uint32_t bar = sb + OFF_FULL + 8 * i;
        const uint64_t da = d0 + (uint64_t)(r.slot * (SLOT >> 4));
        const int n = i - (SM == 1 ? RE0 : GU0);
        const uint64_t dw = SM == 1 ? d0 + (uint64_t)((OFF_W >> 4) + n * 512)
                                    : (((uint64_t)2 << 62) | ((uint64_t)32 << 32) | (128u << 16) | ((sb + OFF_W) >> 4)) + (uint64_t)((n & 7) * 256);
        const uint64_t dt8 = d0 + (uint64_t)((OFF_XS >> 4) + (SM == 1 ? n * 64 : (n >> 1) * 64 + (n & 1) * 4));
        r.slot = r.slot == NST - 1 ? 0 : r.slot + 1;
        mbar_wait(bar);
        KSTAMP(i);
        wgmma_fence();
#pragma unroll
        for (int kk = 0; kk < 4; kk++) {
            wgmma_n128<TA>(accA, da + kk * (TA ? 128 : 2), da + 1024 + kk * 2, kk > 0 || !fresh);
            if (SM == 1) wgmma_n8<0>(small, dw + kk * 2, dt8 + kk * 2, kk > 0 || !sfresh);
            if (SM == 2 && (kk & 1)) wgmma_n8<1>(small, dw + (kk >> 1) * 64, dt8 + (kk >> 1) * 2, kk > 1 || !sfresh);
            wgmma_n128<TA>(accB, da + 512 + kk * (TA ? 128 : 2), da + 1024 + kk * 2, kk > 0 || !fresh);
            if (kk == 1) {
                wgmma_commit();
                wgmma_wait<1>();
                if (leader) mbar_arrive(r.prev);
                released();
            }
        }
        wgmma_commit();
        r.prev = bar + (OFF_EMPTY - OFF_FULL);
        fresh = sfresh = false;
    }
}
template <int HALF, int I>
__device__ __forceinline__ void run_small(float (&acc)[64]) {
    const uint64_t da = make_desc(sb) + (slot_off(I) >> 4);
    KSTAMP(I + HALF * (NENT - FIN));
    wgmma_fence();
#pragma unroll
    for (int kk = 0; kk < 4; kk++) wgmma_n128<1>(acc, da + HALF * 512 + kk * 128, da + 1024 + kk * 2, kk > 0 || !(HALF && I == FIN));
    wgmma_commit();
}
template <int V> struct Int { __host__ __device__ constexpr operator int() const { return V; } };
template <int N, class F> __device__ __forceinline__ void static_for(F f) {
    if constexpr (N > 0) { static_for<N - 1>(f); f(Int<N - 1>()); }
}

template <bool BY_SMID>
__global__ void __launch_bounds__(384, 1)
fused_kernel(const __grid_constant__ Params prm, const __grid_constant__ CUtensorMap mX, const __grid_constant__ CUtensorMap mB, const __grid_constant__ CUtensorMap mCre,
             const __grid_constant__ CUtensorMap mCim, const __grid_constant__ CUtensorMap mW,
             const __grid_constant__ CUtensorMap mWd, const __grid_constant__ CUtensorMap mXr, const __grid_constant__ CUtensorMap mXe) {
    extern __shared__ __align__(1024) uint8_t smem[];
    const uint32_t cstart = clk32();
    const int tid = threadIdx.x, lane = tid & 31;
    uint32_t id = blockIdx.x;
    if (BY_SMID) asm volatile("mov.u32 %0, %%smid;" : "=r"(id));
    {
        const uint32_t o = (tid * 2056) & 0x7880, b = (id & 127) * 8192;
        asm volatile("{ .reg .pred p, q; setp.lt.u32 p, %3, 32; setp.eq.u32 q, %4, 0;\n"
                     "@q prefetch.global.L2 [%1]; @p prefetch.global.L2 [%0]; @q prefetch.global.L2 [%2]; }"
                     ::"l"((const char*)prm.x + (b * 4 + o)), "l"((const char*)prm.b_re + (b + o)), "l"((const char*)prm.b_im + (b + o)), "r"(tid), "r"(tid & ~19) : "memory");
    }
    const int warp = __shfl_sync(0xffffffffu, tid >> 5, 0);
    gap();
    int cta;
    asm("{ .reg .pred p; .reg .u32 a, b, u, q;\n"
        "and.b32 a, %1, 14; shl.b32 a, a, 3; shr.u32 b, %1, 3; and.b32 b, b, 6; add.u32 a, a, b;\n"
        "and.b32 u, %1, 62; mul.lo.u32 q, u, 37; shr.u32 q, q, 9; shl.b32 u, u, 3; mad.lo.u32 u, q, -110, u; add.u32 u, u, 24;\n"
        "setp.lt.u32 p, %1, 64; selp.u32 a, a, u, p; lop3.b32 a, a, %1, 1, 0xF8;\n"
        "setp.lt.u32 p, %1, 124; selp.u32 b, 8, -116, p; add.u32 b, b, %1; setp.lt.u32 p, %1, 120; selp.u32 %0, a, b, p; }" : "=r"(cta) : "r"(id));
    const int chunk = (cta >> 5) * 4 + ((cta >> 2) & 3);
    const int dt = ((cta >> 4) & 1) * 4 + (cta & 3);
    if ((warp | (cta & NCTA)) == 5) {
        mbar_init_n<2>(sb + OFF_FULL, 1);
        tma5b(sb, &mB, 0, dt * 4, sb + OFF_FULL);
        gap();
        tma4(sb + 2 * ABYTES, &mX, 0, chunk * 64, sb + OFF_FULL);
    }
    if (cta >= NCTA) {
        if (smem_u32(smem) != sb) __trap();
        if (tid == 0) wait_count_slow(&prm.s->cnt[0], (atomicAdd(&prm.s->cnt[0], 1u) / NGRID + 1) * NGRID);
        return;
    }
    const bool has_gu = cta >= 16;
    constexpr uint32_t full = sb + OFF_FULL, empty = sb + OFF_EMPTY;
    constexpr uint32_t raw = full + 8 * 32;
    constexpr uint32_t bar_hraw = full + 8 * 97, bar_xs = full + 8 * 98, bar_xb = full + 8 * 100, bar_xa = full + 8 * 101,
        bar_retry = full + 8 * 102, bar_out = full + 8 * 104;
    constexpr uint32_t bar_base = empty - 64, bar_init3 = empty - 56, bar_rdone = empty - 48, bar_order0 = empty - 40, bar_init2 = empty - 32,
        bar_vec = empty - 24, bar_epoch = empty - 16, bar_dummy = empty - 8, bar_xs0 = empty + 8 * 69,
        bar_zero = empty + 8 * 70, bar_xafree = empty + 8 * 71, bar_order2 = empty + 8 * 72, bar_dn = empty + 8 * 73, bar_fp = empty + 8 * 74,
        bar_accb = empty + 8 * 76, bar_xbfree = empty + 8 * 78, bar_fold = empty + 8 * 79, bar_st = empty + 8 * 80,
        bar_order1 = empty + 8 * 67, bar_cand = empty + 8 * 68;

    if (warp == 5) {
        tma5b(sb + SLOT, &mB, 64, dt * 4, full + 8);
        tma4(sb + SLOT + 2 * ABYTES, &mX, 64, chunk * 64, full + 8);
        STAMP(31);
        if (lane < 2) mbar_expect_tx(full + 8 * lane, SLOT);
        __syncwarp();
        named_bar(0, 256);
#pragma unroll 1
        for (int i = 2; i < NST; i++) {
            pace_until(cstart + T2 + i * P2);
            tma5b(sb + i * SLOT, &mB, i * 64, dt * 4, full + 8 * i);
            tma4(sb + i * SLOT + 2 * ABYTES, &mX, i * 64, chunk * 64, full + 8 * i);
            STAMPIF(i == 4, 1);
        }
    } else if (warp == 4) {
        mbar_init_n<12>(bar_init2, 4);
        asm volatile("bar.arrive 0, 256;" ::: "memory");
        mbar_init_n<4>(bar_base, 4);
        mbar_init_n<8>(empty + 64, 4);
        *reinterpret_cast<uint2*>(smem + OFF_KEYS + 16) = make_uint2(0, 0);
        asm volatile("bar.arrive 1, 64;" ::: "memory");
        asm volatile("bar.arrive 5, 96;" ::: "memory");
        asm volatile("bar.arrive 6, 96;" ::: "memory");
        mbar_init_n<32>(full + 256, 3);
        if (lane < 2) mbar_arrive(bar_init2);
    } else if ((warp >> 1) == 3) {
        if (warp == 6) {
            mbar_init_n<8>(full + 16, 1);
            if (lane >= 2 && lane < 10) mbar_expect_tx(full + 8 * lane, lane >= RE0 && lane < RE0 + 4 ? SLOT + ABYTES : SLOT);
            __syncwarp();
            asm volatile("bar.arrive 0, 256;" ::: "memory");
        }
        const char* pf0 = (warp & 1) ? (const char*)((cta & 64) ? prm.b_im : prm.b_re) + (cta & 63) * 16384 : (const char*)prm.x + cta * 32768;
        pace_until(cstart + PF1);
        asm volatile("prefetch.global.L2 [%0];" ::"l"(pf0 + (lane & (30 >> (warp & 1) & 30)) * 1024 + (lane & 1) * 128 + 256));
        const int i0 = warp == 6 ? 10 : 21;
        mbar_init_n<11>(full + 8 * i0, 1);
        if (lane >= i0 && lane < i0 + 11) mbar_expect_tx(full + 8 * lane, lane >= GU0 && has_gu ? SLOT + WBYTES : SLOT);
        mbar_init_n<24>(full + 512 + 192 * (warp & 1), 1);
        named_bar(5, 96);
        if (lane == 0) mbar_arrive(bar_init2);
        STAMP(21);
    }
    __syncwarp();

    if (warp >= 8) {
        asm volatile("setmaxnreg.dec.sync.aligned.u32 72;");
        const uint32_t c0 = cstart;
        uint64_t stream;
        asm volatile("createpolicy.fractional.L2::evict_first.b64 %0, 1.0;" : "=l"(stream));
        const int dc = (cta & 15) * 64, dr = (cta >> 4) * 448;
        auto gutile = [&](int i) {
            const int n = i + 3 - GU0;
            if (has_gu) tma3s(sb + OFF_W + (n & 7) * WBYTES, &mW, cta * 32 - 512, n * 32, full + 8 * (i + 3), stream);
        };
        if (warp == 8) {
            named_bar(0, 256);
            asm volatile("prefetch.tensormap [%0];" ::"l"(&mXr));
#pragma unroll 1
            for (int u = 0; u < 2; u++) {
                sleep_until(c0 + R0 + u * R_PACE);
                tma3(sb + OFF_W + u * ABYTES, &mXr, u * 256, cta * 16, full + 8 * (RE0 + u));
            }
            uint32_t dst = sb;
            auto gemm1 = [&](int i, uint32_t tt) {
                mbar_wait(empty + 8 * (i - NST));
                LATE(i, tt);
                pace_until(tt);
                tma5b(dst, &mB, (i & 15) * 64, (i >> 4) * 64 + dt * 4, full + 8 * i);
                tma4(dst + 2 * ABYTES, &mX, (i & 15) * 64, chunk * 64, full + 8 * i);
                dst = dst == sb + (NST - 1) * SLOT ? sb : dst + SLOT;
            };
            mbar_wait(bar_init2);
            uint32_t tt = c0 + TT0;
#pragma unroll 1
            for (int i = NST; i < AB; i++) {
                gemm1(i, tt);
                if (i < 7) tma3(sb + OFF_W + (i - 3) * ABYTES, &mXr, (i - 3) * 256, cta * 16, full + 8 * (i + 1));
                tt += (i & ~3) == RE0 + 4 ? PER + 72 : PER;
            }
            mbar_wait(bar_base);
            const uint32_t base = uni(lds32(sb + OFF_EPOCH + 8));
            tt = base + Sched<AB>::t;
#pragma unroll 1
            for (int i = AB; i < 32; i++) {
                gemm1(i, tt);
                tt += i >= GU0 + 4 ? PER + 36 : PER;
            }
            const char* hsrc = reinterpret_cast<const char*>(prm.s->h) + (size_t)chunk * 524288;
            auto gemm2 = [&](int i, uint32_t d, int freed, uint32_t tt) {
                mbar_wait(empty + 8 * freed);
                LATE(i, tt);
                pace_until(tt);
                bulk_load(d, hsrc, 2 * ABYTES, raw + 8 * i);
                tma5(d + 2 * ABYTES, (i & 4) ? &mCim : &mCre, ((i & 3) + ((i >> 1) & 12)) * 64, dt * 8, full + 8 * i);
                hsrc += 2 * ABYTES;
            };
            for_entries<32, GU0 + 29>(base, [&](int i, uint32_t tt) {
                gemm2(i, dst, i - NST, tt);
                gutile(i);
                dst = dst == sb + (NST - 1) * SLOT ? sb : dst + SLOT;
            });
            for_entries<GU0 + 29, GU0 + 37>(base, [&](int i, uint32_t tt) {
                gemm2(i, dst, i - NST, tt);
                const int n = i - GU0 - 29;
                if ((n & 5) == 1) tma5(sb + OFF_W + (n & 2) * (ABYTES / 2), &mXe, dt * 128 + (n & 2) * 32, chunk * 64, bar_xa);
                else if (n < 6) asm volatile(ONE "cp.async.bulk.prefetch.tensor.2d.L2.global [%0, {%1, %2}]; }" ::"l"(&mWd), "r"(dc), "r"(dr + 64 * (n < 4 ? 3 + n / 2 : n + 1)) : "memory");
                dst = dst == sb + (NST - 1) * SLOT ? sb : dst + SLOT;
            });
            static_for<NENT - GU0 - 37>([&](auto u) {
                constexpr int i = GU0 + 37 + u;
                if (i == 60) mbar_wait(bar_out + 56);
                gemm2(i, sb + slot_off(i), i < XE ? i - NST : i == XE ? 71   : i - NST - 1, base + Sched<i>::t);
            });
            STAMP(4);
        } else if (warp == 9) {
#pragma unroll
            for (int u = 0; u < 8; u++) {
                const int row = (u >> 2) * 4 + (lane >> 3);
                asm volatile("cp.async.cg.shared.global [%0], [%1], 16;" ::"r"(sb + OFF_XS + (u & 3) * 1024 + row * 128 + (((lane & 7) ^ row) << 4)),
                             "l"((const char*)(u < 4 ? prm.w_r : prm.gate_w) + (u & 3) * 512 + lane * 16) : "memory");
            }
            uint32_t ticket = 0;
            if (lane == 0) ticket = atomicAdd(&prm.s->cnt[0], 1u);
            named_bar(1, 64);
            if (lane == 0) *reinterpret_cast<volatile uint32_t*>(smem + OFF_EPOCH) = ticket / NGRID;
            __syncwarp();
            if (lane < 4) mbar_arrive(bar_epoch);
            asm volatile("cp.async.wait_all;" ::: "memory");
            asm volatile("fence.proxy.async.shared::cta;" ::: "memory");
            __syncwarp();
            if (lane < 4) mbar_arrive(bar_vec);
            STAMP(18);
#pragma unroll 1
            for (int i = 4; i < 22; i++) mbar_init_n<4>(empty + 32 * i, 4, i >= 6 && i < 13);
            if (lane < 2) mbar_arrive(bar_init3);
            STAMP(19);
            mbar_wait(bar_cand);
            {
                const uint32_t* list = reinterpret_cast<const uint32_t*>(smem + OFF_LIST);
                const int n = (int)lds32(sb + OFF_KEYS + 16);
#pragma unroll 1
                for (int i0 = 0; i0 < n; i0 += 32) {
                    const uint32_t k = list[i0 + lane];
                    int rank = 0;
#pragma unroll 2
                    for (int o = 0; o < n; o += 4) {
                        const uint4 l4 = *reinterpret_cast<const uint4*>(list + o);
                        rank += (l4.x > k) + (l4.y > k) + (l4.z > k) + (l4.w > k);
                    }
                    if (rank < 8) reinterpret_cast<uint32_t*>(smem + OFF_SEL)[rank] = k;
                }
                __syncwarp();
                STAMP(6);
                const uint32_t key = lds32(sb + OFF_SEL + 4 * (lane & 7)), tok = ~key & 2047u, tag = lds32(sb + OFF_EPOCH) + 1;
                const uint32_t ta = __shfl_sync(0xffffffffu, tok, lane >> 3), tb = __shfl_sync(0xffffffffu, tok, 4 + (lane >> 3));
                const uint32_t da = sb + OFF_XS + (lane >> 3) * 128 + (((lane & 7) ^ (lane >> 3)) << 4), db = (da ^ 64) + 512;
                const char *sa = (const char*)prm.x + ta * 2048 + (lane & 7) * 16, *sc = (const char*)prm.x + tb * 2048 + (lane & 7) * 16;
#pragma unroll
                for (int u = 0; u < 16; u++) {
                    asm volatile("cp.async.cg.shared.global [%0], [%1], 16;" ::"r"(da + u * 1024), "l"(sa + u * 128) : "memory");
                    asm volatile("cp.async.cg.shared.global [%0], [%1], 16;" ::"r"(db + u * 1024), "l"(sc + u * 128) : "memory");
                    if (u == 3) {
                        asm volatile("cp.async.wait_all;" ::: "memory");
                        asm volatile("fence.proxy.async.shared::cta;" ::: "memory");
                        __syncwarp();
                        if (lane < 4) mbar_arrive(bar_xs0);
                        STAMP(17);
                    }
                }
                if ((tok >> 7) == (uint32_t)chunk) {
                    float4* zp = reinterpret_cast<float4*>(prm.out + tok * D_ + dt * 128) + (lane >> 3) * 2;
#pragma unroll
                    for (int u = 0; u < 8; u++) zp[(u >> 1) * 8 + (u & 1)] = make_float4(0.f, 0.f, 0.f, 0.f);
                }
                uint32_t it = 0;
                unsigned long long u;
                do {
                    u = ld_relaxed1(&prm.s->gpack[tok >> 1]);
                    if (++it > SPIN_LIMIT) __trap();
                } while (!__all_sync(0xffffffffu, (uint32_t)(u >> 32) == tag));
                const uint32_t kb = key >> 16;
                const float r = bf_lo((kb & 0x8000u) ? (kb & 0x7FFFu) : (~kb & 0xFFFFu)), gv = (tok & 1) ? bf_hi((uint32_t)u) : bf_lo((uint32_t)u);
                reinterpret_cast<float*>(smem + OFF_FAC)[lane & 7] = rbf(1.0f - gv) * rbf(sigmoidf_(r));
                asm volatile("cp.async.wait_all;" ::: "memory");
                asm volatile("fence.proxy.async.shared::cta;" ::: "memory");
                __syncwarp();
                if (lane == 0) mbar_arrive(bar_xs);
                STAMP(7);
            }
            char* hd = reinterpret_cast<char*>(prm.s->h) + (size_t)chunk * 524288 + (dt >> 1) * 16384 + (dt & 1) * 4096;
            mbar_wait(bar_base);
            const uint32_t cb = uni(lds32(sb + OFF_EPOCH + 8)) + ST_SHIFT;
            uint32_t tt = cb + Sched<GU0 + 4>::t;
#pragma unroll 1
            for (int np = 0; np < 16; np++) {
                if (!(np & (np & 4 ? 1 : 2))) mbar_wait(bar_st + 4 * (np & 12) + ((np & 3) ? 8 : 0));
                const uint32_t now = clk32() - ST_TOL;
#pragma unroll 1
                while ((int)(tt - now) < 0) tt += PER + 36;
                const uint32_t src = sb + OFF_STG + (np & 3) * 4096;
                pace_until(tt);
                bulk_store(hd, src, 4096);
                asm volatile("cp.async.bulk.commit_group;" ::: "memory");
                if (np & 2) {
                    if (np & 1) asm volatile("cp.async.bulk.wait_group.read 0;" ::: "memory");
                    else asm volatile("cp.async.bulk.wait_group.read 1;" ::: "memory");
                    __syncwarp();
                    const uint32_t u8 = 4 * (np & 12) + 8 * (np & 1);
                    if (lane < 2) mbar_arrive(lane ? (np < 15 ? empty + 8 * 27 + 4 * u8 : bar_dummy) : bar_out + u8);
                }
                STAMPIF(np & 2, 8 + ((np >> 1) & 6) + (np & 1));
                hd += (np & 1) ? 65536 - 8192 : 8192;
                tt += PER + 36;
            }
#pragma unroll 1
            for (int u = 0; u < 2; u++) {
                pace_until(tt);
                tma5(sb + OFF_STG + u * ABYTES, &mXe, dt * 128 + u * 64, chunk * 64 + 8, bar_xb);
                tt += PER + 36;
            }
            wait_count(&prm.s->cnt[32], (lds32(sb + OFF_EPOCH) + 1) * NCTA);
            auto load_hid = [&]() {
                if (lane == 0) mbar_expect_tx(bar_hraw, 7168);
                bulk_load(sb + OFF_XS, prm.s->hid + dr, 7168, bar_hraw);
            };
            static_for<7>([&](auto u) {
                if (u != 2) mbar_wait(u == 1 ? bar_xbfree : empty + 8 * (u == 0 ? GU0 + 31 : u == 3 ? FIN + DNL : FIN - 2 + u));
                if (u < 3) sleep_until(cb + Sched<GU0 + HGE - 2 + u>::t);
                if (u == 2) load_hid();
                tma2(sb + dn_off(u), &mWd, dc, dr + u * 64, bar_dn, stream);
                if (u == 2) {
                    const uint32_t t2 = lds32(sb + OFF_EPOCH) + 1, tagw = (t2 & 1) | ((t2 & 2) << 15);
#pragma unroll 1
                    for (uint32_t it = 0;; it++) {
                        mbar_wait(bar_hraw, it & 1);
                        uint32_t bad = 0;
#pragma unroll
                        for (int i = 0; i < 14; i++) bad |= lds32(sb + OFF_XS + i * 512 + lane * 16 + (lane >> 3) * 4) ^ tagw;
                        if (__all_sync(0xffffffffu, (bad & 0x00010001u) == 0)) break;
                        if (it > SPIN_LIMIT) __trap();
                        load_hid();
                    }
                    if (lane < 4) mbar_arrive(bar_zero);
                    STAMP(48);
                }
            });
            STAMP(27);
        } else {
            named_bar(6, 96);
            if (warp == 10) {
                const char* pb = (const char*)((cta & 64) ? prm.b_im : prm.b_re) + (cta & 63) * 16384;
                const char* pf = (lane < 16 ? (const char*)prm.x + cta * 32768 : pb) + (lane & 15) * 2048 + 512;
#pragma unroll 1
                for (int k = 0; k < 11; k++) {
                    sleep_until(c0 + PF0 + k * PFX_PACE);
                    if (lane < 16 ? k < 6 : lane < 24 && !(k & 1)) prefetch_l2(pf + k * (lane < 16 ? 256 : 128));
                }
#pragma unroll 1
                for (int k = 0; k < 12; k++) {
                    sleep_until(c0 + Sched<12>::t + ST_SHIFT + (k + BP1 - 12) * PER);
                    bulk_prefetch((k < 4 ? pb + 1048576 : (const char*)(k < 8 ? prm.c_re : prm.c_im) + cta * 16384) + (k & 3) * 4096, 4096);
                    if (k == 4) { mbar_wait(bar_init2); mbar_wait(bar_init3); }
                    if (k >= 4 && lane < 8) mbar_expect_tx(full + 8 * (8 * k + lane), 8 * k + lane < GU0 + 32 && has_gu ? 2 * ABYTES + WBYTES : 2 * ABYTES);
                }
                asm volatile("prefetch.tensormap [%0];" ::"l"(&mCre));
                asm volatile("prefetch.tensormap [%0];" ::"l"(&mCim));
                asm volatile("prefetch.tensormap [%0];" ::"l"(&mWd));
                asm volatile("prefetch.tensormap [%0];" ::"l"(&mXe));
                if (lane < 2) mbar_expect_tx(bar_xb + 8 * lane, 2 * ABYTES);
                mbar_wait(bar_xs);
                mbar_wait(bar_st);
                if (lane == 0) red_release(&prm.s->cnt[32]);
                __syncwarp();
                STAMP(22);
            } else {
                asm volatile("prefetch.tensormap [%0];" ::"l"(&mW));
                mbar_wait(bar_epoch);
                const uint32_t tag = lds32(sb + OFF_EPOCH) + 1;
                st_cell(prm.s->time + cta, 0, 0, 0, 0, lane == 0);
                mbar_wait(empty + 8 * AE);
                uint32_t gown, tm[4][4] = {}, it = 0;
                asm volatile("mov.u32 %0, %%globaltimer_lo;" : "=r"(gown));
                const uint32_t town = clk32();
                st_cell(prm.s->time + cta, tag, town, gown, 0, lane == 0);
                sleep_until(town + AG0);
                do {
#pragma unroll
                    for (int m = 0; m < 4; m++) ld_cell(tm[m], prm.s->time + ((cta & 96) ^ (32 * m)) + lane);
                    if (++it > SPIN_LIMIT) __trap();
                } while (!__all_sync(0xffffffffu, tm[0][0] == tag && tm[1][0] == tag && tm[2][0] == tag && tm[3][0] == tag));
                const int last = __reduce_max_sync(0xffffffffu, max(max((int)(tm[0][2] - gown), (int)(tm[1][2] - gown)), max((int)(tm[2][2] - gown), (int)(tm[3][2] - gown))));
                const uint32_t cand = tm[0][1] + ((min((int)(gown + last - tm[0][2]), 4000) * CLK_NS) >> 8);
                const uint32_t b0 = __shfl_sync(0xffffffffu, cand, cta & 16), b1 = __shfl_sync(0xffffffffu, cand, cta & 30);
                const uint32_t base = (b0 - b1 + 400u < 800u ? b0 : b1) + MARGIN - Sched<AE + NST>::t;
                *reinterpret_cast<volatile uint32_t*>(smem + OFF_EPOCH + 8) = base;
                mbar_wait(bar_init3);
                if (lane < 4) mbar_arrive(bar_base);
                STAMP(23);
                const uint32_t cb = base + W_SHIFT;
                auto early = [&](int i, uint32_t tt) {
                    mbar_wait(empty + 8 * (i - NST));
                    pace_until(tt);
                    gutile(i);
                };
                for_entries<GU0 - 3, GU0 + 4>(cb, early);
                for_entries<GU0 + 4, 32>(cb, early);
            }
            mbar_wait(bar_epoch);
            const uint32_t t2 = lds32(sb + OFF_EPOCH) + 1, tagw = (t2 & 1) | ((t2 & 2) << 15), half = (warp & 1) * ABYTES;
            const uint32_t lo = half + lane * 32 + (lane & 4) * 4 + (lane >> 3) * 4, retry = bar_retry + (warp & 1) * 8;
            const bool leader = lane == 0;
            uint32_t slot = sb + (32 % NST) * SLOT, rpar = 0;
#pragma unroll 1
            for (int i = 32; i < NENT; i++) {
                const uint32_t src = i == XE ? sb + OFF_W : slot;
                if (i != XE) slot = slot == sb + (NST - 1) * SLOT ? sb : slot + SLOT;
                auto current = [&]() {
                    uint32_t v[8];
#pragma unroll
                    for (int u = 0; u < 8; u++) v[u] = lds32(src + lo + u * 1024);
#pragma unroll
                    for (int u = 0; u < 8; u += 2) asm("lop3.b32 %0, %0, %1, %2, 0x7e;" : "+r"(v[u]) : "r"(v[u + 1]), "r"(tagw));
                    return __all_sync(0xffffffffu, ((v[0] | v[2] | v[4] | v[6]) & 0x00010001u) == 0);
                };
                mbar_wait(raw + 8 * i);
                if (!current()) {
#pragma unroll 1
                    for (uint32_t it = 0;; it++) {
                        if (it > SPIN_LIMIT) __trap();
                        STAMP(16);
                        if (leader) mbar_expect_tx(retry, ABYTES);
                        bulk_load(src + half, reinterpret_cast<const char*>(prm.s->h) + (size_t)chunk * 524288 + (i - 32) * 16384 + half, ABYTES, retry);
                        mbar_wait(retry, rpar);
                        rpar ^= 1;
                        if (current()) break;
                    }
                }
                if (leader) mbar_arrive(full + 8 * i);
            }
        }
    } else {
        asm volatile("setmaxnreg.inc.sync.aligned.u32 216;");
        const int wg = warp >> 2, w = warp & 3, g = lane >> 2, c = lane & 3, at = tid & 127;
        float facc[4];
        float2 a[2], m0[2], a32[2], a128[2];
        auto load_const = [&]() {
            const float2* cp = reinterpret_cast<const float2*>(smem + OFF_CONST) + wg * 64 + w * 8 + g;
#pragma unroll
            for (int h = 0; h < 2; h++) { a[h] = cp[32 * h]; m0[h] = cp[128 + 32 * h]; a32[h] = cp[256 + 32 * h]; a128[h] = cp[384 + 32 * h]; }
        };
        if (wg == 0) {
            named_bar(0, 256);
            STAMPIF(tid == 0, 20);
        } else {
            const int pc = (at >> 5) * 256 + dt * 32 + (at & 31);
            const float lr = __bfloat162float(prm.lam_re[pc]), li = __bfloat162float(prm.lam_im[pc]), ld = __bfloat162float(prm.log_dt[pc]);
            const uint32_t dk = __ldg(reinterpret_cast<const uint32_t*>(prm.dskip + dt * 128) + (at & 63));
#pragma unroll
            for (int i = 0; i < 4; i++) sts128(sb + OFF_LIST + i * 2048 + at * 16, 0u, 0u, 0u, 0u);

            {
                reinterpret_cast<uint32_t*>(smem + OFF_DK)[at & 63] = dk;
                const float dtv = rbf(expf(ld));
                const float er = expf(dtv * lr);
                float sn, cs;
                sincospif(dtv * li * 0.318309886183790672f, &sn, &cs);
                const float ar = er * cs, ai = er * sn;
                const float nr = ar - 1.0f, ni = ai;
                const bool big = fabsf(lr) >= fabsf(li);
                const float t = (big ? li : lr) / (big ? lr : li), dn = big ? lr + li * t : lr * t + li;
                const float cr = (big ? nr + ni * t : nr * t + ni) / dn, ci = (big ? ni - nr * t : ni * t - nr) / dn;
                float2* cp = reinterpret_cast<float2*>(smem + OFF_CONST) + at;
                float2 pw = make_float2(ar, prm.swapped ? ai : -ai);
                cp[0] = pw;
                cp[128] = make_float2(prm.swapped ? -2.f * cr : 2.f * cr, -2.f * ci);
#pragma unroll
                for (int i = 1; i <= 7; i++) {
                    pw = cmul(pw, pw);
                    if (i == 5) cp[256] = pw;
                    if (i == 7) cp[384] = pw;
                }
                __syncwarp();
            }
            named_bar(2, 128);
            load_const();
            mbar_wait(bar_epoch);
            const uint32_t tag = *reinterpret_cast<volatile uint32_t*>(smem + OFF_EPOCH) + 1;
            asm volatile("st.relaxed.gpu.global.b64 [%0], %1;" ::"l"(&prm.s->carry[(chunk >> 2) * 4096 + pc * 4 + (chunk & 3)]), "l"((unsigned long long)(tag + 2)) : "memory");
            if (w == 2) st_cell(lane < 4 ? (uint4*)prm.s->rpack + cta * 4 + lane : (uint4*)prm.s->gpack + cta * 4 + (lane & 3), 0, 0, 0, 0, lane < 8);
            {
                const uint32_t nt = ((tag & 1) | ((tag & 2) << 15)) ^ 0x00010001u;
                st_cell(prm.s->hid + cta * 32 - 512 + lane, nt, nt, nt, nt, has_gu && w == 3);
            }
            named_bar(2, 128);
            if (at < 2) mbar_arrive(bar_init3);
            unsigned long long* pub = (w ? prm.s->gpack : prm.s->rpack) + cta * 8 + lane;
            asm volatile("" : "+l"(pub));
            STAMPIF(lane == 0, 52);
            mbar_wait(bar_rdone);

            if (w < 2) {
                const float2* red = reinterpret_cast<const float2*>(smem + OFF_RED) + w * 8 + (lane & 7);
                const float2 r0 = red[0], r1 = red[16], r2 = red[32], r3 = red[48];
                const float v0 = (r0.x + r1.x) + (r2.x + r3.x), v1 = (r0.y + r1.y) + (r2.y + r3.y);
                uint32_t pk2;
                if (w == 0) {
                    pk2 = pack_bf(v0, v1);
                    pk2 ^= (((pk2 >> 15) & 0x00010001u) * 0x7FFFu) ^ 0x80008000u;
                } else pk2 = pack_bf(sigmoidf_(rbf(v0)), sigmoidf_(rbf(v1)));
                if (lane < 8) asm volatile("st.relaxed.gpu.global.b64 [%0], %1;" ::"l"(pub), "l"(((unsigned long long)tag << 32) | pk2) : "memory");
                __syncwarp();
            }
            STAMPIF(at == 0, 24);
            uint32_t it = 0, pr[8], g1;
            mbar_wait(bar_init3);
            sleep_until(clk32() + (w < 2 ? G0 : G0 + 250));
            while (true) {
                bool ok = true;
#pragma unroll
                for (int k = 0; k < 4; k++) {
                    const ulonglong2 u = ld_relaxed2(&prm.s->rpack[k * 256 + 2 * at]);
                    ok = ok && (uint32_t)(u.x >> 32) == tag && (uint32_t)(u.y >> 32) == tag;
                    pr[2 * k] = (uint32_t)u.x; pr[2 * k + 1] = (uint32_t)u.y;
                }
                const unsigned long long u1 = ld_relaxed1(&prm.s->gpack[chunk * 64 + (at & 63)]);
                ok = ok && (uint32_t)(u1 >> 32) == tag;
                g1 = (uint32_t)u1;
                if (__all_sync(0xffffffffu, ok)) break;
                if (++it > SPIN_LIMIT) __trap();
            }
            STAMPIF(lane == 0, 25);
            uint32_t m = __vmaxu2(__vimax3_u16x2(__vimax3_u16x2(pr[0], pr[1], pr[2]), pr[3], pr[4]), __vimax3_u16x2(pr[5], pr[6], pr[7]));
            m = (max(m, m << 16) & 0xFFFF0000u) | (uint32_t)lane;
            const uint32_t m1 = __reduce_max_sync(0xffffffffu, m), m2 = __reduce_max_sync(0xffffffffu, m == m1 ? 0u : m);
            uint32_t* keys = reinterpret_cast<uint32_t*>(smem + OFF_KEYS);
            if (lane == 0) keys[w] = m2;
            sts128(sb + OFF_XS + 4096 + at * 16, pr[0], pr[1], pr[2], pr[3]);
            sts128(sb + OFF_XS + 6144 + at * 16, pr[4], pr[5], pr[6], pr[7]);
            *reinterpret_cast<uint32_t*>(smem + OFF_G + 4 * (at & 63)) = g1;
            named_bar(2, 128);
            const uint4 th4 = *reinterpret_cast<const uint4*>(keys);
            const uint32_t th = (max(min(min(th4.x, th4.y), min(th4.z, th4.w)) >> 16, 1u) - 1u) * 0x00010001u;
            uint32_t mask = 0;
#pragma unroll
            for (int k = 7; k >= 0; k--) mask = mask * 2 + __vminu2(__vmaxu2(pr[k], th) ^ th, 0x00010001u);
            uint32_t pos = 0;
            asm volatile("{ .reg .pred p; setp.ne.u32 p, %2, 0; @p atom.shared.add.u32 %0, [%1], %2; }" : "+r"(pos) : "r"(sb + OFF_KEYS + 16), "r"(__popc(mask)) : "memory");
            while (mask) {
                const int bit = __ffs(mask) - 1, k = bit & 7, hi = bit >> 4;
                mask &= mask - 1;
                const uint32_t sc = *reinterpret_cast<const uint16_t*>(smem + OFF_XS + 4096 + (k >> 2) * 2048 + at * 16 + (k & 3) * 4 + hi * 2);
                *reinterpret_cast<uint32_t*>(smem + OFF_LIST + 4 * pos++) = (sc << 16) | (0x8000u + 2047u - (uint32_t)((k >> 1) * 512 + 4 * at + 2 * (k & 1) + hi));
            }
            __syncwarp();
            if (lane == 0) mbar_arrive(bar_cand);
            STAMPIF(lane == 0, 26);
            mbar_wait(bar_order0);
        }

        float accA[64], accB[64];
        Ring ring = {bar_dummy, wg};
        {
            run_entries<0, 0>(ring, wg * 16, wg ? GU0 : RE0, accA, accB, facc, true);
            if (wg == 0) {
                float racc[4];
                mbar_wait(bar_vec);
                run_entries<0, 1>(ring, RE0, RE0 + 4, accA, accB, racc, false, true);
                mbar_wait(bar_init2);
                const uint32_t red = sb + OFF_RED + 4 * (w * 32 + (c >> 1) * 16 + g);
                run_entries<0, 0>(ring, RE0 + 4, RE0 + 5, accA, accB, facc, false, false, [&]() {
                    pin4(racc);
                    asm volatile("{ .reg .pred p; setp.ne.u32 p, %3, 0; @p st.shared.f32 [%0], %1; @p st.shared.f32 [%0 + 32], %2; }" ::"r"(red),
                                 "f"((w & 1) ? racc[1] : racc[0]), "f"((w & 1) ? racc[3] : racc[2]), "r"((uint32_t)((c & 1) == (w >> 1))) : "memory");
                    __syncwarp();
                    if (lane == 0) mbar_arrive(bar_rdone);
                    STAMPIF(lane == 0, 5);
                });
                run_entries<0, 0>(ring, RE0 + 5, 16, accA, accB, facc);
                if (lane == 0) mbar_arrive(bar_order0);
                mbar_wait(bar_init3);
                load_const();
                named_bar(3, 128);
            } else {
#pragma unroll
                for (int u = 0; u < 2; u++) {
                    mbar_wait(u ? bar_xs : bar_xs0);
                    run_entries<0, 2>(ring, GU0 + 8 * u, u ? 32 : GU0 + 8, accA, accB, facc, false, u == 0);
                }
                if (lane == 0) mbar_arrive(bar_order1);
            }
        }
        const uint32_t tag = *reinterpret_cast<volatile uint32_t*>(smem + OFF_EPOCH) + 1;
        const float2 a64[2] = {cmul(a32[0], a32[0]), cmul(a32[1], a32[1])};
        wgmma_wait<0>();
        pin64(accA); pin64(accB); pin4(facc);
        if (lane == 0) mbar_arrive(ring.prev);
        STAMPIF(at == 0, 28 + wg);
        GSTAMP(tid == 0, 1);

        const int tl = 32 * (g >> 1) + (g & 1) + 4 * w + 16 * wg, t0 = chunk * 128 + tl;
        float* op = prm.out + (size_t)t0 * D_ + dt * 128 + 4 * c;
        uint2 xv[8][2], dk[8];
        uint32_t gp[2], om[2], routed[2];
        auto row_setup = [&]() {
            const uint4 sa = *reinterpret_cast<const uint4*>(smem + OFF_SEL), sc = *reinterpret_cast<const uint4*>(smem + OFF_SEL + 16);
#pragma unroll
            for (int r = 0; r < 2; r++) {
                const uint32_t id = 0x8000u + 2047u - (uint32_t)(t0 + 2 * r);
                routed[r] = (uint16_t)sa.x == id || (uint16_t)sa.y == id || (uint16_t)sa.z == id || (uint16_t)sa.w == id ||
                            (uint16_t)sc.x == id || (uint16_t)sc.y == id || (uint16_t)sc.z == id || (uint16_t)sc.w == id;
                gp[r] = reinterpret_cast<const uint16_t*>(smem + OFF_G)[tl + 2 * r] * 0x00010001u;
                om[r] = pack_bf(1.0f - bf_hi(gp[r]), 1.0f - bf_hi(gp[r]));
            }
#pragma unroll
            for (int j = 0; j < 8; j++) dk[j] = lds64(sb + OFF_DK + 32 * j + 8 * c);
        };
        auto release = [&](uint32_t bar) {
            asm volatile("fence.proxy.async.shared::cta;" ::: "memory");
            __syncwarp();
            if (lane == 0) mbar_arrive(bar);
        };

        {
            const uint32_t t2 = tag & 3u;
            float2* cslot = &prm.s->carry[(wg * 512 + dt * 32 + w * 8 + g) * 4];
            const int j1 = chunk - 1 - c;
            unsigned long long v[2][4] = {{t2, t2, t2, t2}, {t2, t2, t2, t2}};
            auto poll = [&](int h) {
#pragma unroll
                for (int m = 0; m < 4; m++)
                    asm volatile("{ .reg .pred p; setp.ge.s32 p, %2, %3; @p ld.relaxed.gpu.global.b64 %0, [%1]; }"
                                 : "+l"(v[h][m]) : "l"(cslot + (j1 >> 2) * 4096 + c - m * 4096 + h * 1024), "r"(j1), "r"(4 * m) : "memory");
            };
            float2 e[2], w0[2];
            auto chain = [&](int h, int s0, int s1) {
                float (&acc)[64] = h ? accB : accA;
                if (s0 == 1) e[h] = make_float2(acc[0], acc[2]);
#pragma unroll
                for (int s = s0; s < s1; s++) {
                    const int i0 = 4 * (s >> 1) + (s & 1);
                    e[h] = cfma(make_float2(a[h].x, -a[h].y), e[h], make_float2(acc[i0], acc[i0 + 2]));
                }
                asm volatile("" : "+f"(e[h].x), "+f"(e[h].y), "+f"(accB[0]), "+f"(accB[2]));
                gap();
            };
            auto publish = [&](int h) {
                float2 f = make_float2(fmaf(m0[h].x, e[h].x, m0[h].y * e[h].y), fmaf(-m0[h].x, e[h].y, m0[h].y * e[h].x));
                float2 y = make_float2(__shfl_up_sync(0xffffffffu, f.x, 1, 4), __shfl_up_sync(0xffffffffu, f.y, 1, 4));
                if (c >= 1) f = cfma(a32[h], y, f);
                y = make_float2(__shfl_up_sync(0xffffffffu, f.x, 2, 4), __shfl_up_sync(0xffffffffu, f.y, 2, 4));
                if (c >= 2) f = cfma(a64[h], y, f);
                asm volatile("{ .reg .pred p; .reg .b64 t; setp.eq.u32 p, %3, 3; mov.b64 t, {%1, %2}; @p st.relaxed.gpu.global.b64 [%0], t; }"
                             ::"l"(cslot + (chunk >> 2) * 4096 + (chunk & 3) + h * 1024), "r"((__float_as_uint(f.x) & ~3u) | t2), "r"(__float_as_uint(f.y)), "r"(c) : "memory");
                w0[h] = make_float2(__shfl_up_sync(0xffffffffu, f.x, 1, 4), __shfl_up_sync(0xffffffffu, f.y, 1, 4));
                if (c == 0) w0[h] = make_float2(0.f, 0.f);
            };
            auto scale = [&](int h, int n0, int n1) {
                float (&acc)[64] = h ? accB : accA;
#pragma unroll
                for (int n = n0; n < n1; n++) {
                    asm volatile("{ .reg .f32 a, b, c, d, n; neg.f32 n, %4; mul.f32 a, %1, %5; mul.f32 b, %0, %5; mul.f32 c, %3, %5; mul.f32 d, %2, %5;\n"
                                 "fma.rn.f32 %0, %0, %4, a; fma.rn.f32 %1, %1, n, b; fma.rn.f32 %2, %2, %4, c; fma.rn.f32 %3, %3, n, d; }"
                                 : "+f"(acc[4 * n]), "+f"(acc[4 * n + 2]), "+f"(acc[4 * n + 1]), "+f"(acc[4 * n + 3]) : "f"(m0[h].x), "f"(m0[h].y));
                    gap();
                }
            };
            auto carry = [&](int h) {
                const float2 one = make_float2(1.f, 0.f), a256 = cmul(a128[h], a128[h]);
                float2 a512 = cmul(a256, a256), pw128 = cmul((j1 & 1) ? a128[h] : one, (j1 & 2) ? a256 : one);
                float2 pw32 = cmul((c & 1) ? a32[h] : one, (c & 2) ? a64[h] : one);
                asm volatile("" : "+f"(a512.x), "+f"(a512.y), "+f"(pw128.x), "+f"(pw128.y), "+f"(pw32.x), "+f"(pw32.y));
                STAMPIF(lane == 0 && !h, 34 + 2 * wg);
                uint32_t it = 0;
                while (!__all_sync(0xffffffffu, ((((uint32_t)v[h][0] ^ t2) | ((uint32_t)v[h][1] ^ t2) | ((uint32_t)v[h][2] ^ t2) | ((uint32_t)v[h][3] ^ t2)) & 3u) == 0)) {
                    poll(h);
                    if (++it > SPIN_LIMIT) __trap();
                }
                STAMPIF(lane == 0 && !h, 35 + 2 * wg);
                float2 hin = make_float2(__uint_as_float((uint32_t)v[h][3]), __uint_as_float((uint32_t)(v[h][3] >> 32)));
#pragma unroll
                for (int m = 2; m >= 0; m--) hin = cfma(a512, hin, make_float2(__uint_as_float((uint32_t)v[h][m]), __uint_as_float((uint32_t)(v[h][m] >> 32))));
                hin = cmul(pw128, hin);
                hin.x += __shfl_xor_sync(0xffffffffu, hin.x, 1); hin.y += __shfl_xor_sync(0xffffffffu, hin.y, 1);
                hin.x += __shfl_xor_sync(0xffffffffu, hin.x, 2); hin.y += __shfl_xor_sync(0xffffffffu, hin.y, 2);
                w0[h] = cfma(pw32, hin, w0[h]);
            };
            chain(0, 1, 32);
            publish(0);
            chain(1, 1, 8);
            STAMPIF(lane == 0, 30 + 2 * wg);
            chain(1, 8, 32);
            publish(1);
            gap();
            scale(0, 0, POLL_S);
            poll(0);
            scale(0, POLL_S, 16);
            carry(0);
            if (wg) mbar_wait(bar_out + 24);
            STAMPIF(lane == 0, 38 + 2 * wg);
            const uint32_t stg = sb + OFF_STG + prm.swapped * 8192 + w * 1024 + (lane & 7) * 128 + (((lane >> 3) ^ (lane & 7)) << 4);
            const uint32_t second = prm.swapped ? -8192 : 8192;
            uint32_t hold = prm.swapped >> 1, last[8];
            const uint32_t keep = c == (g >> 1) ? 0xFFFEFFFEu : 0xFFFFFFFFu, tagw = ((t2 & 1) | ((t2 & 2) << 15)) & ~keep;
#pragma unroll
            for (int h = 0; h < 2; h++) {
                float (&acc)[64] = h ? accB : accA;
                uint32_t ra[16], ia[16];
                if (h) {
                    scale(1, 0, 4);
#pragma unroll
                    for (int u = 0; u < 4; u++) asm volatile("lop3.b32 %0, %0, %1, %2, 0x80;" : "+r"(hold) : "r"(last[u]), "r"(last[4 + u]));
                    release(bar_st + 32 * wg + 8 + hold);
                    poll(1);
                    scale(1, 4, 16);
                    mbar_wait(bar_xs);
                    row_setup();
                    carry(1);
                }
                auto stage = [&](uint32_t (&r)[16], uint32_t base, int j) {
                    stsm4((base ^ ((j & 1) * 64)) + (j >> 1) * 4096, r[4 * j], r[4 * j + 1], r[4 * j + 2], r[4 * j + 3]);
                };
#pragma unroll
                for (int n = 0; n < 16; n++) {
                    const float2 y = cfma(a[h], w0[h], make_float2(acc[4 * n], acc[4 * n + 2]));
                    w0[h] = cfma(a[h], y, make_float2(acc[4 * n + 1], acc[4 * n + 3]));
                    ra[n] = pack_bf(y.x, w0[h].x);
                    ia[n] = pack_bf(y.y, w0[h].y);
                    if (!(n & 1)) { ra[n] = (ra[n] & keep) | tagw; ia[n] = (ia[n] & keep) | tagw; }
                    if (!h && (n & 3) == 3) {
                        if (n > 3) {
                            gap();
#pragma unroll
                            for (int u = n - 7; u < n - 3; u++) asm volatile("lop3.b32 %0, %0, %1, %2, 0x80;" : "+r"(hold) : "r"(ra[u]), "r"(ia[u]));
                        }
                        if (n == 15) {
#pragma unroll
                            for (int u = 0; u < 4; u++) { last[u] = ra[12 + u]; last[4 + u] = ia[12 + u]; }
                        }
                        if (n == 11) { asm volatile("" : "+r"(ra[n]), "+r"(ia[n])); gap(); release(bar_st + 32 * wg); }
                        stage(ra, stg, n >> 2); stage(ia, stg + second, n >> 2);
                        gap();
                    }
                }
                if (h) {
                    STAMPIF(lane == 0, 39 + 2 * wg);
                    mbar_wait(bar_out + 32 * wg);
                    if (prm.swapped) {
#pragma unroll
                        for (int n = 0; n < 16; n++) { const uint32_t t = ra[n]; ra[n] = ia[n]; ia[n] = t; }
                    }
                    const uint32_t st0 = stg - prm.swapped * 8192;
#pragma unroll
                    for (int j = 0; j < 4; j++) stage(ra, st0, j);
                    release(bar_st + 32 * wg + 16);
                    mbar_wait(bar_out + 32 * wg + 8);
#pragma unroll
                    for (int j = 0; j < 4; j++) stage(ia, st0 + 8192, j);
                    release(bar_st + 32 * wg + 24);
                }
                STAMPIF(lane == 0, 42 + 2 * wg + h);
            }
        }

        const uint32_t xr = 2 * (g & 3) + (g >> 2), xa = sb + (wg ? OFF_STG : OFF_W) + (16 * w + xr) * 128 + (((c >> 1) ^ xr) << 4) + (c & 1) * 8;
        auto handover = [&](uint32_t bar) {
            const uint4 z = ldsm4(sb + OFF_KEYS + 16);
            if (lane == 1) mbar_arrive(bar + z.x);
        };
        auto load_x = [&](int j0, int j1) {
#pragma unroll
            for (int j = j0; j < j1; j++)
#pragma unroll
                for (int r = 0; r < 2; r++) xv[j][r] = lds64((xa ^ (32 * (j & 3))) + (j >> 2) * ABYTES + r * 1024);
        };
        auto skip_term = [&](int j0, int j1) {
#pragma unroll
            for (int j = j0; j < j1; j++)
#pragma unroll
                for (int r = 0; r < 2; r++) {
                    xv[j][r].x = mul_bf2(xv[j][r].x, fma_bf2(gp[r], dk[j].x, om[r]));
                    xv[j][r].y = mul_bf2(xv[j][r].y, fma_bf2(gp[r], dk[j].y, om[r]));
                    asm volatile("" : "+r"(xv[j][r].x), "+r"(xv[j][r].y));
                }
        };
        auto finish = [&](float (&acc)[64], int j, bool gaps) {
#pragma unroll
            for (int r = 0; r < 2; r++) {
                const int o = 8 * j + 2 * r;
                const float gv = bf_hi(gp[r]);
                acc[o] = fmaf(gv, acc[o], bf_lo(xv[j][r].x)); acc[o + 1] = fmaf(gv, acc[o + 1], bf_hi(xv[j][r].x));
                acc[o + 4] = fmaf(gv, acc[o + 4], bf_lo(xv[j][r].y)); acc[o + 5] = fmaf(gv, acc[o + 5], bf_hi(xv[j][r].y));
                stg4_unless(op + r * 2 * D_ + 16 * j, acc[o], acc[o + 1], acc[o + 4], acc[o + 5], routed[r] | (NOST >> wg & 1));
                if (gaps) gap();
            }
        };
        auto finish_routed = [&](float (&acc)[64]) {
#pragma unroll
            for (int r = 0; r < 2; r++)
                if (routed[r]) {
#pragma unroll
                    for (int j = 0; j < 8; j++) red4(op + r * 2 * D_ + 16 * j, acc[8 * j + 2 * r], acc[8 * j + 2 * r + 1], acc[8 * j + 2 * r + 4], acc[8 * j + 2 * r + 5]);
                }
            __syncwarp();
        };
        const uint32_t xbuf = sb + slot_off(FIN) + w * 2048 + lane * 16;

        if (wg == 1) {
            float outB[64];
            {
                sts128(sb + OFF_XS + at * 16, __float_as_uint(facc[0]), __float_as_uint(facc[1]), __float_as_uint(facc[2]), __float_as_uint(facc[3]));
                named_bar(2, 128);
                const uint32_t pg = sb + OFF_XS + prm.up_first * 1024 + (at & 63) * 16 + (w >> 1) * 8, pu = pg + 1024 - prm.up_first * 2048;
                const uint2 g1 = lds64(pg), u1 = lds64(pu);
                uint4* hp = prm.s->hid + cta * 32 - 512 + 16 * (w & 1) + 8 * (w >> 1) + g;
                asm volatile("" : "+l"(hp));
                mbar_wait(bar_fp);
                const uint2 g2 = lds64(pg + 2048), u2 = lds64(pu + 2048);
                const float ga = rbf(__uint_as_float(g1.x) + __uint_as_float(g2.x)), gb = rbf(__uint_as_float(g1.y) + __uint_as_float(g2.y));
                uint32_t hw = mul_bf2(pack_bf(__fdividef(ga, 1.0f + __expf(-ga)), __fdividef(gb, 1.0f + __expf(-gb))),
                                      pack_bf(__uint_as_float(u1.x) + __uint_as_float(u2.x), __uint_as_float(u1.y) + __uint_as_float(u2.y)));
                if (c == 2 * (w & 1) + (w >> 1)) hw = (hw & 0xFFFEFFFEu) | (tag & 1) | ((tag & 2) << 15);
                st_cell(hp, hw, __shfl_down_sync(0xffffffffu, hw, 1), __shfl_down_sync(0xffffffffu, hw, 2), __shfl_down_sync(0xffffffffu, hw, 3), has_gu && c == 0);
            }
            STAMPIF(lane == 0, 47);
            mbar_wait(bar_xb);
            load_x(0, 8);
            release(bar_xbfree);
            skip_term(0, 8);
            STAMPIF(lane == 0, 46);
            mbar_wait(bar_order2);
            static_for<NENT - FIN>([&](auto u) {
                run_small<1, FIN + u>(outB);
                if (u == FE) { wgmma_wait<2>(); if (lane == 0) mbar_arrive(bar_fold); }
            });
            wgmma_wait<0>();
            pin64(outB);
            KSTAMP(2 * NENT - FIN);
            STAMPIF(at == 0, 50);
            LT(0);
#pragma unroll
            for (int q = 0; q < 2; q++) {
                uint4 pb[16];
                if (!(q && (FAKE & 1))) mbar_wait(bar_accb + 8 * q);
                if (q) LT(1);
#pragma unroll
                for (int v = q * HP; v < (q ? 16 : HP); v++) pb[v] = ldsm4(xbuf + (v >> 2) * ABYTES + (v & 3) * 512);
#pragma unroll
                for (int v = q * HP; v < (q ? 16 : HP); v++) {
                    outB[4 * v] += __uint_as_float(pb[v].x); outB[4 * v + 1] += __uint_as_float(pb[v].y);
                    outB[4 * v + 2] += __uint_as_float(pb[v].z); outB[4 * v + 3] += __uint_as_float(pb[v].w);
                    if (v & 1) finish(outB, v >> 1, false);
                    if (v == DV) { gap(); if (lane == 0) mbar_expect_tx(bar_dn, w ? 0 : 7 * ABYTES); }
                }
            }
            finish_routed(outB);
            STAMPIF(lane == 0, 51);
            LT(2);
        } else {
            float outA[64], outB[64], gacc[4];
            ring.slot = 32 % NST;
            ring.prev = bar_dummy;
            mbar_wait(bar_order1);
            run_entries<1, 2>(ring, 32, GU0 + 32, outA, outB, gacc, true, true);
            run_entries<1, 0>(ring, GU0 + 32, GU0 + 33, outA, outB, gacc, false, false, [&]() {
                pin4(gacc);
                sts128(sb + OFF_XS + 2048 + at * 16, __float_as_uint(gacc[0]), __float_as_uint(gacc[1]), __float_as_uint(gacc[2]), __float_as_uint(gacc[3]));
                __syncwarp();
                if (lane == 0) mbar_arrive(bar_fp);
            });
            mbar_wait(bar_xa);
            run_entries<1, 0>(ring, GU0 + 33, GU0 + 34, outA, outB, gacc, false, false, [&]() { load_x(0, 2); });
            load_x(2, 4);
            run_entries<1, 0>(ring, GU0 + 34, GU0 + 35, outA, outB, gacc, false, false, [&]() { load_x(4, 6); });
            load_x(6, 8);
            run_entries<1, 0>(ring, GU0 + 35, GU0 + 36, outA, outB, gacc, false, false, [&]() { release(bar_xafree); });
            run_entries<1, 0>(ring, GU0 + 36, FIN, outA, outB, gacc);
            auto dump = [&](int v) {
                stsm4(xbuf + (v >> 2) * ABYTES + (v & 3) * 512, __float_as_uint(outB[4 * v]), __float_as_uint(outB[4 * v + 1]), __float_as_uint(outB[4 * v + 2]),
                      __float_as_uint(outB[4 * v + 3]));
            };
            static_for<NENT - FIN>([&](auto u) {
                mbar_wait(full + 8 * (FIN + u));
                run_small<0, FIN + u>(outA);
                if (u == 5 && lane == 0) mbar_arrive(bar_order2);
                wgmma_wait<1>();
                if (lane == 0) mbar_arrive(empty + 8 * (FIN + u - 1));
                if (u == 0) pin64(outB);
                if (u == 2) mbar_wait(empty + 8 * FIN);
                if (u >= 2) dump(u - 2);
                if (u < 4) skip_term(2 * u, 2 * u + 2);
            });
            const uint2 sk = lds64(sb + OFF_SEL + 8 * c), fk = lds64(sb + OFF_FAC + 8 * c);
            float* y0 = prm.out + (~sk.x & 2047u) * D_ + (cta & 15) * 64 + w * 16 + g;
            float* y1 = prm.out + (~sk.y & 2047u) * D_ + (cta & 15) * 64 + w * 16 + g;
            asm volatile("" : "+l"(y0), "+l"(y1));
            handover(bar_accb);
            wgmma_wait<0>();
            pin64(outA);
            STAMPIF(at == 0, 53);
            GSTAMP(at == 0, 2);
#pragma unroll
            for (int j = 0; j < 8; j++) {
                finish(outA, j, true);
            }
            STAMPIF(lane == 0, 54);
            LT(0);
            mbar_wait(bar_fold);
#pragma unroll
            for (int v = 4; v < (FAKE & 1 ? 4 : 16); v++) dump(v);
            handover(bar_accb + 8);
            STAMPIF(lane == 0, 55);
            finish_routed(outA);
            float yacc[4];
            const uint64_t dw = make_desc(sb), dh = (uint64_t)(((sb + OFF_XS) & 0x3FFFF) >> 4) | ((uint64_t)8 << 16) | ((uint64_t)8 << 32);
            mbar_wait(bar_zero);
            mbar_wait(bar_dn);
            STAMPIF(at == 0, 2);
            LT(1);
            wgmma_fence();
#pragma unroll
            for (int n = 0; n < (FAKE & 2 ? 1 : 28); n++) wgmma_n8<1, 1>(yacc, dw + (dn_off(n >> 2) >> 4) + (n & 3) * 128, dh + n * 16, n > 0);
            wgmma_commit();
            wgmma_wait<0>();
            pin4(yacc);
            LT(2);
            asm volatile("red.global.add.f32 [%0], %2; red.global.add.f32 [%1], %3; red.global.add.f32 [%0 + 32], %4; red.global.add.f32 [%1 + 32], %5;"
                         ::"l"(y0), "l"(y1), "f"(yacc[0] * __uint_as_float(fk.x)), "f"(yacc[1] * __uint_as_float(fk.y)), "f"(yacc[2] * __uint_as_float(fk.x)),
                         "f"(yacc[3] * __uint_as_float(fk.y)) : "memory");
            STAMPIF(lane == 0, 3);
            LT(3);
        }
    }
}

typedef CUresult (*EncodeFn)(CUtensorMap*, CUtensorMapDataType, cuuint32_t, void*, const cuuint64_t*, const cuuint64_t*, const cuuint32_t*,
                             const cuuint32_t*, CUtensorMapInterleave, CUtensorMapSwizzle, CUtensorMapL2promotion, CUtensorMapFloatOOBfill);

bool encode(EncodeFn fn, CUtensorMap* m, const void* ptr, int rank, const cuuint64_t* dims, const cuuint64_t* strides, const cuuint32_t* box,
            CUtensorMapSwizzle sw = CU_TENSOR_MAP_SWIZZLE_128B, CUtensorMapL2promotion promo = CU_TENSOR_MAP_L2_PROMOTION_NONE) {
    const cuuint32_t es[5] = {1, 1, 1, 1, 1};
    return fn(m, CU_TENSOR_MAP_DATA_TYPE_BFLOAT16, rank, const_cast<void*>(ptr), dims, strides, box, es, CU_TENSOR_MAP_INTERLEAVE_NONE,
              sw, promo, CU_TENSOR_MAP_FLOAT_OOB_FILL_NONE) == CUDA_SUCCESS;
}

}

extern "C" void kernel_launch(void* const* d_in, const int* in_sizes, int n_in, void* d_out, int out_size) {
    (void)in_sizes; (void)n_in; (void)out_size;
    Params prm;
    prm.x = (const __nv_bfloat16*)d_in[0];
    prm.lam_re = (const __nv_bfloat16*)d_in[1];
    prm.lam_im = (const __nv_bfloat16*)d_in[2];
    prm.b_re = (const __nv_bfloat16*)d_in[3];
    prm.b_im = (const __nv_bfloat16*)d_in[4];
    prm.c_re = (const __nv_bfloat16*)d_in[5];
    prm.c_im = (const __nv_bfloat16*)d_in[6];
    prm.log_dt = (const __nv_bfloat16*)d_in[7];
    prm.dskip = (const __nv_bfloat16*)d_in[8];
    prm.w_r = (const __nv_bfloat16*)d_in[10];
    prm.gate_w = (const __nv_bfloat16*)d_in[14];
    prm.out = (float*)d_out;
    cudaGetSymbolAddress((void**)&prm.s, g_scratch);
    int dev = 0, sms = 0;
    cudaGetDevice(&dev);
    cudaDeviceGetAttribute(&sms, cudaDevAttrMultiProcessorCount, dev);
    auto kernel = sms == NGRID ? fused_kernel<true> : fused_kernel<false>;
    prm.swapped = prm.b_im < prm.b_re;

    void* fnp = nullptr;
    cudaDriverEntryPointQueryResult qr;
    cudaGetDriverEntryPoint("cuTensorMapEncodeTiled", &fnp, cudaEnableDefault, &qr);
    EncodeFn fn = (EncodeFn)fnp;
    cudaFuncSetAttribute(kernel, cudaFuncAttributeMaxDynamicSharedMemorySize, SMEM_BYTES);

    CUtensorMap mX, mB, mCre, mCim, mW, mWd, mXr, mXe;
    const cuuint64_t row = 2048;
    {
        const cuuint64_t dims[4] = {1024, 2, 4, 976}, st[3] = {row, 32 * row, 2 * row};
        const cuuint32_t box[4] = {64, 2, 4, 16};
        encode(fn, &mX, prm.x, 4, dims, st, box, CU_TENSOR_MAP_SWIZZLE_128B, PROMO);
    }
    {
        const char *lo = (const char*)(prm.swapped ? prm.b_im : prm.b_re), *hi = (const char*)(prm.swapped ? prm.b_re : prm.b_im);
        const cuuint64_t dims[5] = {1024, 8, 2, 96, 2}, st[4] = {row, (cuuint64_t)(hi - lo), 8 * row, 256 * row};
        const cuuint32_t box[5] = {64, 8, 2, 4, 2};
        encode(fn, &mB, lo, 5, dims, st, box, CU_TENSOR_MAP_SWIZZLE_128B, PROMO);
    }
    {
        const cuuint64_t dims[5] = {1024, 2, 4, 2, 64}, st[4] = {row, 4 * row, 2 * row, 16 * row};
        const cuuint32_t box[5] = {64, 2, 4, 2, 8};
        encode(fn, &mCre, prm.c_re, 5, dims, st, box);
        encode(fn, &mCim, prm.c_im, 5, dims, st, box);
    }
    {
        const char *pg = (const char*)d_in[11], *pu = (const char*)d_in[12];
        prm.up_first = pu < pg;
        const cuuint64_t dims[3] = {F_, D_, 2}, st[2] = {F_ * 2, (cuuint64_t)(pu < pg ? pg - pu : pu - pg)}, dimsd[2] = {D_, F_}, std_[1] = {row};
        const cuuint32_t box[3] = {32, 32, 2}, boxd[2] = {64, 64};
        encode(fn, &mW, pu < pg ? pu : pg, 3, dims, st, box, CU_TENSOR_MAP_SWIZZLE_64B, CU_TENSOR_MAP_L2_PROMOTION_NONE);
        encode(fn, &mWd, d_in[13], 2, dimsd, std_, boxd, CU_TENSOR_MAP_SWIZZLE_128B, CU_TENSOR_MAP_L2_PROMOTION_NONE);
    }
    {
        const cuuint64_t dims[3] = {D_ - 192, S_, 4}, st[2] = {row, 128};
        const cuuint32_t box[3] = {64, 16, 4};
        encode(fn, &mXr, prm.x, 3, dims, st, box, CU_TENSOR_MAP_SWIZZLE_128B, CU_TENSOR_MAP_L2_PROMOTION_NONE);
    }
    {
        const cuuint64_t dims[5] = {D_, 2, 2, 2, 976}, st[4] = {64 * row, row, 32 * row, 2 * row};
        const cuuint32_t box[5] = {64, 2, 2, 2, 8};
        encode(fn, &mXe, prm.x, 5, dims, st, box);
    }
    kernel<<<NGRID, 384, SMEM_BYTES, cudaStreamPerThread>>>(prm, mX, mB, mCre, mCim, mW, mWd, mXr, mXe);
}
```

```cpp
#include <cuda_runtime.h>
#include <cuda_bf16.h>
#include <cuda.h>
#include <stdint.h>

namespace {

constexpr int S_ = 2048, D_ = 1024, F_ = 3584;
constexpr int NCTA = 128, NGRID = 132;
#define XE_ 58
#define GU0_ 18
constexpr int NENT = 64, FIN = 58, XE = XE_;
constexpr int NST = 5;
constexpr int RE0 = 4;
constexpr int GU0 = GU0_;
constexpr uint32_t SLOT = 32768, ABYTES = 8192, WBYTES = 4096;
constexpr uint32_t OFF_XS = NST * SLOT;
constexpr uint32_t OFF_LIST = OFF_XS + 8192;
constexpr uint32_t OFF_W = OFF_XS + 16384;
constexpr uint32_t OFF_STG = OFF_W + 32768;
__host__ __device__ constexpr uint32_t slot_off(int i) { return i < XE ? (i % NST) * SLOT : i == XE ? OFF_W : ((i - 1) % NST) * SLOT; }
__host__ __device__ constexpr uint32_t dn_off(int u) { return u == 0 ? OFF_XS + ABYTES : u < 3 ? OFF_STG + (u - 1) * ABYTES : slot_off(FIN - 2 + u); }
__host__ __device__ constexpr uint32_t sum_off(int v) { return slot_off(FIN) + (v >> 2) * ABYTES + (v & 3) * 512; }
constexpr uint32_t OFF_CONST = OFF_STG;
constexpr uint32_t OFF_RED = OFF_STG + 4096;
constexpr uint32_t OFF_FULL = OFF_STG + 16384;
constexpr uint32_t OFF_EMPTY = OFF_FULL + 120 * 8;
constexpr uint32_t OFF_G = OFF_EMPTY + 88 * 8;
constexpr uint32_t OFF_DK = OFF_G + 256;
constexpr uint32_t OFF_KEYS = OFF_DK + 256;
constexpr uint32_t OFF_SEL = OFF_KEYS + 32;
constexpr uint32_t OFF_FAC = OFF_SEL + 32;
constexpr uint32_t OFF_EPOCH = OFF_FAC + 32;
constexpr uint32_t OFF_PROF = OFF_EPOCH + 16;
constexpr uint32_t SMEM_BYTES = OFF_PROF + 768;
static_assert(SMEM_BYTES <= 232448, "smem");

constexpr uint32_t sb = 1024;
constexpr uint32_t SPIN_LIMIT = 1u << 18;

struct Scratch {
    unsigned int cnt[2 * 32];
    unsigned long long rpack[S_ / 2];
    unsigned long long gpack[S_ / 2];
    uint4 time[NCTA];
    float2 carry[16 * 1024];
    uint4 hid[F_];
    uint4 h[8 * 4 * 256 * 64];
};
__device__ __align__(128) Scratch g_scratch;
#define LT(i) do {} while (0)
#define STAMPW(cond, w) do {} while (0)
#define LATE(i, tt) do {} while (0)
#define LANDED(i) do {} while (0)
#define GSTAMP(cond, w) do {} while (0)
#define LP(i) do {} while (0)
#define STAMPIF(cond, i) STAMPW(cond, 72 + (i))
#define STAMP(i) STAMPW(1, 72 + (i))
#define KSTAMP(i) STAMPW((threadIdx.x & 127) == 0, i)

struct Params {
    const __nv_bfloat16 *x, *b_re, *b_im;
    Scratch* s;
    int up_first;
    int swapped;
    const __nv_bfloat16 *lam_re, *lam_im, *c_re, *c_im, *log_dt, *dskip, *w_r, *gate_w;
    float* out;
};

__device__ __forceinline__ uint32_t smem_u32(const void* p) { return (uint32_t)__cvta_generic_to_shared(p); }
__device__ __forceinline__ void mbar_init(uint32_t bar, uint32_t cnt) { asm volatile("mbarrier.init.shared::cta.b64 [%0], %1;" ::"r"(bar), "r"(cnt) : "memory"); }
__device__ __forceinline__ void mbar_expect_tx(uint32_t bar, uint32_t bytes) { asm volatile("mbarrier.arrive.expect_tx.shared::cta.b64 _, [%0], %1;" ::"r"(bar), "r"(bytes) : "memory"); }
__device__ __forceinline__ void mbar_arrive(uint32_t bar) { asm volatile("mbarrier.arrive.shared::cta.b64 _, [%0];" ::"r"(bar) : "memory"); }
__device__ __forceinline__ void mbar_wait(uint32_t bar, uint32_t parity = 0) {
    asm volatile("{ .reg .pred p; .reg .u32 n;\n"
                 "mov.u32 n, 0;\n"
                 "AGAIN: mbarrier.try_wait.parity.shared::cta.b64 p, [%0], %1;\n"
                 "@p bra.uni DONE;\n"
                 "add.u32 n, n, 1;\n"
                 "setp.lt.u32 p, n, %2;\n"
                 "@p bra.uni AGAIN;\n"
                 "trap;\n"
                 "DONE: }" ::"r"(bar), "r"(parity), "n"(SPIN_LIMIT) : "memory");
}
__device__ __forceinline__ bool elect_one() {
    uint32_t pred;
    asm volatile("{ .reg .pred P; elect.sync _|P, 0xffffffff; selp.b32 %0, 1, 0, P; }" : "=r"(pred));
    return pred;
}
__device__ __forceinline__ void named_bar(int id, int n) { asm volatile("bar.sync %0, %1;" ::"r"(id), "r"(n) : "memory"); }

#define ONE "{ .reg .pred e; elect.sync _|e, 0xffffffff;\n@e "
template <int N> __device__ __forceinline__ void mbar_init_n(uint32_t bar, uint32_t cnt, uint32_t extra = 0) {
    if (elect_one()) {
#pragma unroll
        for (int i = 0; i < N; i++) mbar_init(bar + 8 * i, i == N - 1 ? cnt + extra : cnt);
        asm volatile("fence.mbarrier_init.release.cluster;" ::: "memory");
    }
    __syncwarp();
}
__device__ __forceinline__ void bulk_load(uint32_t dst, const void* src, uint32_t bytes, uint32_t bar) {
    asm volatile(ONE "cp.async.bulk.shared::cluster.global.mbarrier::complete_tx::bytes [%0], [%1], %2, [%3]; }" ::"r"(dst), "l"(src), "r"(bytes), "r"(bar) : "memory");
}
__device__ __forceinline__ void sts128(uint32_t a, uint32_t x, uint32_t y, uint32_t z, uint32_t w) {
    asm volatile("st.shared.v4.u32 [%0], {%1,%2,%3,%4};" ::"r"(a), "r"(x), "r"(y), "r"(z), "r"(w) : "memory");
}
__device__ __forceinline__ uint2 lds64(uint32_t a) {
    uint2 v;
    asm volatile("ld.shared.v2.u32 {%0,%1}, [%2];" : "=r"(v.x), "=r"(v.y) : "r"(a) : "memory");
    return v;
}
__device__ __forceinline__ uint32_t clk32() { uint32_t c; asm volatile("mov.u32 %0, %%clock;" : "=r"(c)); return c; }
__device__ __forceinline__ void gap() { asm volatile("pmevent 1;" ::: "memory"); }
__device__ __forceinline__ void pace_until(uint32_t t) { while ((int)(clk32() - t) < 0) {} }
#define SLEEP_MARGIN 200
__device__ __forceinline__ void sleep_until(uint32_t t) {
    while ((int)(clk32() + SLEEP_MARGIN - t) < 0) __nanosleep(40);
    pace_until(t);
}
__device__ __forceinline__ void tma2(uint32_t dst, const CUtensorMap* m, int c0, int c1, uint32_t bar, uint64_t pol) {
    asm volatile(ONE "cp.async.bulk.tensor.2d.shared::cluster.global.mbarrier::complete_tx::bytes.L2::cache_hint [%0], [%1, {%3, %4}], [%2], %5; }"
                 ::"r"(dst), "l"(m), "r"(bar), "r"(c0), "r"(c1), "l"(pol) : "memory");
}
__device__ __forceinline__ void tma3s(uint32_t dst, const CUtensorMap* m, int c0, int c1, uint32_t bar, uint64_t pol) {
    asm volatile(ONE "cp.async.bulk.tensor.3d.shared::cluster.global.mbarrier::complete_tx::bytes.L2::cache_hint [%0], [%1, {%3, %4, %5}], [%2], %6; }"
                 ::"r"(dst), "l"(m), "r"(bar), "r"(c0), "r"(c1), "r"(0), "l"(pol) : "memory");
}
__device__ __forceinline__ void tma3(uint32_t dst, const CUtensorMap* m, int c0, int c1, uint32_t bar) {
    asm volatile(ONE "cp.async.bulk.tensor.3d.shared::cluster.global.mbarrier::complete_tx::bytes [%0], [%1, {%3, %4, %5}], [%2]; }"
                 ::"r"(dst), "l"(m), "r"(bar), "r"(c0), "r"(c1), "r"(0) : "memory");
}
__device__ __forceinline__ void tma4(uint32_t dst, const CUtensorMap* m, int c0, int c3, uint32_t bar) {
    asm volatile(ONE "cp.async.bulk.tensor.4d.shared::cluster.global.mbarrier::complete_tx::bytes [%0], [%1, {%3, %5, %5, %4}], [%2]; }"
                 ::"r"(dst), "l"(m), "r"(bar), "r"(c0), "r"(c3), "r"(0) : "memory");
}
__device__ __forceinline__ void tma5(uint32_t dst, const CUtensorMap* m, int c0, int c4, uint32_t bar) {
    asm volatile(ONE "cp.async.bulk.tensor.5d.shared::cluster.global.mbarrier::complete_tx::bytes [%0], [%1, {%3, %5, %5, %5, %4}], [%2]; }"
                 ::"r"(dst), "l"(m), "r"(bar), "r"(c0), "r"(c4), "r"(0) : "memory");
}
__device__ __forceinline__ void tma5b(uint32_t dst, const CUtensorMap* m, int c0, int c3, uint32_t bar) {
    asm volatile(ONE "cp.async.bulk.tensor.5d.shared::cluster.global.mbarrier::complete_tx::bytes [%0], [%1, {%3, %5, %5, %4, %5}], [%2]; }"
                 ::"r"(dst), "l"(m), "r"(bar), "r"(c0), "r"(c3), "r"(0) : "memory");
}
__device__ __forceinline__ void prefetch_l2(const void* p) {
    asm volatile("cp.async.ca.shared.global.L2::256B [%0], [%1], 4;" ::"r"(sb + OFF_EPOCH + 12), "l"(p) : "memory");
}

__device__ __forceinline__ uint32_t lds32(uint32_t a) {
    uint32_t v;
    asm volatile("ld.volatile.shared.u32 %0, [%1];" : "=r"(v) : "r"(a) : "memory");
    return v;
}
__device__ __forceinline__ uint32_t uni(uint32_t v) { return __shfl_sync(0xffffffffu, v, 0); }   __device__ __forceinline__ uint32_t ld_acquire(const unsigned int* p) {
    uint32_t v;
    asm volatile("ld.acquire.gpu.global.u32 %0, [%1];" : "=r"(v) : "l"(p) : "memory");
    return v;
}
__device__ __forceinline__ void red_release(unsigned int* p) { asm volatile("red.release.gpu.global.add.u32 [%0], 1;" ::"l"(p) : "memory"); }
__device__ __forceinline__ void wait_count(const unsigned int* p, uint32_t target) {
#pragma unroll 1
    for (uint32_t it = 0; it < SPIN_LIMIT; ++it)
        if ((int)(ld_acquire(p) - target) >= 0) return;
    __trap();
}
__device__ __forceinline__ void wait_count_slow(const unsigned int* p, uint32_t target) {
#pragma unroll 1
    for (uint32_t it = 0; it < SPIN_LIMIT; ++it) {
        if ((int)(ld_acquire(p) - target) >= 0) return;
        __nanosleep(200);
    }
    __trap();
}
__device__ __forceinline__ unsigned long long ld_relaxed1(const void* p) {
    unsigned long long v;
    asm volatile("ld.relaxed.gpu.global.b64 %0, [%1];" : "=l"(v) : "l"(p) : "memory");
    return v;
}
__device__ __forceinline__ ulonglong2 ld_relaxed2(const void* p) {
    ulonglong2 v;
    asm volatile("ld.relaxed.gpu.global.v2.b64 {%0, %1}, [%2];" : "=l"(v.x), "=l"(v.y) : "l"(p) : "memory");
    return v;
}
__device__ __forceinline__ void ld_cell(uint32_t (&v)[4], const void* p, bool on = true) {
    asm volatile("{ .reg .pred p; .reg .b64 l, h; .reg .b128 t; setp.ne.u32 p, %5, 0; mov.b64 l, {%0, %1}; mov.b64 h, {%2, %3}; mov.b128 t, {l, h};\n"
                 "@p ld.relaxed.gpu.global.b128 t, [%4]; mov.b128 {l, h}, t; mov.b64 {%0, %1}, l; mov.b64 {%2, %3}, h; }"
                 : "+r"(v[0]), "+r"(v[1]), "+r"(v[2]), "+r"(v[3]) : "l"(p), "r"((uint32_t)on) : "memory");
}
__device__ __forceinline__ void st_cell(void* p, uint32_t a, uint32_t b, uint32_t c, uint32_t d, bool on) {
    asm volatile("{ .reg .pred p; .reg .b64 l, h; .reg .b128 t; setp.ne.u32 p, %5, 0; mov.b64 l, {%1, %2}; mov.b64 h, {%3, %4}; mov.b128 t, {l, h};\n"
                 "@p st.relaxed.gpu.global.b128 [%0], t; }" ::"l"(p), "r"(a), "r"(b), "r"(c), "r"(d), "r"((uint32_t)on) : "memory");
}

__device__ __forceinline__ uint64_t make_desc(uint32_t addr, uint32_t sbo = 1024) {
    return (uint64_t)((addr & 0x3FFFF) >> 4) | ((uint64_t)1 << 16) | ((uint64_t)(sbo >> 4) << 32) | ((uint64_t)1 << 62);
}
__device__ __forceinline__ void wgmma_fence() { asm volatile("wgmma.fence.sync.aligned;" ::: "memory"); }
__device__ __forceinline__ void wgmma_commit() { asm volatile("wgmma.commit_group.sync.aligned;" ::: "memory"); }
template <int N> __device__ __forceinline__ void wgmma_wait() { asm volatile("wgmma.wait_group.sync.aligned %0;" ::"n"(N) : "memory"); }

#define R8(d, i) "+f"(d[i]), "+f"(d[i + 1]), "+f"(d[i + 2]), "+f"(d[i + 3]), "+f"(d[i + 4]), "+f"(d[i + 5]), "+f"(d[i + 6]), "+f"(d[i + 7])
#define R64(d) R8(d, 0), R8(d, 8), R8(d, 16), R8(d, 24), R8(d, 32), R8(d, 40), R8(d, 48), R8(d, 56)
template <int TA>
__device__ __forceinline__ void wgmma_n128(float (&d)[64], uint64_t da, uint64_t db, int scale_d = 1) {
    asm volatile("{ .reg .pred p; setp.ne.b32 p, %66, 0;\n"
                 "wgmma.mma_async.sync.aligned.m64n128k16.f32.bf16.bf16 "
                 "{%0,%1,%2,%3,%4,%5,%6,%7,%8,%9,%10,%11,%12,%13,%14,%15,%16,%17,%18,%19,%20,%21,%22,%23,%24,%25,%26,%27,%28,%29,%30,%31,"
                 "%32,%33,%34,%35,%36,%37,%38,%39,%40,%41,%42,%43,%44,%45,%46,%47,%48,%49,%50,%51,%52,%53,%54,%55,%56,%57,%58,%59,%60,%61,%62,%63}, "
                 "%64, %65, p, 1, 1, %67, 0; }"
                 : R64(d)
                 : "l"(da), "l"(db), "r"(scale_d), "n"(TA));
}
__device__ __forceinline__ void pin4(float (&d)[4]) { asm volatile("" : "+f"(d[0]), "+f"(d[1]), "+f"(d[2]), "+f"(d[3])::"memory"); }
__device__ __forceinline__ void pin64(float (&d)[64]) { asm volatile("" : R64(d)::"memory"); }

template <int TA, int TB = 0>
__device__ __forceinline__ void wgmma_n8(float (&d)[4], uint64_t da, uint64_t db, int scale_d = 1) {
    asm volatile("{ .reg .pred p; setp.ne.b32 p, %7, 0;\n"
                 "wgmma.mma_async.sync.aligned.m64n8k16.f32.bf16.bf16 {%0,%1,%2,%3}, %4, %5, p, 1, 1, %6, %8; }"
                 : "+f"(d[0]), "+f"(d[1]), "+f"(d[2]), "+f"(d[3])
                 : "l"(da), "l"(db), "n"(TA), "r"(scale_d), "n"(TB));
}

__device__ __forceinline__ float bf_lo(uint32_t u) { return __uint_as_float(u << 16); }
__device__ __forceinline__ float bf_hi(uint32_t u) { return __uint_as_float(u & 0xFFFF0000u); }
__device__ __forceinline__ float rbf(float v) { return __bfloat162float(__float2bfloat16_rn(v)); }
__device__ __forceinline__ uint32_t pack_bf(float lo, float hi) {
    uint32_t r;
    asm("cvt.rn.bf16x2.f32 %0, %1, %2;" : "=r"(r) : "f"(hi), "f"(lo));
    return r;
}
__device__ __forceinline__ uint32_t mul_bf2(uint32_t a, uint32_t b) {
    __nv_bfloat162 r = __hmul2(*reinterpret_cast<__nv_bfloat162*>(&a), *reinterpret_cast<__nv_bfloat162*>(&b));
    return *reinterpret_cast<uint32_t*>(&r);
}
__device__ __forceinline__ uint32_t fma_bf2(uint32_t a, uint32_t b, uint32_t c) {
    uint32_t r;
    asm("fma.rn.bf16x2 %0, %1, %2, %3;" : "=r"(r) : "r"(a), "r"(b), "r"(c));
    return r;
}
__device__ __forceinline__ float2 cmul(float2 a, float2 b) { return make_float2(a.x * b.x - a.y * b.y, a.x * b.y + a.y * b.x); }
__device__ __forceinline__ float2 cfma(float2 a, float2 b, float2 c) {
    return make_float2(fmaf(a.x, b.x, fmaf(-a.y, b.y, c.x)), fmaf(a.x, b.y, fmaf(a.y, b.x, c.y)));
}
__device__ __forceinline__ float sigmoidf_(float v) { return __fdividef(1.0f, 1.0f + expf(-v)); }

__device__ __forceinline__ void bulk_prefetch(const void* src, uint32_t bytes) {
    asm volatile(ONE "cp.async.bulk.prefetch.L2.global [%0], %1; }" ::"l"(src), "r"(bytes) : "memory");
}
__device__ __forceinline__ void bulk_store(void* dst, uint32_t src, uint32_t bytes) {
    asm volatile(ONE "cp.async.bulk.global.shared::cta.bulk_group [%0], [%1], %2; }" ::"l"(dst), "r"(src), "r"(bytes) : "memory");
}
__device__ __forceinline__ void stsm4(uint32_t a, uint32_t x, uint32_t y, uint32_t z, uint32_t w) {
    asm volatile("stmatrix.sync.aligned.m8n8.x4.shared.b16 [%0], {%1,%2,%3,%4};" ::"r"(a), "r"(x), "r"(y), "r"(z), "r"(w) : "memory");
}
__device__ __forceinline__ uint4 ldsm4(uint32_t a) {
    uint4 v;
    asm volatile("ldmatrix.sync.aligned.m8n8.x4.shared.b16 {%0,%1,%2,%3}, [%4];" : "=r"(v.x), "=r"(v.y), "=r"(v.z), "=r"(v.w) : "r"(a) : "memory");
    return v;
}
__device__ __forceinline__ void stg4_unless(float* p, float a, float b, float c, float d, uint32_t skip) {
    asm volatile("{ .reg .pred p; setp.eq.u32 p, %5, 0; @p st.global.v4.f32 [%0], {%1,%2,%3,%4}; }" ::"l"(p), "f"(a), "f"(b), "f"(c), "f"(d), "r"(skip) : "memory");
}
__device__ __forceinline__ void red4(float* p, float a, float b, float c, float d) {
    asm volatile("red.global.add.v4.f32 [%0], {%1,%2,%3,%4};" ::"l"(p), "f"(a), "f"(b), "f"(c), "f"(d) : "memory");
}

#define TT0 2900
#define PER 514
#define PCUT 60
#define PFIN 360
#define PF0 1500
#define PFX_PACE 400
#define PF1 700
#define T2 300
#define P2 520
#define G0 450
#define R0 2100
#define R_PACE 350
#define W_SHIFT 250
#define PROMO CU_TENSOR_MAP_L2_PROMOTION_L2_256B
#define POLL_S 0
#define ST_TOL 100
#define ST_SHIFT 300
#define CLK_NS 420
#define MARGIN 150
#define BP1 12
#define DV 15
#define FE 5
#define HP 4
#define AE 6
#define AG0 900
#define AB 16
#define HGE 39
constexpr uint32_t duration(int i) { return PER + (i >= RE0 && i < RE0 + 4 ? 72 : 0) + (i >= GU0 && i < GU0 + 32 ? 36 : 0); }
constexpr uint32_t cmax(uint32_t a, uint32_t b) { return a > b ? a : b; }
constexpr uint32_t issue_time(int i) {
    return i <= NST ? TT0 : i < XE ? issue_time(i - 1) + duration(i - NST) - (i >= XE - 3 && i > GU0 + 36 ? PCUT : 0) : issue_time(XE - 1) + cmax((i - XE + 1) * PFIN, (i - XE) * 512);
}
template <int I> struct Sched { static constexpr uint32_t t = issue_time(I); };
template <int LO, int HI, class F>
__device__ __forceinline__ void for_entries(uint32_t base, F body) {
    constexpr uint32_t per = Sched<LO + 1>::t - Sched<LO>::t;
    static_assert(Sched<HI - 1>::t - Sched<LO>::t == (HI - 1 - LO) * per, "period");
    uint32_t tt = base + Sched<LO>::t;
#pragma unroll 1
    for (int i = LO; i < HI; i++) {
        body(i, tt);
        tt += per;
    }
}

struct Ring { uint32_t prev; int slot; };
struct NoHook { __device__ void operator()() const {} };
template <int TA, int SM, class H = NoHook>
__device__ __forceinline__ void run_entries(Ring& r, int lo, int hi, float (&accA)[64], float (&accB)[64], float (&small)[4],
                                            bool fresh = false, bool sfresh = false, H released = H()) {
    const uint64_t d0 = make_desc(sb);
    const bool leader = (threadIdx.x & 31) == 0;
#pragma unroll 1
    for (int i = lo; i < hi; i++) {
        const uint32_t bar = sb + OFF_FULL + 8 * i;
        const uint64_t da = d0 + (uint64_t)(r.slot * (SLOT >> 4));
        const int n = i - (SM == 1 ? RE0 : GU0);
        const uint64_t dw = SM == 1 ? d0 + (uint64_t)((OFF_W >> 4) + n * 512)
                                    : (((uint64_t)2 << 62) | ((uint64_t)32 << 32) | (128u << 16) | ((sb + OFF_W) >> 4)) + (uint64_t)((n & 7) * 256);
        const uint64_t dt8 = d0 + (uint64_t)((OFF_XS >> 4) + (SM == 1 ? n * 64 : (n >> 1) * 64 + (n & 1) * 4));
        r.slot = r.slot == NST - 1 ? 0 : r.slot + 1;
        mbar_wait(bar);
        KSTAMP(i);
        wgmma_fence();
#pragma unroll
        for (int kk = 0; kk < 4; kk++) {
            wgmma_n128<TA>(accA, da + kk * (TA ? 128 : 2), da + 1024 + kk * 2, kk > 0 || !fresh);
            if (SM == 1) wgmma_n8<0>(small, dw + kk * 2, dt8 + kk * 2, kk > 0 || !sfresh);
            if (SM == 2 && (kk & 1)) wgmma_n8<1>(small, dw + (kk >> 1) * 64, dt8 + (kk >> 1) * 2, kk > 1 || !sfresh);
            wgmma_n128<TA>(accB, da + 512 + kk * (TA ? 128 : 2), da + 1024 + kk * 2, kk > 0 || !fresh);
            if (kk == 1) {
                wgmma_commit();
                wgmma_wait<1>();
                if (leader) mbar_arrive(r.prev);
                released();
            }
        }
        wgmma_commit();
        r.prev = bar + (OFF_EMPTY - OFF_FULL);
        fresh = sfresh = false;
    }
}
template <int HALF, int I>
__device__ __forceinline__ void run_small(float (&acc)[64]) {
    const uint64_t da = make_desc(sb) + (slot_off(I) >> 4);
    KSTAMP(I + HALF * (NENT - FIN));
    wgmma_fence();
#pragma unroll
    for (int kk = 0; kk < 4; kk++) wgmma_n128<1>(acc, da + HALF * 512 + kk * 128, da + 1024 + kk * 2, kk > 0 || !(HALF && I == FIN));
    wgmma_commit();
}
template <int V> struct Int { __host__ __device__ constexpr operator int() const { return V; } };
template <int N, class F> __device__ __forceinline__ void static_for(F f) {
    if constexpr (N > 0) { static_for<N - 1>(f); f(Int<N - 1>()); }
}

template <bool BY_SMID>
__global__ void __launch_bounds__(384, 1)
fused_kernel(const __grid_constant__ Params prm, const __grid_constant__ CUtensorMap mX, const __grid_constant__ CUtensorMap mB, const __grid_constant__ CUtensorMap mCre,
             const __grid_constant__ CUtensorMap mCim, const __grid_constant__ CUtensorMap mW,
             const __grid_constant__ CUtensorMap mWd, const __grid_constant__ CUtensorMap mXr, const __grid_constant__ CUtensorMap mXe) {
    extern __shared__ __align__(1024) uint8_t smem[];
    const uint32_t cstart = clk32();
    const int tid = threadIdx.x, lane = tid & 31;
    uint32_t id = blockIdx.x;
    if (BY_SMID) asm volatile("mov.u32 %0, %%smid;" : "=r"(id));
    {
        const uint32_t o = (tid * 2056) & 0x7880, b = (id & 127) * 8192;
        asm volatile("{ .reg .pred p, q; setp.lt.u32 p, %3, 32; setp.eq.u32 q, %4, 0;\n"
                     "@q prefetch.global.L2 [%1]; @p prefetch.global.L2 [%0]; @q prefetch.global.L2 [%2]; }"
                     ::"l"((const char*)prm.x + (b * 4 + o)), "l"((const char*)prm.b_re + (b + o)), "l"((const char*)prm.b_im + (b + o)), "r"(tid), "r"(tid & ~19) : "memory");
    }
    const int warp = __shfl_sync(0xffffffffu, tid >> 5, 0);
    gap();
    int cta;
    asm("{ .reg .pred p; .reg .u32 a, b, u, q;\n"
        "and.b32 a, %1, 14; shl.b32 a, a, 3; shr.u32 b, %1, 3; and.b32 b, b, 6; add.u32 a, a, b;\n"
        "and.b32 u, %1, 62; mul.lo.u32 q, u, 37; shr.u32 q, q, 9; shl.b32 u, u, 3; mad.lo.u32 u, q, -110, u; add.u32 u, u, 24;\n"
        "setp.lt.u32 p, %1, 64; selp.u32 a, a, u, p; lop3.b32 a, a, %1, 1, 0xF8;\n"
        "setp.lt.u32 p, %1, 124; selp.u32 b, 8, -116, p; add.u32 b, b, %1; setp.lt.u32 p, %1, 120; selp.u32 %0, a, b, p; }" : "=r"(cta) : "r"(id));
    const int chunk = (cta >> 5) * 4 + ((cta >> 2) & 3);
    const int dt = ((cta >> 4) & 1) * 4 + (cta & 3);
    if ((warp | (cta & NCTA)) == 5) {
        mbar_init_n<2>(sb + OFF_FULL, 1);
        tma5b(sb, &mB, 0, dt * 4, sb + OFF_FULL);
        gap();
        tma4(sb + 2 * ABYTES, &mX, 0, chunk * 64, sb + OFF_FULL);
        tma5b(sb + SLOT, &mB, 64, dt * 4, sb + OFF_FULL + 8);
        tma4(sb + SLOT + 2 * ABYTES, &mX, 64, chunk * 64, sb + OFF_FULL + 8);
    }
    if (cta >= NCTA) {
        if (smem_u32(smem) != sb) __trap();
        if (tid == 0) wait_count_slow(&prm.s->cnt[0], (atomicAdd(&prm.s->cnt[0], 1u) / NGRID + 1) * NGRID);
        return;
    }
    const bool has_gu = cta >= 16;
    constexpr uint32_t full = sb + OFF_FULL, empty = sb + OFF_EMPTY;
    constexpr uint32_t raw = full + 8 * 32;
    constexpr uint32_t bar_hraw = full + 8 * 97, bar_xs = full + 8 * 98, bar_xb = full + 8 * 100, bar_xa = full + 8 * 101,
        bar_retry = full + 8 * 102, bar_out = full + 8 * 104;
    constexpr uint32_t bar_base = empty - 64, bar_init3 = empty - 56, bar_rdone = empty - 48, bar_order0 = empty - 40, bar_init2 = empty - 32,
        bar_vec = empty - 24, bar_epoch = empty - 16, bar_dummy = empty - 8, bar_xs0 = empty + 8 * 69,
        bar_zero = empty + 8 * 70, bar_xafree = empty + 8 * 71, bar_order2 = empty + 8 * 72, bar_dn = empty + 8 * 73, bar_fp = empty + 8 * 74,
        bar_accb = empty + 8 * 76, bar_xbfree = empty + 8 * 78, bar_fold = empty + 8 * 79, bar_st = empty + 8 * 80,
        bar_order1 = empty + 8 * 67, bar_cand = empty + 8 * 68;

    if (warp == 5) {
        STAMP(31);
        if (lane < 2) mbar_expect_tx(full + 8 * lane, SLOT);
        __syncwarp();
        named_bar(0, 256);
#pragma unroll 1
        for (int i = 2; i < NST; i++) {
            pace_until(cstart + T2 + i * P2);
            tma5b(sb + i * SLOT, &mB, i * 64, dt * 4, full + 8 * i);
            tma4(sb + i * SLOT + 2 * ABYTES, &mX, i * 64, chunk * 64, full + 8 * i);
            STAMPIF(i == 4, 1);
        }
    } else if (warp == 4) {
        mbar_init_n<12>(bar_init2, 4);
        asm volatile("bar.arrive 0, 256;" ::: "memory");
        mbar_init_n<4>(bar_base, 4);
        mbar_init_n<8>(empty + 64, 4);
        *reinterpret_cast<uint2*>(smem + OFF_KEYS + 16) = make_uint2(0, 0);
        asm volatile("bar.arrive 1, 64;" ::: "memory");
        asm volatile("bar.arrive 5, 96;" ::: "memory");
        asm volatile("bar.arrive 6, 96;" ::: "memory");
        mbar_init_n<32>(full + 256, 3);
        if (lane < 2) mbar_arrive(bar_init2);
    } else if ((warp >> 1) == 3) {
        if (warp == 6) {
            mbar_init_n<8>(full + 16, 1);
            if (lane >= 2 && lane < 10) mbar_expect_tx(full + 8 * lane, lane >= RE0 && lane < RE0 + 4 ? SLOT + ABYTES : SLOT);
            __syncwarp();
            asm volatile("bar.arrive 0, 256;" ::: "memory");
        }
        const char* pf0 = (warp & 1) ? (const char*)((cta & 64) ? prm.b_im : prm.b_re) + (cta & 63) * 16384 : (const char*)prm.x + cta * 32768;
        pace_until(cstart + PF1);
        asm volatile("prefetch.global.L2 [%0];" ::"l"(pf0 + (lane & (30 >> (warp & 1) & 30)) * 1024 + (lane & 1) * 128 + 256));
        const int i0 = warp == 6 ? 10 : 21;
        mbar_init_n<11>(full + 8 * i0, 1);
        if (lane >= i0 && lane < i0 + 11) mbar_expect_tx(full + 8 * lane, lane >= GU0 && has_gu ? SLOT + WBYTES : SLOT);
        mbar_init_n<24>(full + 512 + 192 * (warp & 1), 1);
        named_bar(5, 96);
        if (lane == 0) mbar_arrive(bar_init2);
        STAMP(21);
    }
    __syncwarp();

    if (warp >= 8) {
        asm volatile("setmaxnreg.dec.sync.aligned.u32 72;");
        const uint32_t c0 = cstart;
        uint64_t stream;
        asm volatile("createpolicy.fractional.L2::evict_first.b64 %0, 1.0;" : "=l"(stream));
        const int dc = (cta & 15) * 64, dr = (cta >> 4) * 448;
        auto gutile = [&](int i) {
            const int n = i + 3 - GU0;
            if (has_gu) tma3s(sb + OFF_W + (n & 7) * WBYTES, &mW, cta * 32 - 512, n * 32, full + 8 * (i + 3), stream);
        };
        if (warp == 8) {
            named_bar(0, 256);
            asm volatile("prefetch.tensormap [%0];" ::"l"(&mXr));
#pragma unroll 1
            for (int u = 0; u < 2; u++) {
                sleep_until(c0 + R0 + u * R_PACE);
                tma3(sb + OFF_W + u * ABYTES, &mXr, u * 256, cta * 16, full + 8 * (RE0 + u));
            }
            uint32_t dst = sb;
            auto gemm1 = [&](int i, uint32_t tt) {
                mbar_wait(empty + 8 * (i - NST));
                LATE(i, tt);
                pace_until(tt);
                tma5b(dst, &mB, (i & 15) * 64, (i >> 4) * 64 + dt * 4, full + 8 * i);
                tma4(dst + 2 * ABYTES, &mX, (i & 15) * 64, chunk * 64, full + 8 * i);
                dst = dst == sb + (NST - 1) * SLOT ? sb : dst + SLOT;
            };
            mbar_wait(bar_init2);
            uint32_t tt = c0 + TT0;
#pragma unroll 1
            for (int i = NST; i < AB; i++) {
                gemm1(i, tt);
                if (i < 7) tma3(sb + OFF_W + (i - 3) * ABYTES, &mXr, (i - 3) * 256, cta * 16, full + 8 * (i + 1));
                tt += (i & ~3) == RE0 + 4 ? PER + 72 : PER;
            }
            mbar_wait(bar_base);
            const uint32_t base = uni(lds32(sb + OFF_EPOCH + 8));
            tt = base + Sched<AB>::t;
#pragma unroll 1
            for (int i = AB; i < 32; i++) {
                gemm1(i, tt);
                tt += i >= GU0 + 4 ? PER + 36 : PER;
            }
            const char* hsrc = reinterpret_cast<const char*>(prm.s->h) + (size_t)chunk * 524288;
            auto gemm2 = [&](int i, uint32_t d, int freed, uint32_t tt) {
                mbar_wait(empty + 8 * freed);
                LATE(i, tt);
                pace_until(tt);
                bulk_load(d, hsrc, 2 * ABYTES, raw + 8 * i);
                tma5(d + 2 * ABYTES, (i & 4) ? &mCim : &mCre, ((i & 3) + ((i >> 1) & 12)) * 64, dt * 8, full + 8 * i);
                hsrc += 2 * ABYTES;
            };
            for_entries<32, GU0 + 29>(base, [&](int i, uint32_t tt) {
                gemm2(i, dst, i - NST, tt);
                gutile(i);
                dst = dst == sb + (NST - 1) * SLOT ? sb : dst + SLOT;
            });
            for_entries<GU0 + 29, GU0 + 37>(base, [&](int i, uint32_t tt) {
                gemm2(i, dst, i - NST, tt);
                const int n = i - GU0 - 29;
                if ((n & 5) == 1) tma5(sb + OFF_W + (n & 2) * (ABYTES / 2), &mXe, dt * 128 + (n & 2) * 32, chunk * 64, bar_xa);
                else if (n < 6) asm volatile(ONE "cp.async.bulk.prefetch.tensor.2d.L2.global [%0, {%1, %2}]; }" ::"l"(&mWd), "r"(dc), "r"(dr + 64 * (n < 4 ? 3 + n / 2 : n + 1)) : "memory");
                dst = dst == sb + (NST - 1) * SLOT ? sb : dst + SLOT;
            });
            static_for<NENT - GU0 - 37>([&](auto u) {
                constexpr int i = GU0 + 37 + u;
                if (i == 60) mbar_wait(bar_out + 56);
                gemm2(i, sb + slot_off(i), i < XE ? i - NST : i == XE ? 71   : i - NST - 1, base + Sched<i>::t);
            });
            STAMP(4);
        } else if (warp == 9) {
#pragma unroll
            for (int u = 0; u < 8; u++) {
                const int row = (u >> 2) * 4 + (lane >> 3);
                asm volatile("cp.async.cg.shared.global [%0], [%1], 16;" ::"r"(sb + OFF_XS + (u & 3) * 1024 + row * 128 + (((lane & 7) ^ row) << 4)),
                             "l"((const char*)(u < 4 ? prm.w_r : prm.gate_w) + (u & 3) * 512 + lane * 16) : "memory");
            }
            uint32_t ticket = 0;
            if (lane == 0) ticket = atomicAdd(&prm.s->cnt[0], 1u);
            named_bar(1, 64);
            if (lane == 0) *reinterpret_cast<volatile uint32_t*>(smem + OFF_EPOCH) = ticket / NGRID;
            __syncwarp();
            if (lane < 4) mbar_arrive(bar_epoch);
            asm volatile("cp.async.wait_all;" ::: "memory");
            asm volatile("fence.proxy.async.shared::cta;" ::: "memory");
            __syncwarp();
            if (lane < 4) mbar_arrive(bar_vec);
            STAMP(18);
#pragma unroll 1
            for (int i = 4; i < 22; i++) mbar_init_n<4>(empty + 32 * i, 4, i >= 6 && i < 13);
            if (lane < 2) mbar_arrive(bar_init3);
            STAMP(19);
            mbar_wait(bar_cand);
            {
                const uint32_t* list = reinterpret_cast<const uint32_t*>(smem + OFF_LIST);
                const int n = (int)lds32(sb + OFF_KEYS + 16);
#pragma unroll 1
                for (int i0 = 0; i0 < n; i0 += 32) {
                    const uint32_t k = list[i0 + lane];
                    int rank = 0;
#pragma unroll 2
                    for (int o = 0; o < n; o += 4) {
                        const uint4 l4 = *reinterpret_cast<const uint4*>(list + o);
                        rank += (l4.x > k) + (l4.y > k) + (l4.z > k) + (l4.w > k);
                    }
                    if (rank < 8) reinterpret_cast<uint32_t*>(smem + OFF_SEL)[rank] = k;
                }
                __syncwarp();
                STAMP(6);
                const uint32_t key = lds32(sb + OFF_SEL + 4 * (lane & 7)), tok = ~key & 2047u, tag = lds32(sb + OFF_EPOCH) + 1;
                const uint32_t ta = __shfl_sync(0xffffffffu, tok, lane >> 3), tb = __shfl_sync(0xffffffffu, tok, 4 + (lane >> 3));
                const uint32_t da = sb + OFF_XS + (lane >> 3) * 128 + (((lane & 7) ^ (lane >> 3)) << 4), db = (da ^ 64) + 512;
                const char *sa = (const char*)prm.x + ta * 2048 + (lane & 7) * 16, *sc = (const char*)prm.x + tb * 2048 + (lane & 7) * 16;
#pragma unroll
                for (int u = 0; u < 16; u++) {
                    asm volatile("cp.async.cg.shared.global [%0], [%1], 16;" ::"r"(da + u * 1024), "l"(sa + u * 128) : "memory");
                    asm volatile("cp.async.cg.shared.global [%0], [%1], 16;" ::"r"(db + u * 1024), "l"(sc + u * 128) : "memory");
                    if (u == 3) {
                        asm volatile("cp.async.wait_all;" ::: "memory");
                        asm volatile("fence.proxy.async.shared::cta;" ::: "memory");
                        __syncwarp();
                        if (lane < 4) mbar_arrive(bar_xs0);
                        STAMP(17);
                    }
                }
                if ((tok >> 7) == (uint32_t)chunk) {
                    float4* zp = reinterpret_cast<float4*>(prm.out + tok * D_ + dt * 128) + (lane >> 3) * 2;
#pragma unroll
                    for (int u = 0; u < 8; u++) zp[(u >> 1) * 8 + (u & 1)] = make_float4(0.f, 0.f, 0.f, 0.f);
                }
                uint32_t it = 0;
                unsigned long long u;
                do {
                    u = ld_relaxed1(&prm.s->gpack[tok >> 1]);
                    if (++it > SPIN_LIMIT) __trap();
                } while (!__all_sync(0xffffffffu, (uint32_t)(u >> 32) == tag));
                const uint32_t kb = key >> 16;
                const float r = bf_lo((kb & 0x8000u) ? (kb & 0x7FFFu) : (~kb & 0xFFFFu)), gv = (tok & 1) ? bf_hi((uint32_t)u) : bf_lo((uint32_t)u);
                reinterpret_cast<float*>(smem + OFF_FAC)[lane & 7] = rbf(1.0f - gv) * rbf(sigmoidf_(r));
                asm volatile("cp.async.wait_all;" ::: "memory");
                asm volatile("fence.proxy.async.shared::cta;" ::: "memory");
                __syncwarp();
                if (lane == 0) mbar_arrive(bar_xs);
                STAMP(7);
            }
            char* hd = reinterpret_cast<char*>(prm.s->h) + (size_t)chunk * 524288 + (dt >> 1) * 16384 + (dt & 1) * 4096;
            mbar_wait(bar_base);
            const uint32_t cb = uni(lds32(sb + OFF_EPOCH + 8)) + ST_SHIFT;
            uint32_t tt = cb + Sched<GU0 + 4>::t;
#pragma unroll 1
            for (int np = 0; np < 16; np++) {
                if (!(np & (np & 4 ? 1 : 2))) mbar_wait(bar_st + 4 * (np & 12) + ((np & 3) ? 8 : 0));
                const uint32_t now = clk32() - ST_TOL;
#pragma unroll 1
                while ((int)(tt - now) < 0) tt += PER + 36;
                const uint32_t src = sb + OFF_STG + (np & 3) * 4096;
                pace_until(tt);
                bulk_store(hd, src, 4096);
                asm volatile("cp.async.bulk.commit_group;" ::: "memory");
                if (np & 2) {
                    if (np & 1) asm volatile("cp.async.bulk.wait_group.read 0;" ::: "memory");
                    else asm volatile("cp.async.bulk.wait_group.read 1;" ::: "memory");
                    __syncwarp();
                    const uint32_t u8 = 4 * (np & 12) + 8 * (np & 1);
                    if (lane < 2) mbar_arrive(lane ? (np < 15 ? empty + 8 * 27 + 4 * u8 : bar_dummy) : bar_out + u8);
                }
                STAMPIF(np & 2, 8 + ((np >> 1) & 6) + (np & 1));
                hd += (np & 1) ? 65536 - 8192 : 8192;
                tt += PER + 36;
            }
#pragma unroll 1
            for (int u = 0; u < 2; u++) {
                pace_until(tt);
                tma5(sb + OFF_STG + u * ABYTES, &mXe, dt * 128 + u * 64, chunk * 64 + 8, bar_xb);
                tt += PER + 36;
            }
            wait_count(&prm.s->cnt[32], (lds32(sb + OFF_EPOCH) + 1) * NCTA);
            auto load_hid = [&]() {
                if (lane == 0) mbar_expect_tx(bar_hraw, 7168);
                bulk_load(sb + OFF_XS, prm.s->hid + dr, 7168, bar_hraw);
            };
            static_for<7>([&](auto u) {
                if (u != 2) mbar_wait(u == 1 ? bar_xbfree : empty + 8 * (u == 0 ? GU0 + 31 : FIN - 2 + u));
                if (u < 3) sleep_until(cb + Sched<GU0 + HGE - 2 + u>::t);
                if (u == 2) load_hid();
                tma2(sb + dn_off(u), &mWd, dc, dr + u * 64, bar_dn, stream);
                if (u == 2) {
                    const uint32_t t2 = lds32(sb + OFF_EPOCH) + 1, tagw = (t2 & 1) | ((t2 & 2) << 15);
#pragma unroll 1
                    for (uint32_t it = 0;; it++) {
                        mbar_wait(bar_hraw, it & 1);
                        uint32_t bad = 0;
#pragma unroll
                        for (int i = 0; i < 14; i++) bad |= lds32(sb + OFF_XS + i * 512 + lane * 16 + (lane >> 3) * 4) ^ tagw;
                        if (__all_sync(0xffffffffu, (bad & 0x00010001u) == 0)) break;
                        if (it > SPIN_LIMIT) __trap();
                        load_hid();
                    }
                    if (lane < 4) mbar_arrive(bar_zero);
                    STAMP(48);
                }
            });
            STAMP(27);
        } else {
            named_bar(6, 96);
            if (warp == 10) {
                const char* pb = (const char*)((cta & 64) ? prm.b_im : prm.b_re) + (cta & 63) * 16384;
                const char* pf = (lane < 16 ? (const char*)prm.x + cta * 32768 : pb) + (lane & 15) * 2048 + 512;
#pragma unroll 1
                for (int k = 0; k < 11; k++) {
                    sleep_until(c0 + PF0 + k * PFX_PACE);
                    if (lane < 16 ? k < 6 : lane < 24 && !(k & 1)) prefetch_l2(pf + k * (lane < 16 ? 256 : 128));
                }
#pragma unroll 1
                for (int k = 0; k < 12; k++) {
                    sleep_until(c0 + Sched<12>::t + ST_SHIFT + (k + BP1 - 12) * PER);
                    bulk_prefetch((k < 4 ? pb + 1048576 : (const char*)(k < 8 ? prm.c_re : prm.c_im) + cta * 16384) + (k & 3) * 4096, 4096);
                    if (k == 4) { mbar_wait(bar_init2); mbar_wait(bar_init3); }
                    if (k >= 4 && lane < 8) mbar_expect_tx(full + 8 * (8 * k + lane), 8 * k + lane < GU0 + 32 && has_gu ? 2 * ABYTES + WBYTES : 2 * ABYTES);
                }
                asm volatile("prefetch.tensormap [%0];" ::"l"(&mCre));
                asm volatile("prefetch.tensormap [%0];" ::"l"(&mCim));
                asm volatile("prefetch.tensormap [%0];" ::"l"(&mWd));
                asm volatile("prefetch.tensormap [%0];" ::"l"(&mXe));
                if (lane < 2) mbar_expect_tx(bar_xb + 8 * lane, 2 * ABYTES);
                mbar_wait(bar_xs);
                mbar_wait(bar_st);
                if (lane == 0) red_release(&prm.s->cnt[32]);
                __syncwarp();
                STAMP(22);
            } else {
                asm volatile("prefetch.tensormap [%0];" ::"l"(&mW));
                mbar_wait(bar_epoch);
                const uint32_t tag = lds32(sb + OFF_EPOCH) + 1;
                st_cell(prm.s->time + cta, 0, 0, 0, 0, lane == 0);
                mbar_wait(empty + 8 * AE);
                uint32_t gown, tm[4][4] = {}, it = 0;
                asm volatile("mov.u32 %0, %%globaltimer_lo;" : "=r"(gown));
                const uint32_t town = clk32();
                st_cell(prm.s->time + cta, tag, town, gown, 0, lane == 0);
                sleep_until(town + AG0);
                do {
#pragma unroll
                    for (int m = 0; m < 4; m++) ld_cell(tm[m], prm.s->time + ((cta & 96) ^ (32 * m)) + lane);
                    if (++it > SPIN_LIMIT) __trap();
                } while (!__all_sync(0xffffffffu, tm[0][0] == tag && tm[1][0] == tag && tm[2][0] == tag && tm[3][0] == tag));
                const int last = __reduce_max_sync(0xffffffffu, max(max((int)(tm[0][2] - gown), (int)(tm[1][2] - gown)), max((int)(tm[2][2] - gown), (int)(tm[3][2] - gown))));
                const uint32_t cand = tm[0][1] + ((min((int)(gown + last - tm[0][2]), 4000) * CLK_NS) >> 8);
                const uint32_t b0 = __shfl_sync(0xffffffffu, cand, cta & 16), b1 = __shfl_sync(0xffffffffu, cand, cta & 30);
                const uint32_t base = (b0 - b1 + 400u < 800u ? b0 : b1) + MARGIN - Sched<AE + NST>::t;
                *reinterpret_cast<volatile uint32_t*>(smem + OFF_EPOCH + 8) = base;
                mbar_wait(bar_init3);
                if (lane < 4) mbar_arrive(bar_base);
                STAMP(23);
                const uint32_t cb = base + W_SHIFT;
                auto early = [&](int i, uint32_t tt) {
                    mbar_wait(empty + 8 * (i - NST));
                    pace_until(tt);
                    gutile(i);
                };
                for_entries<GU0 - 3, GU0 + 4>(cb, early);
                for_entries<GU0 + 4, 32>(cb, early);
            }
            mbar_wait(bar_epoch);
            const uint32_t t2 = lds32(sb + OFF_EPOCH) + 1, tagw = (t2 & 1) | ((t2 & 2) << 15), half = (warp & 1) * ABYTES;
            const uint32_t lo = half + lane * 32 + (lane & 4) * 4 + (lane >> 3) * 4, retry = bar_retry + (warp & 1) * 8;
            const bool leader = lane == 0;
            uint32_t slot = sb + (32 % NST) * SLOT, rpar = 0;
#pragma unroll 1
            for (int i = 32; i < NENT; i++) {
                const uint32_t src = i == XE ? sb + OFF_W : slot;
                if (i != XE) slot = slot == sb + (NST - 1) * SLOT ? sb : slot + SLOT;
                auto current = [&]() {
                    uint32_t v[8];
#pragma unroll
                    for (int u = 0; u < 8; u++) v[u] = lds32(src + lo + u * 1024);
#pragma unroll
                    for (int u = 0; u < 8; u += 2) asm("lop3.b32 %0, %0, %1, %2, 0x7e;" : "+r"(v[u]) : "r"(v[u + 1]), "r"(tagw));
                    return __all_sync(0xffffffffu, ((v[0] | v[2] | v[4] | v[6]) & 0x00010001u) == 0);
                };
                mbar_wait(raw + 8 * i);
                if (!current()) {
#pragma unroll 1
                    for (uint32_t it = 0;; it++) {
                        if (it > SPIN_LIMIT) __trap();
                        STAMP(16);
                        if (leader) mbar_expect_tx(retry, ABYTES);
                        bulk_load(src + half, reinterpret_cast<const char*>(prm.s->h) + (size_t)chunk * 524288 + (i - 32) * 16384 + half, ABYTES, retry);
                        mbar_wait(retry, rpar);
                        rpar ^= 1;
                        if (current()) break;
                    }
                }
                if (leader) mbar_arrive(full + 8 * i);
            }
        }
    } else {
        asm volatile("setmaxnreg.inc.sync.aligned.u32 216;");
        const int wg = warp >> 2, w = warp & 3, g = lane >> 2, c = lane & 3, at = tid & 127;
        float facc[4];
        float2 a[2], m0[2], a32[2], a128[2];
        auto load_const = [&]() {
            const float2* cp = reinterpret_cast<const float2*>(smem + OFF_CONST) + wg * 64 + w * 8 + g;
#pragma unroll
            for (int h = 0; h < 2; h++) { a[h] = cp[32 * h]; m0[h] = cp[128 + 32 * h]; a32[h] = cp[256 + 32 * h]; a128[h] = cp[384 + 32 * h]; }
        };
        if (wg == 0) {
            named_bar(0, 256);
            STAMPIF(tid == 0, 20);
        } else {
            const int pc = (at >> 5) * 256 + dt * 32 + (at & 31);
            const float lr = __bfloat162float(prm.lam_re[pc]), li = __bfloat162float(prm.lam_im[pc]), ld = __bfloat162float(prm.log_dt[pc]);
            const uint32_t dk = __ldg(reinterpret_cast<const uint32_t*>(prm.dskip + dt * 128) + (at & 63));
#pragma unroll
            for (int i = 0; i < 4; i++) sts128(sb + OFF_LIST + i * 2048 + at * 16, 0u, 0u, 0u, 0u);

            {
                reinterpret_cast<uint32_t*>(smem + OFF_DK)[at & 63] = dk;
                const float dtv = rbf(expf(ld));
                const float er = expf(dtv * lr);
                float sn, cs;
                sincospif(dtv * li * 0.318309886183790672f, &sn, &cs);
                const float ar = er * cs, ai = er * sn;
                const float nr = ar - 1.0f, ni = ai;
                const bool big = fabsf(lr) >= fabsf(li);
                const float t = (big ? li : lr) / (big ? lr : li), dn = big ? lr + li * t : lr * t + li;
                const float cr = (big ? nr + ni * t : nr * t + ni) / dn, ci = (big ? ni - nr * t : ni * t - nr) / dn;
                float2* cp = reinterpret_cast<float2*>(smem + OFF_CONST) + at;
                float2 pw = make_float2(ar, prm.swapped ? ai : -ai);
                cp[0] = pw;
                cp[128] = make_float2(prm.swapped ? -2.f * cr : 2.f * cr, -2.f * ci);
#pragma unroll
                for (int i = 1; i <= 7; i++) {
                    pw = cmul(pw, pw);
                    if (i == 5) cp[256] = pw;
                    if (i == 7) cp[384] = pw;
                }
                __syncwarp();
            }
            named_bar(2, 128);
            load_const();
            mbar_wait(bar_epoch);
            const uint32_t tag = *reinterpret_cast<volatile uint32_t*>(smem + OFF_EPOCH) + 1;
            asm volatile("st.relaxed.gpu.global.b64 [%0], %1;" ::"l"(&prm.s->carry[(chunk >> 2) * 4096 + pc * 4 + (chunk & 3)]), "l"((unsigned long long)(tag + 2)) : "memory");
            if (w == 2) st_cell(lane < 4 ? (uint4*)prm.s->rpack + cta * 4 + lane : (uint4*)prm.s->gpack + cta * 4 + (lane & 3), 0, 0, 0, 0, lane < 8);
            {
                const uint32_t nt = ((tag & 1) | ((tag & 2) << 15)) ^ 0x00010001u;
                st_cell(prm.s->hid + cta * 32 - 512 + lane, nt, nt, nt, nt, has_gu && w == 3);
            }
            named_bar(2, 128);
            if (at < 2) mbar_arrive(bar_init3);
            unsigned long long* pub = (w ? prm.s->gpack : prm.s->rpack) + cta * 8 + lane;
            asm volatile("" : "+l"(pub));
            STAMPIF(lane == 0, 52);
            mbar_wait(bar_rdone);

            if (w < 2) {
                const float2* red = reinterpret_cast<const float2*>(smem + OFF_RED) + w * 8 + (lane & 7);
                const float2 r0 = red[0], r1 = red[16], r2 = red[32], r3 = red[48];
                const float v0 = (r0.x + r1.x) + (r2.x + r3.x), v1 = (r0.y + r1.y) + (r2.y + r3.y);
                uint32_t pk2;
                if (w == 0) {
                    pk2 = pack_bf(v0, v1);
                    pk2 ^= (((pk2 >> 15) & 0x00010001u) * 0x7FFFu) ^ 0x80008000u;
                } else pk2 = pack_bf(sigmoidf_(rbf(v0)), sigmoidf_(rbf(v1)));
                if (lane < 8) asm volatile("st.relaxed.gpu.global.b64 [%0], %1;" ::"l"(pub), "l"(((unsigned long long)tag << 32) | pk2) : "memory");
                __syncwarp();
            }
            STAMPIF(at == 0, 24);
            uint32_t it = 0, pr[8], g1;
            mbar_wait(bar_init3);
            sleep_until(clk32() + (w < 2 ? G0 : G0 + 250));
            while (true) {
                bool ok = true;
#pragma unroll
                for (int k = 0; k < 4; k++) {
                    const ulonglong2 u = ld_relaxed2(&prm.s->rpack[k * 256 + 2 * at]);
                    ok = ok && (uint32_t)(u.x >> 32) == tag && (uint32_t)(u.y >> 32) == tag;
                    pr[2 * k] = (uint32_t)u.x; pr[2 * k + 1] = (uint32_t)u.y;
                }
                const unsigned long long u1 = ld_relaxed1(&prm.s->gpack[chunk * 64 + (at & 63)]);
                ok = ok && (uint32_t)(u1 >> 32) == tag;
                g1 = (uint32_t)u1;
                if (__all_sync(0xffffffffu, ok)) break;
                if (++it > SPIN_LIMIT) __trap();
            }
            STAMPIF(lane == 0, 25);
            uint32_t m = __vmaxu2(__vimax3_u16x2(__vimax3_u16x2(pr[0], pr[1], pr[2]), pr[3], pr[4]), __vimax3_u16x2(pr[5], pr[6], pr[7]));
            m = (max(m, m << 16) & 0xFFFF0000u) | (uint32_t)lane;
            const uint32_t m1 = __reduce_max_sync(0xffffffffu, m), m2 = __reduce_max_sync(0xffffffffu, m == m1 ? 0u : m);
            uint32_t* keys = reinterpret_cast<uint32_t*>(smem + OFF_KEYS);
            if (lane == 0) keys[w] = m2;
            sts128(sb + OFF_XS + 4096 + at * 16, pr[0], pr[1], pr[2], pr[3]);
            sts128(sb + OFF_XS + 6144 + at * 16, pr[4], pr[5], pr[6], pr[7]);
            *reinterpret_cast<uint32_t*>(smem + OFF_G + 4 * (at & 63)) = g1;
            named_bar(2, 128);
            const uint4 th4 = *reinterpret_cast<const uint4*>(keys);
            const uint32_t th = (max(min(min(th4.x, th4.y), min(th4.z, th4.w)) >> 16, 1u) - 1u) * 0x00010001u;
            uint32_t mask = 0;
#pragma unroll
            for (int k = 7; k >= 0; k--) mask = mask * 2 + __vminu2(__vmaxu2(pr[k], th) ^ th, 0x00010001u);
            uint32_t pos = 0;
            asm volatile("{ .reg .pred p; setp.ne.u32 p, %2, 0; @p atom.shared.add.u32 %0, [%1], %2; }" : "+r"(pos) : "r"(sb + OFF_KEYS + 16), "r"(__popc(mask)) : "memory");
            while (mask) {
                const int bit = __ffs(mask) - 1, k = bit & 7, hi = bit >> 4;
                mask &= mask - 1;
                const uint32_t sc = *reinterpret_cast<const uint16_t*>(smem + OFF_XS + 4096 + (k >> 2) * 2048 + at * 16 + (k & 3) * 4 + hi * 2);
                *reinterpret_cast<uint32_t*>(smem + OFF_LIST + 4 * pos++) = (sc << 16) | (0x8000u + 2047u - (uint32_t)((k >> 1) * 512 + 4 * at + 2 * (k & 1) + hi));
            }
            __syncwarp();
            if (lane == 0) mbar_arrive(bar_cand);
            STAMPIF(lane == 0, 26);
            mbar_wait(bar_order0);
        }

        float accA[64], accB[64];
        Ring ring = {bar_dummy, wg};
        {
            run_entries<0, 0>(ring, wg * 16, wg ? GU0 : RE0, accA, accB, facc, true);
            if (wg == 0) {
                float racc[4];
                mbar_wait(bar_vec);
                run_entries<0, 1>(ring, RE0, RE0 + 4, accA, accB, racc, false, true);
                mbar_wait(bar_init2);
                const uint32_t red = sb + OFF_RED + 4 * (w * 32 + (c >> 1) * 16 + g);
                run_entries<0, 0>(ring, RE0 + 4, RE0 + 5, accA, accB, facc, false, false, [&]() {
                    pin4(racc);
                    asm volatile("{ .reg .pred p; setp.ne.u32 p, %3, 0; @p st.shared.f32 [%0], %1; @p st.shared.f32 [%0 + 32], %2; }" ::"r"(red),
                                 "f"((w & 1) ? racc[1] : racc[0]), "f"((w & 1) ? racc[3] : racc[2]), "r"((uint32_t)((c & 1) == (w >> 1))) : "memory");
                    __syncwarp();
                    if (lane == 0) mbar_arrive(bar_rdone);
                    STAMPIF(lane == 0, 5);
                });
                run_entries<0, 0>(ring, RE0 + 5, 16, accA, accB, facc);
                if (lane == 0) mbar_arrive(bar_order0);
                mbar_wait(bar_init3);
                load_const();
                named_bar(3, 128);
            } else {
#pragma unroll
                for (int u = 0; u < 2; u++) {
                    mbar_wait(u ? bar_xs : bar_xs0);
                    run_entries<0, 2>(ring, GU0 + 8 * u, u ? 32 : GU0 + 8, accA, accB, facc, false, u == 0);
                }
                if (lane == 0) mbar_arrive(bar_order1);
            }
        }
        const uint32_t tag = *reinterpret_cast<volatile uint32_t*>(smem + OFF_EPOCH) + 1;
        const float2 a64[2] = {cmul(a32[0], a32[0]), cmul(a32[1], a32[1])};
        wgmma_wait<0>();
        pin64(accA); pin64(accB); pin4(facc);
        if (lane == 0) mbar_arrive(ring.prev);
        STAMPIF(at == 0, 28 + wg);
        GSTAMP(tid == 0, 1);
        LP(1);

        const int tl = 32 * (g >> 1) + (g & 1) + 4 * w + 16 * wg, t0 = chunk * 128 + tl;
        float* op = prm.out + (size_t)t0 * D_ + dt * 128 + 4 * c;
        uint2 xv[8][2], dk[8];
        uint32_t gp[2], om[2], routed[2];
        auto row_setup = [&]() {
            const uint4 sa = *reinterpret_cast<const uint4*>(smem + OFF_SEL), sc = *reinterpret_cast<const uint4*>(smem + OFF_SEL + 16);
#pragma unroll
            for (int r = 0; r < 2; r++) {
                const uint32_t id = 0x8000u + 2047u - (uint32_t)(t0 + 2 * r);
                routed[r] = (uint16_t)sa.x == id || (uint16_t)sa.y == id || (uint16_t)sa.z == id || (uint16_t)sa.w == id ||
                            (uint16_t)sc.x == id || (uint16_t)sc.y == id || (uint16_t)sc.z == id || (uint16_t)sc.w == id;
                gp[r] = reinterpret_cast<const uint16_t*>(smem + OFF_G)[tl + 2 * r] * 0x00010001u;
                om[r] = pack_bf(1.0f - bf_hi(gp[r]), 1.0f - bf_hi(gp[r]));
            }
#pragma unroll
            for (int j = 0; j < 8; j++) dk[j] = lds64(sb + OFF_DK + 32 * j + 8 * c);
        };
        auto release = [&](uint32_t bar) {
            asm volatile("fence.proxy.async.shared::cta;" ::: "memory");
            __syncwarp();
            if (lane == 0) mbar_arrive(bar);
        };

        {
            const uint32_t t2 = tag & 3u;
            float2* cslot = &prm.s->carry[(wg * 512 + dt * 32 + w * 8 + g) * 4];
            const int j1 = chunk - 1 - c;
            unsigned long long v[2][4] = {{t2, t2, t2, t2}, {t2, t2, t2, t2}};
            auto poll = [&](int h) {
#pragma unroll
                for (int m = 0; m < 4; m++)
                    asm volatile("{ .reg .pred p; setp.ge.s32 p, %2, %3; @p ld.relaxed.gpu.global.b64 %0, [%1]; }"
                                 : "+l"(v[h][m]) : "l"(cslot + (j1 >> 2) * 4096 + c - m * 4096 + h * 1024), "r"(j1), "r"(4 * m) : "memory");
            };
            float2 e[2], w0[2];
            auto chain = [&](int h, int s0, int s1) {
                float (&acc)[64] = h ? accB : accA;
                if (s0 == 1) e[h] = make_float2(acc[0], acc[2]);
#pragma unroll
                for (int s = s0; s < s1; s++) {
                    const int i0 = 4 * (s >> 1) + (s & 1);
                    e[h] = cfma(make_float2(a[h].x, -a[h].y), e[h], make_float2(acc[i0], acc[i0 + 2]));
                }
                asm volatile("" : "+f"(e[h].x), "+f"(e[h].y), "+f"(accB[0]), "+f"(accB[2]));
                gap();
            };
            auto publish = [&](int h) {
                float2 f = make_float2(fmaf(m0[h].x, e[h].x, m0[h].y * e[h].y), fmaf(-m0[h].x, e[h].y, m0[h].y * e[h].x));
                float2 y = make_float2(__shfl_up_sync(0xffffffffu, f.x, 1, 4), __shfl_up_sync(0xffffffffu, f.y, 1, 4));
                if (c >= 1) f = cfma(a32[h], y, f);
                y = make_float2(__shfl_up_sync(0xffffffffu, f.x, 2, 4), __shfl_up_sync(0xffffffffu, f.y, 2, 4));
                if (c >= 2) f = cfma(a64[h], y, f);
                asm volatile("{ .reg .pred p; .reg .b64 t; setp.eq.u32 p, %3, 3; mov.b64 t, {%1, %2}; @p st.relaxed.gpu.global.b64 [%0], t; }"
                             ::"l"(cslot + (chunk >> 2) * 4096 + (chunk & 3) + h * 1024), "r"((__float_as_uint(f.x) & ~3u) | t2), "r"(__float_as_uint(f.y)), "r"(c) : "memory");
                w0[h] = make_float2(__shfl_up_sync(0xffffffffu, f.x, 1, 4), __shfl_up_sync(0xffffffffu, f.y, 1, 4));
                if (c == 0) w0[h] = make_float2(0.f, 0.f);
            };
            auto scale = [&](int h, int n0, int n1) {
                float (&acc)[64] = h ? accB : accA;
#pragma unroll
                for (int n = n0; n < n1; n++) {
                    asm volatile("{ .reg .f32 a, b, c, d, n; neg.f32 n, %4; mul.f32 a, %1, %5; mul.f32 b, %0, %5; mul.f32 c, %3, %5; mul.f32 d, %2, %5;\n"
                                 "fma.rn.f32 %0, %0, %4, a; fma.rn.f32 %1, %1, n, b; fma.rn.f32 %2, %2, %4, c; fma.rn.f32 %3, %3, n, d; }"
                                 : "+f"(acc[4 * n]), "+f"(acc[4 * n + 2]), "+f"(acc[4 * n + 1]), "+f"(acc[4 * n + 3]) : "f"(m0[h].x), "f"(m0[h].y));
                    gap();
                }
            };
            auto carry = [&](int h) {
                const float2 one = make_float2(1.f, 0.f), a256 = cmul(a128[h], a128[h]);
                float2 a512 = cmul(a256, a256), pw128 = cmul((j1 & 1) ? a128[h] : one, (j1 & 2) ? a256 : one);
                float2 pw32 = cmul((c & 1) ? a32[h] : one, (c & 2) ? a64[h] : one);
                asm volatile("" : "+f"(a512.x), "+f"(a512.y), "+f"(pw128.x), "+f"(pw128.y), "+f"(pw32.x), "+f"(pw32.y));
                STAMPIF(lane == 0 && !h, 34 + 2 * wg);
                uint32_t it = 0;
                while (!__all_sync(0xffffffffu, ((((uint32_t)v[h][0] ^ t2) | ((uint32_t)v[h][1] ^ t2) | ((uint32_t)v[h][2] ^ t2) | ((uint32_t)v[h][3] ^ t2)) & 3u) == 0)) {
                    poll(h);
                    if (++it > SPIN_LIMIT) __trap();
                }
                STAMPIF(lane == 0 && !h, 35 + 2 * wg);
                float2 hin = make_float2(__uint_as_float((uint32_t)v[h][3]), __uint_as_float((uint32_t)(v[h][3] >> 32)));
#pragma unroll
                for (int m = 2; m >= 0; m--) hin = cfma(a512, hin, make_float2(__uint_as_float((uint32_t)v[h][m]), __uint_as_float((uint32_t)(v[h][m] >> 32))));
                hin = cmul(pw128, hin);
                hin.x += __shfl_xor_sync(0xffffffffu, hin.x, 1); hin.y += __shfl_xor_sync(0xffffffffu, hin.y, 1);
                hin.x += __shfl_xor_sync(0xffffffffu, hin.x, 2); hin.y += __shfl_xor_sync(0xffffffffu, hin.y, 2);
                w0[h] = cfma(pw32, hin, w0[h]);
            };
            chain(0, 1, 32);
            publish(0);
            chain(1, 1, 8);
            STAMPIF(lane == 0, 30 + 2 * wg);
            chain(1, 8, 32);
            publish(1);
            gap();
            scale(0, 0, POLL_S);
            poll(0);
            scale(0, POLL_S, 16);
            carry(0);
            if (wg) mbar_wait(bar_out + 24);
            STAMPIF(lane == 0, 38 + 2 * wg);
            const uint32_t stg = sb + OFF_STG + prm.swapped * 8192 + w * 1024 + (lane & 7) * 128 + (((lane >> 3) ^ (lane & 7)) << 4);
            const uint32_t second = prm.swapped ? -8192 : 8192;
            uint32_t hold = prm.swapped >> 1, last[8];
            const uint32_t keep = c == (g >> 1) ? 0xFFFEFFFEu : 0xFFFFFFFFu, tagw = ((t2 & 1) | ((t2 & 2) << 15)) & ~keep;
#pragma unroll
            for (int h = 0; h < 2; h++) {
                float (&acc)[64] = h ? accB : accA;
                uint32_t ra[16], ia[16];
                if (h) {
                    scale(1, 0, 4);
#pragma unroll
                    for (int u = 0; u < 4; u++) asm volatile("lop3.b32 %0, %0, %1, %2, 0x80;" : "+r"(hold) : "r"(last[u]), "r"(last[4 + u]));
                    release(bar_st + 32 * wg + 8 + hold);
                    poll(1);
                    scale(1, 4, 16);
                    mbar_wait(bar_xs);
                    row_setup();
                    carry(1);
                }
                auto stage = [&](uint32_t (&r)[16], uint32_t base, int j) {
                    stsm4((base ^ ((j & 1) * 64)) + (j >> 1) * 4096, r[4 * j], r[4 * j + 1], r[4 * j + 2], r[4 * j + 3]);
                };
#pragma unroll
                for (int n = 0; n < 16; n++) {
                    const float2 y = cfma(a[h], w0[h], make_float2(acc[4 * n], acc[4 * n + 2]));
                    w0[h] = cfma(a[h], y, make_float2(acc[4 * n + 1], acc[4 * n + 3]));
                    ra[n] = pack_bf(y.x, w0[h].x);
                    ia[n] = pack_bf(y.y, w0[h].y);
                    if (!(n & 1)) { ra[n] = (ra[n] & keep) | tagw; ia[n] = (ia[n] & keep) | tagw; }
                    if (!h && (n & 3) == 3) {
                        if (n > 3) {
                            gap();
#pragma unroll
                            for (int u = n - 7; u < n - 3; u++) asm volatile("lop3.b32 %0, %0, %1, %2, 0x80;" : "+r"(hold) : "r"(ra[u]), "r"(ia[u]));
                        }
                        if (n == 15) {
#pragma unroll
                            for (int u = 0; u < 4; u++) { last[u] = ra[12 + u]; last[4 + u] = ia[12 + u]; }
                        }
                        if (n == 11) { asm volatile("" : "+r"(ra[n]), "+r"(ia[n])); gap(); release(bar_st + 32 * wg); }
                        stage(ra, stg, n >> 2); stage(ia, stg + second, n >> 2);
                        gap();
                    }
                }
                if (h) {
                    STAMPIF(lane == 0, 39 + 2 * wg);
                    mbar_wait(bar_out + 32 * wg);
                    if (prm.swapped) {
#pragma unroll
                        for (int n = 0; n < 16; n++) { const uint32_t t = ra[n]; ra[n] = ia[n]; ia[n] = t; }
                    }
                    const uint32_t st0 = stg - prm.swapped * 8192;
#pragma unroll
                    for (int j = 0; j < 4; j++) stage(ra, st0, j);
                    release(bar_st + 32 * wg + 16);
                    mbar_wait(bar_out + 32 * wg + 8);
#pragma unroll
                    for (int j = 0; j < 4; j++) stage(ia, st0 + 8192, j);
                    release(bar_st + 32 * wg + 24);
                }
                STAMPIF(lane == 0, 42 + 2 * wg + h);
            }
        }

        const uint32_t xr = 2 * (g & 3) + (g >> 2), xa = sb + (wg ? OFF_STG : OFF_W) + (16 * w + xr) * 128 + (((c >> 1) ^ xr) << 4) + (c & 1) * 8;
        auto handover = [&](uint32_t bar) {
            const uint4 z = ldsm4(sb + OFF_KEYS + 16);
            if (lane == 1) mbar_arrive(bar + z.x);
        };
        auto load_x = [&](int j0, int j1) {
#pragma unroll
            for (int j = j0; j < j1; j++)
#pragma unroll
                for (int r = 0; r < 2; r++) xv[j][r] = lds64((xa ^ (32 * (j & 3))) + (j >> 2) * ABYTES + r * 1024);
        };
        auto skip_term = [&](int j0, int j1) {
#pragma unroll
            for (int j = j0; j < j1; j++)
#pragma unroll
                for (int r = 0; r < 2; r++) {
                    xv[j][r].x = mul_bf2(xv[j][r].x, fma_bf2(gp[r], dk[j].x, om[r]));
                    xv[j][r].y = mul_bf2(xv[j][r].y, fma_bf2(gp[r], dk[j].y, om[r]));
                    asm volatile("" : "+r"(xv[j][r].x), "+r"(xv[j][r].y));
                }
        };
        auto finish = [&](float (&acc)[64], int j, bool gaps) {
#pragma unroll
            for (int r = 0; r < 2; r++) {
                const int o = 8 * j + 2 * r;
                const float gv = bf_hi(gp[r]);
                acc[o] = fmaf(gv, acc[o], bf_lo(xv[j][r].x)); acc[o + 1] = fmaf(gv, acc[o + 1], bf_hi(xv[j][r].x));
                acc[o + 4] = fmaf(gv, acc[o + 4], bf_lo(xv[j][r].y)); acc[o + 5] = fmaf(gv, acc[o + 5], bf_hi(xv[j][r].y));
                stg4_unless(op + r * 2 * D_ + 16 * j, acc[o], acc[o + 1], acc[o + 4], acc[o + 5], routed[r]);
                if (gaps) gap();
            }
        };
        auto finish_routed = [&](float (&acc)[64]) {
#pragma unroll
            for (int r = 0; r < 2; r++)
                if (routed[r]) {
#pragma unroll
                    for (int j = 0; j < 8; j++) red4(op + r * 2 * D_ + 16 * j, acc[8 * j + 2 * r], acc[8 * j + 2 * r + 1], acc[8 * j + 2 * r + 4], acc[8 * j + 2 * r + 5]);
                }
            __syncwarp();
        };
        const uint32_t xbuf = sb + w * 2048 + lane * 16;

        if (wg == 1) {
            float outB[64];
            {
                sts128(sb + OFF_XS + at * 16, __float_as_uint(facc[0]), __float_as_uint(facc[1]), __float_as_uint(facc[2]), __float_as_uint(facc[3]));
                named_bar(2, 128);
                const uint32_t pg = sb + OFF_XS + prm.up_first * 1024 + (at & 63) * 16 + (w >> 1) * 8, pu = pg + 1024 - prm.up_first * 2048;
                const uint2 g1 = lds64(pg), u1 = lds64(pu);
                uint4* hp = prm.s->hid + cta * 32 - 512 + 16 * (w & 1) + 8 * (w >> 1) + g;
                asm volatile("" : "+l"(hp));
                mbar_wait(bar_fp);
                const uint2 g2 = lds64(pg + 2048), u2 = lds64(pu + 2048);
                const float ga = rbf(__uint_as_float(g1.x) + __uint_as_float(g2.x)), gb = rbf(__uint_as_float(g1.y) + __uint_as_float(g2.y));
                uint32_t hw = mul_bf2(pack_bf(__fdividef(ga, 1.0f + __expf(-ga)), __fdividef(gb, 1.0f + __expf(-gb))),
                                      pack_bf(__uint_as_float(u1.x) + __uint_as_float(u2.x), __uint_as_float(u1.y) + __uint_as_float(u2.y)));
                if (c == 2 * (w & 1) + (w >> 1)) hw = (hw & 0xFFFEFFFEu) | (tag & 1) | ((tag & 2) << 15);
                st_cell(hp, hw, __shfl_down_sync(0xffffffffu, hw, 1), __shfl_down_sync(0xffffffffu, hw, 2), __shfl_down_sync(0xffffffffu, hw, 3), has_gu && c == 0);
            }
            STAMPIF(lane == 0, 47);
            mbar_wait(bar_xb);
            load_x(0, 8);
            release(bar_xbfree);
            skip_term(0, 8);
            STAMPIF(lane == 0, 46);
            mbar_wait(bar_order2);
            static_for<NENT - FIN>([&](auto u) {
                run_small<1, FIN + u>(outB);
                if (u == FE) { wgmma_wait<2>(); if (lane == 0) mbar_arrive(bar_fold); }
            });
            wgmma_wait<0>();
            pin64(outB);
            KSTAMP(2 * NENT - FIN);
            STAMPIF(at == 0, 50);
            LT(0);
#pragma unroll
            for (int q = 0; q < 2; q++) {
                uint4 pb[16];
                mbar_wait(bar_accb + 8 * q);
                if (q) LT(1);
#pragma unroll
                for (int v = q * HP; v < (q ? 16 : HP); v++) pb[v] = ldsm4(xbuf + sum_off(v));
#pragma unroll
                for (int v = q * HP; v < (q ? 16 : HP); v++) {
                    outB[4 * v] += __uint_as_float(pb[v].x); outB[4 * v + 1] += __uint_as_float(pb[v].y);
                    outB[4 * v + 2] += __uint_as_float(pb[v].z); outB[4 * v + 3] += __uint_as_float(pb[v].w);
                    if (v & 1) finish(outB, v >> 1, false);
                    if (v == DV) { gap(); if (lane == 0) mbar_expect_tx(bar_dn, w ? 0 : 7 * ABYTES); }
                }
            }
            finish_routed(outB);
            STAMPIF(lane == 0, 51);
            LT(2);
        } else {
            float outA[64], outB[64], gacc[4];
            ring.slot = 32 % NST;
            ring.prev = bar_dummy;
            mbar_wait(bar_order1);
            run_entries<1, 2>(ring, 32, GU0 + 32, outA, outB, gacc, true, true);
            run_entries<1, 0>(ring, GU0 + 32, GU0 + 33, outA, outB, gacc, false, false, [&]() {
                LP(2);
                pin4(gacc);
                sts128(sb + OFF_XS + 2048 + at * 16, __float_as_uint(gacc[0]), __float_as_uint(gacc[1]), __float_as_uint(gacc[2]), __float_as_uint(gacc[3]));
                __syncwarp();
                if (lane == 0) mbar_arrive(bar_fp);
            });
            mbar_wait(bar_xa);
            load_x(0, 2);
            run_entries<1, 0>(ring, GU0 + 33, GU0 + 34, outA, outB, gacc, false, false, [&]() { load_x(2, 3); });
            load_x(3, 5);
            run_entries<1, 0>(ring, GU0 + 34, GU0 + 35, outA, outB, gacc, false, false, [&]() { load_x(5, 6); });
            load_x(6, 8);
            run_entries<1, 0>(ring, GU0 + 35, GU0 + 36, outA, outB, gacc, false, false, [&]() { handover(bar_xafree); });
            skip_term(0, 3);
            run_entries<1, 0>(ring, GU0 + 36, GU0 + 37, outA, outB, gacc, false, false, [&]() { skip_term(3, 5); });
            skip_term(5, 8);
            run_entries<1, 0>(ring, GU0 + 37, FIN, outA, outB, gacc);
            auto dump = [&](int v) {
                stsm4(xbuf + sum_off(v), __float_as_uint(outB[4 * v]), __float_as_uint(outB[4 * v + 1]), __float_as_uint(outB[4 * v + 2]),
                      __float_as_uint(outB[4 * v + 3]));
            };
            static_for<NENT - FIN>([&](auto u) {
                mbar_wait(full + 8 * (FIN + u));
                run_small<0, FIN + u>(outA);
                if (u == 5 && lane == 0) mbar_arrive(bar_order2);
                wgmma_wait<1>();
                if (lane == 0) mbar_arrive(empty + 8 * (FIN + u - 1));
                if (u == 0) { pin64(outB); LP(3); }
                if (u == 2) mbar_wait(empty + 8 * FIN);
                if (u >= 2) dump(u - 2);
            });
            const uint2 sk = lds64(sb + OFF_SEL + 8 * c), fk = lds64(sb + OFF_FAC + 8 * c);
            float* y0 = prm.out + (~sk.x & 2047u) * D_ + (cta & 15) * 64 + w * 16 + g;
            float* y1 = prm.out + (~sk.y & 2047u) * D_ + (cta & 15) * 64 + w * 16 + g;
            asm volatile("" : "+l"(y0), "+l"(y1));
            handover(bar_accb);
            wgmma_wait<0>();
            pin64(outA);
            STAMPIF(at == 0, 53);
            GSTAMP(at == 0, 2);
#pragma unroll
            for (int j = 0; j < 8; j++) {
                finish(outA, j, true);
            }
            STAMPIF(lane == 0, 54);
            LT(0);
            mbar_wait(bar_fold);
#pragma unroll
            for (int v = 4; v < 16; v++) dump(v);
            handover(bar_accb + 8);
            STAMPIF(lane == 0, 55);
            finish_routed(outA);
            float yacc[4];
            const uint64_t dw = make_desc(sb), dh = (uint64_t)(((sb + OFF_XS) & 0x3FFFF) >> 4) | ((uint64_t)8 << 16) | ((uint64_t)8 << 32);
            mbar_wait(bar_zero);
            mbar_wait(bar_dn);
            STAMPIF(at == 0, 2);
            LT(1);
            wgmma_fence();
#pragma unroll
            for (int n = 0; n < 28; n++) wgmma_n8<1, 1>(yacc, dw + (dn_off(n >> 2) >> 4) + (n & 3) * 128, dh + n * 16, n > 0);
            wgmma_commit();
            wgmma_wait<0>();
            pin4(yacc);
            LT(2);
            asm volatile("red.global.add.f32 [%0], %2; red.global.add.f32 [%1], %3; red.global.add.f32 [%0 + 32], %4; red.global.add.f32 [%1 + 32], %5;"
                         ::"l"(y0), "l"(y1), "f"(yacc[0] * __uint_as_float(fk.x)), "f"(yacc[1] * __uint_as_float(fk.y)), "f"(yacc[2] * __uint_as_float(fk.x)),
                         "f"(yacc[3] * __uint_as_float(fk.y)) : "memory");
            STAMPIF(lane == 0, 3);
            LT(3);
        }
    }
}

typedef CUresult (*EncodeFn)(CUtensorMap*, CUtensorMapDataType, cuuint32_t, void*, const cuuint64_t*, const cuuint64_t*, const cuuint32_t*,
                             const cuuint32_t*, CUtensorMapInterleave, CUtensorMapSwizzle, CUtensorMapL2promotion, CUtensorMapFloatOOBfill);

bool encode(EncodeFn fn, CUtensorMap* m, const void* ptr, int rank, const cuuint64_t* dims, const cuuint64_t* strides, const cuuint32_t* box,
            CUtensorMapSwizzle sw = CU_TENSOR_MAP_SWIZZLE_128B, CUtensorMapL2promotion promo = CU_TENSOR_MAP_L2_PROMOTION_NONE) {
    const cuuint32_t es[5] = {1, 1, 1, 1, 1};
    return fn(m, CU_TENSOR_MAP_DATA_TYPE_BFLOAT16, rank, const_cast<void*>(ptr), dims, strides, box, es, CU_TENSOR_MAP_INTERLEAVE_NONE,
              sw, promo, CU_TENSOR_MAP_FLOAT_OOB_FILL_NONE) == CUDA_SUCCESS;
}

}

extern "C" void kernel_launch(void* const* d_in, const int* in_sizes, int n_in, void* d_out, int out_size) {
    (void)in_sizes; (void)n_in; (void)out_size;
    Params prm;
    prm.x = (const __nv_bfloat16*)d_in[0];
    prm.lam_re = (const __nv_bfloat16*)d_in[1];
    prm.lam_im = (const __nv_bfloat16*)d_in[2];
    prm.b_re = (const __nv_bfloat16*)d_in[3];
    prm.b_im = (const __nv_bfloat16*)d_in[4];
    prm.c_re = (const __nv_bfloat16*)d_in[5];
    prm.c_im = (const __nv_bfloat16*)d_in[6];
    prm.log_dt = (const __nv_bfloat16*)d_in[7];
    prm.dskip = (const __nv_bfloat16*)d_in[8];
    prm.w_r = (const __nv_bfloat16*)d_in[10];
    prm.gate_w = (const __nv_bfloat16*)d_in[14];
    prm.out = (float*)d_out;
    cudaGetSymbolAddress((void**)&prm.s, g_scratch);
    int dev = 0, sms = 0;
    cudaGetDevice(&dev);
    cudaDeviceGetAttribute(&sms, cudaDevAttrMultiProcessorCount, dev);
    auto kernel = sms == NGRID ? fused_kernel<true> : fused_kernel<false>;
    prm.swapped = prm.b_im < prm.b_re;

    void* fnp = nullptr;
    cudaDriverEntryPointQueryResult qr;
    cudaGetDriverEntryPoint("cuTensorMapEncodeTiled", &fnp, cudaEnableDefault, &qr);
    EncodeFn fn = (EncodeFn)fnp;
    cudaFuncSetAttribute(kernel, cudaFuncAttributeMaxDynamicSharedMemorySize, SMEM_BYTES);

    CUtensorMap mX, mB, mCre, mCim, mW, mWd, mXr, mXe;
    const cuuint64_t row = 2048;
    {
        const cuuint64_t dims[4] = {1024, 2, 4, 976}, st[3] = {row, 32 * row, 2 * row};
        const cuuint32_t box[4] = {64, 2, 4, 16};
        encode(fn, &mX, prm.x, 4, dims, st, box, CU_TENSOR_MAP_SWIZZLE_128B, PROMO);
    }
    {
        const char *lo = (const char*)(prm.swapped ? prm.b_im : prm.b_re), *hi = (const char*)(prm.swapped ? prm.b_re : prm.b_im);
        const cuuint64_t dims[5] = {1024, 8, 2, 96, 2}, st[4] = {row, (cuuint64_t)(hi - lo), 8 * row, 256 * row};
        const cuuint32_t box[5] = {64, 8, 2, 4, 2};
        encode(fn, &mB, lo, 5, dims, st, box, CU_TENSOR_MAP_SWIZZLE_128B, PROMO);
    }
    {
        const cuuint64_t dims[5] = {1024, 2, 4, 2, 64}, st[4] = {row, 4 * row, 2 * row, 16 * row};
        const cuuint32_t box[5] = {64, 2, 4, 2, 8};
        encode(fn, &mCre, prm.c_re, 5, dims, st, box);
        encode(fn, &mCim, prm.c_im, 5, dims, st, box);
    }
    {
        const char *pg = (const char*)d_in[11], *pu = (const char*)d_in[12];
        prm.up_first = pu < pg;
        const cuuint64_t dims[3] = {F_, D_, 2}, st[2] = {F_ * 2, (cuuint64_t)(pu < pg ? pg - pu : pu - pg)}, dimsd[2] = {D_, F_}, std_[1] = {row};
        const cuuint32_t box[3] = {32, 32, 2}, boxd[2] = {64, 64};
        encode(fn, &mW, pu < pg ? pu : pg, 3, dims, st, box, CU_TENSOR_MAP_SWIZZLE_64B, CU_TENSOR_MAP_L2_PROMOTION_NONE);
        encode(fn, &mWd, d_in[13], 2, dimsd, std_, boxd, CU_TENSOR_MAP_SWIZZLE_128B, CU_TENSOR_MAP_L2_PROMOTION_NONE);
    }
    {
        const cuuint64_t dims[3] = {D_ - 192, S_, 4}, st[2] = {row, 128};
        const cuuint32_t box[3] = {64, 16, 4};
        encode(fn, &mXr, prm.x, 3, dims, st, box, CU_TENSOR_MAP_SWIZZLE_128B, CU_TENSOR_MAP_L2_PROMOTION_NONE);
    }
    {
        const cuuint64_t dims[5] = {D_, 2, 2, 2, 976}, st[4] = {64 * row, row, 32 * row, 2 * row};
        const cuuint32_t box[5] = {64, 2, 2, 2, 8};
        encode(fn, &mXe, prm.x, 5, dims, st, box);
    }
    kernel<<<NGRID, 384, SMEM_BYTES, cudaStreamPerThread>>>(prm, mX, mB, mCre, mCim, mW, mWd, mXr, mXe);
}
```

```cpp
#include <cuda_runtime.h>
#include <cuda_bf16.h>
#include <cuda.h>
#include <stdint.h>

namespace {

constexpr int S_ = 2048, D_ = 1024, F_ = 3584;
constexpr int NCTA = 128, NGRID = 132;
#define XE_ 58
#define GU0_ 18
constexpr int NENT = 64, FIN = 58, XE = XE_;
constexpr int NST = 5;
constexpr int RE0 = 4;
constexpr int GU0 = GU0_;
constexpr uint32_t SLOT = 32768, ABYTES = 8192, WBYTES = 4096;
constexpr uint32_t OFF_XS = NST * SLOT;
constexpr uint32_t OFF_LIST = OFF_XS + 8192;
constexpr uint32_t OFF_W = OFF_XS + 16384;
constexpr uint32_t OFF_STG = OFF_W + 32768;
__host__ __device__ constexpr uint32_t slot_off(int i) { return i < XE ? (i % NST) * SLOT : i == XE ? OFF_W : ((i - 1) % NST) * SLOT; }
__host__ __device__ constexpr uint32_t dn_off(int u) { return u == 0 ? OFF_XS + ABYTES : u < 3 ? OFF_STG + (u - 1) * ABYTES : slot_off(FIN - 2 + u); }
__host__ __device__ constexpr uint32_t sum_off(int v) { return slot_off(FIN) + (v >> 2) * ABYTES + (v & 3) * 512; }
constexpr uint32_t OFF_CONST = OFF_STG;
constexpr uint32_t OFF_RED = OFF_STG + 4096;
constexpr uint32_t OFF_FULL = OFF_STG + 16384;
constexpr uint32_t OFF_EMPTY = OFF_FULL + 120 * 8;
constexpr uint32_t OFF_G = OFF_EMPTY + 88 * 8;
constexpr uint32_t OFF_DK = OFF_G + 256;
constexpr uint32_t OFF_KEYS = OFF_DK + 256;
constexpr uint32_t OFF_SEL = OFF_KEYS + 32;
constexpr uint32_t OFF_FAC = OFF_SEL + 32;
constexpr uint32_t OFF_EPOCH = OFF_FAC + 32;
constexpr uint32_t OFF_PROF = OFF_EPOCH + 16;
constexpr uint32_t SMEM_BYTES = OFF_PROF + 768;
static_assert(SMEM_BYTES <= 232448, "smem");

constexpr uint32_t sb = 1024;
constexpr uint32_t SPIN_LIMIT = 1u << 18;

struct Scratch {
    unsigned int cnt[2 * 32];
    unsigned long long rpack[S_ / 2];
    unsigned long long gpack[S_ / 2];
    uint4 time[NCTA];
    float2 carry[16 * 1024];
    uint4 hid[F_];
    uint4 h[8 * 4 * 256 * 64];
};
__device__ __align__(128) Scratch g_scratch;
#define LT(i) do {} while (0)
#define STAMPW(cond, w) do {} while (0)
#define LATE(i, tt) do {} while (0)
#define LANDED(i) do {} while (0)
#define GSTAMP(cond, w) do {} while (0)
#define LP(i) do {} while (0)
#define STAMPIF(cond, i) STAMPW(cond, 72 + (i))
#define STAMP(i) STAMPW(1, 72 + (i))
#define KSTAMP(i) STAMPW((threadIdx.x & 127) == 0, i)

struct Params {
    const __nv_bfloat16 *x, *b_re, *b_im;
    Scratch* s;
    int up_first;
    int swapped;
    const __nv_bfloat16 *lam_re, *lam_im, *c_re, *c_im, *log_dt, *dskip, *w_r, *gate_w;
    float* out;
};

__device__ __forceinline__ uint32_t smem_u32(const void* p) { return (uint32_t)__cvta_generic_to_shared(p); }
__device__ __forceinline__ void mbar_init(uint32_t bar, uint32_t cnt) { asm volatile("mbarrier.init.shared::cta.b64 [%0], %1;" ::"r"(bar), "r"(cnt) : "memory"); }
__device__ __forceinline__ void mbar_expect_tx(uint32_t bar, uint32_t bytes) { asm volatile("mbarrier.arrive.expect_tx.shared::cta.b64 _, [%0], %1;" ::"r"(bar), "r"(bytes) : "memory"); }
__device__ __forceinline__ void mbar_arrive(uint32_t bar) { asm volatile("mbarrier.arrive.shared::cta.b64 _, [%0];" ::"r"(bar) : "memory"); }
__device__ __forceinline__ void mbar_wait(uint32_t bar, uint32_t parity = 0) {
    asm volatile("{ .reg .pred p; .reg .u32 n;\n"
                 "mov.u32 n, 0;\n"
                 "AGAIN: mbarrier.try_wait.parity.shared::cta.b64 p, [%0], %1;\n"
                 "@p bra.uni DONE;\n"
                 "add.u32 n, n, 1;\n"
                 "setp.lt.u32 p, n, %2;\n"
                 "@p bra.uni AGAIN;\n"
                 "trap;\n"
                 "DONE: }" ::"r"(bar), "r"(parity), "n"(SPIN_LIMIT) : "memory");
}
__device__ __forceinline__ bool elect_one() {
    uint32_t pred;
    asm volatile("{ .reg .pred P; elect.sync _|P, 0xffffffff; selp.b32 %0, 1, 0, P; }" : "=r"(pred));
    return pred;
}
__device__ __forceinline__ void named_bar(int id, int n) { asm volatile("bar.sync %0, %1;" ::"r"(id), "r"(n) : "memory"); }

#define ONE "{ .reg .pred e; elect.sync _|e, 0xffffffff;\n@e "
template <int N> __device__ __forceinline__ void mbar_init_n(uint32_t bar, uint32_t cnt, uint32_t extra = 0) {
    if (elect_one()) {
#pragma unroll
        for (int i = 0; i < N; i++) mbar_init(bar + 8 * i, i == N - 1 ? cnt + extra : cnt);
        asm volatile("fence.mbarrier_init.release.cluster;" ::: "memory");
    }
    __syncwarp();
}
__device__ __forceinline__ void bulk_load(uint32_t dst, const void* src, uint32_t bytes, uint32_t bar) {
    asm volatile(ONE "cp.async.bulk.shared::cluster.global.mbarrier::complete_tx::bytes [%0], [%1], %2, [%3]; }" ::"r"(dst), "l"(src), "r"(bytes), "r"(bar) : "memory");
}
__device__ __forceinline__ void sts128(uint32_t a, uint32_t x, uint32_t y, uint32_t z, uint32_t w) {
    asm volatile("st.shared.v4.u32 [%0], {%1,%2,%3,%4};" ::"r"(a), "r"(x), "r"(y), "r"(z), "r"(w) : "memory");
}
__device__ __forceinline__ uint2 lds64(uint32_t a) {
    uint2 v;
    asm volatile("ld.shared.v2.u32 {%0,%1}, [%2];" : "=r"(v.x), "=r"(v.y) : "r"(a) : "memory");
    return v;
}
__device__ __forceinline__ uint32_t clk32() { uint32_t c; asm volatile("mov.u32 %0, %%clock;" : "=r"(c)); return c; }
__device__ __forceinline__ void gap() { asm volatile("pmevent 1;" ::: "memory"); }
__device__ __forceinline__ void pace_until(uint32_t t) { while ((int)(clk32() - t) < 0) {} }
#define SLEEP_MARGIN 200
__device__ __forceinline__ void sleep_until(uint32_t t) {
    while ((int)(clk32() + SLEEP_MARGIN - t) < 0) __nanosleep(40);
    pace_until(t);
}
__device__ __forceinline__ void tma2(uint32_t dst, const CUtensorMap* m, int c0, int c1, uint32_t bar, uint64_t pol) {
    asm volatile(ONE "cp.async.bulk.tensor.2d.shared::cluster.global.mbarrier::complete_tx::bytes.L2::cache_hint [%0], [%1, {%3, %4}], [%2], %5; }"
                 ::"r"(dst), "l"(m), "r"(bar), "r"(c0), "r"(c1), "l"(pol) : "memory");
}
__device__ __forceinline__ void tma3s(uint32_t dst, const CUtensorMap* m, int c0, int c1, uint32_t bar, uint64_t pol) {
    asm volatile(ONE "cp.async.bulk.tensor.3d.shared::cluster.global.mbarrier::complete_tx::bytes.L2::cache_hint [%0], [%1, {%3, %4, %5}], [%2], %6; }"
                 ::"r"(dst), "l"(m), "r"(bar), "r"(c0), "r"(c1), "r"(0), "l"(pol) : "memory");
}
__device__ __forceinline__ void tma3(uint32_t dst, const CUtensorMap* m, int c0, int c1, uint32_t bar) {
    asm volatile(ONE "cp.async.bulk.tensor.3d.shared::cluster.global.mbarrier::complete_tx::bytes [%0], [%1, {%3, %4, %5}], [%2]; }"
                 ::"r"(dst), "l"(m), "r"(bar), "r"(c0), "r"(c1), "r"(0) : "memory");
}
__device__ __forceinline__ void tma4(uint32_t dst, const CUtensorMap* m, int c0, int c3, uint32_t bar) {
    asm volatile(ONE "cp.async.bulk.tensor.4d.shared::cluster.global.mbarrier::complete_tx::bytes [%0], [%1, {%3, %5, %5, %4}], [%2]; }"
                 ::"r"(dst), "l"(m), "r"(bar), "r"(c0), "r"(c3), "r"(0) : "memory");
}
__device__ __forceinline__ void tma5(uint32_t dst, const CUtensorMap* m, int c0, int c4, uint32_t bar) {
    asm volatile(ONE "cp.async.bulk.tensor.5d.shared::cluster.global.mbarrier::complete_tx::bytes [%0], [%1, {%3, %5, %5, %5, %4}], [%2]; }"
                 ::"r"(dst), "l"(m), "r"(bar), "r"(c0), "r"(c4), "r"(0) : "memory");
}
__device__ __forceinline__ void tma5b(uint32_t dst, const CUtensorMap* m, int c0, int c3, uint32_t bar) {
    asm volatile(ONE "cp.async.bulk.tensor.5d.shared::cluster.global.mbarrier::complete_tx::bytes [%0], [%1, {%3, %5, %5, %4, %5}], [%2]; }"
                 ::"r"(dst), "l"(m), "r"(bar), "r"(c0), "r"(c3), "r"(0) : "memory");
}
__device__ __forceinline__ void prefetch_l2(const void* p) {
    asm volatile("cp.async.ca.shared.global.L2::256B [%0], [%1], 4;" ::"r"(sb + OFF_EPOCH + 12), "l"(p) : "memory");
}

__device__ __forceinline__ uint32_t lds32(uint32_t a) {
    uint32_t v;
    asm volatile("ld.volatile.shared.u32 %0, [%1];" : "=r"(v) : "r"(a) : "memory");
    return v;
}
__device__ __forceinline__ uint32_t uni(uint32_t v) { return __shfl_sync(0xffffffffu, v, 0); }   __device__ __forceinline__ uint32_t ld_acquire(const unsigned int* p) {
    uint32_t v;
    asm volatile("ld.acquire.gpu.global.u32 %0, [%1];" : "=r"(v) : "l"(p) : "memory");
    return v;
}
__device__ __forceinline__ void red_release(unsigned int* p) { asm volatile("red.release.gpu.global.add.u32 [%0], 1;" ::"l"(p) : "memory"); }
__device__ __forceinline__ void wait_count(const unsigned int* p, uint32_t target) {
#pragma unroll 1
    for (uint32_t it = 0; it < SPIN_LIMIT; ++it)
        if ((int)(ld_acquire(p) - target) >= 0) return;
    __trap();
}
__device__ __forceinline__ void wait_count_slow(const unsigned int* p, uint32_t target) {
#pragma unroll 1
    for (uint32_t it = 0; it < SPIN_LIMIT; ++it) {
        if ((int)(ld_acquire(p) - target) >= 0) return;
        __nanosleep(200);
    }
    __trap();
}
__device__ __forceinline__ unsigned long long ld_relaxed1(const void* p) {
    unsigned long long v;
    asm volatile("ld.relaxed.gpu.global.b64 %0, [%1];" : "=l"(v) : "l"(p) : "memory");
    return v;
}
__device__ __forceinline__ ulonglong2 ld_relaxed2(const void* p) {
    ulonglong2 v;
    asm volatile("ld.relaxed.gpu.global.v2.b64 {%0, %1}, [%2];" : "=l"(v.x), "=l"(v.y) : "l"(p) : "memory");
    return v;
}
__device__ __forceinline__ void ld_cell(uint32_t (&v)[4], const void* p, bool on = true) {
    asm volatile("{ .reg .pred p; .reg .b64 l, h; .reg .b128 t; setp.ne.u32 p, %5, 0; mov.b64 l, {%0, %1}; mov.b64 h, {%2, %3}; mov.b128 t, {l, h};\n"
                 "@p ld.relaxed.gpu.global.b128 t, [%4]; mov.b128 {l, h}, t; mov.b64 {%0, %1}, l; mov.b64 {%2, %3}, h; }"
                 : "+r"(v[0]), "+r"(v[1]), "+r"(v[2]), "+r"(v[3]) : "l"(p), "r"((uint32_t)on) : "memory");
}
__device__ __forceinline__ void st_cell(void* p, uint32_t a, uint32_t b, uint32_t c, uint32_t d, bool on) {
    asm volatile("{ .reg .pred p; .reg .b64 l, h; .reg .b128 t; setp.ne.u32 p, %5, 0; mov.b64 l, {%1, %2}; mov.b64 h, {%3, %4}; mov.b128 t, {l, h};\n"
                 "@p st.relaxed.gpu.global.b128 [%0], t; }" ::"l"(p), "r"(a), "r"(b), "r"(c), "r"(d), "r"((uint32_t)on) : "memory");
}

__device__ __forceinline__ uint64_t make_desc(uint32_t addr, uint32_t sbo = 1024) {
    return (uint64_t)((addr & 0x3FFFF) >> 4) | ((uint64_t)1 << 16) | ((uint64_t)(sbo >> 4) << 32) | ((uint64_t)1 << 62);
}
__device__ __forceinline__ void wgmma_fence() { asm volatile("wgmma.fence.sync.aligned;" ::: "memory"); }
__device__ __forceinline__ void wgmma_commit() { asm volatile("wgmma.commit_group.sync.aligned;" ::: "memory"); }
template <int N> __device__ __forceinline__ void wgmma_wait() { asm volatile("wgmma.wait_group.sync.aligned %0;" ::"n"(N) : "memory"); }

#define R8(d, i) "+f"(d[i]), "+f"(d[i + 1]), "+f"(d[i + 2]), "+f"(d[i + 3]), "+f"(d[i + 4]), "+f"(d[i + 5]), "+f"(d[i + 6]), "+f"(d[i + 7])
#define R64(d) R8(d, 0), R8(d, 8), R8(d, 16), R8(d, 24), R8(d, 32), R8(d, 40), R8(d, 48), R8(d, 56)
template <int TA>
__device__ __forceinline__ void wgmma_n128(float (&d)[64], uint64_t da, uint64_t db, int scale_d = 1) {
    asm volatile("{ .reg .pred p; setp.ne.b32 p, %66, 0;\n"
                 "wgmma.mma_async.sync.aligned.m64n128k16.f32.bf16.bf16 "
                 "{%0,%1,%2,%3,%4,%5,%6,%7,%8,%9,%10,%11,%12,%13,%14,%15,%16,%17,%18,%19,%20,%21,%22,%23,%24,%25,%26,%27,%28,%29,%30,%31,"
                 "%32,%33,%34,%35,%36,%37,%38,%39,%40,%41,%42,%43,%44,%45,%46,%47,%48,%49,%50,%51,%52,%53,%54,%55,%56,%57,%58,%59,%60,%61,%62,%63}, "
                 "%64, %65, p, 1, 1, %67, 0; }"
                 : R64(d)
                 : "l"(da), "l"(db), "r"(scale_d), "n"(TA));
}
__device__ __forceinline__ void pin4(float (&d)[4]) { asm volatile("" : "+f"(d[0]), "+f"(d[1]), "+f"(d[2]), "+f"(d[3])::"memory"); }
__device__ __forceinline__ void pin64(float (&d)[64]) { asm volatile("" : R64(d)::"memory"); }

template <int TA, int TB = 0>
__device__ __forceinline__ void wgmma_n8(float (&d)[4], uint64_t da, uint64_t db, int scale_d = 1) {
    asm volatile("{ .reg .pred p; setp.ne.b32 p, %7, 0;\n"
                 "wgmma.mma_async.sync.aligned.m64n8k16.f32.bf16.bf16 {%0,%1,%2,%3}, %4, %5, p, 1, 1, %6, %8; }"
                 : "+f"(d[0]), "+f"(d[1]), "+f"(d[2]), "+f"(d[3])
                 : "l"(da), "l"(db), "n"(TA), "r"(scale_d), "n"(TB));
}

__device__ __forceinline__ float bf_lo(uint32_t u) { return __uint_as_float(u << 16); }
__device__ __forceinline__ float bf_hi(uint32_t u) { return __uint_as_float(u & 0xFFFF0000u); }
__device__ __forceinline__ float rbf(float v) { return __bfloat162float(__float2bfloat16_rn(v)); }
__device__ __forceinline__ uint32_t pack_bf(float lo, float hi) {
    uint32_t r;
    asm("cvt.rn.bf16x2.f32 %0, %1, %2;" : "=r"(r) : "f"(hi), "f"(lo));
    return r;
}
__device__ __forceinline__ uint32_t mul_bf2(uint32_t a, uint32_t b) {
    __nv_bfloat162 r = __hmul2(*reinterpret_cast<__nv_bfloat162*>(&a), *reinterpret_cast<__nv_bfloat162*>(&b));
    return *reinterpret_cast<uint32_t*>(&r);
}
__device__ __forceinline__ uint32_t fma_bf2(uint32_t a, uint32_t b, uint32_t c) {
    uint32_t r;
    asm("fma.rn.bf16x2 %0, %1, %2, %3;" : "=r"(r) : "r"(a), "r"(b), "r"(c));
    return r;
}
__device__ __forceinline__ float2 cmul(float2 a, float2 b) { return make_float2(a.x * b.x - a.y * b.y, a.x * b.y + a.y * b.x); }
__device__ __forceinline__ float2 cfma(float2 a, float2 b, float2 c) {
    return make_float2(fmaf(a.x, b.x, fmaf(-a.y, b.y, c.x)), fmaf(a.x, b.y, fmaf(a.y, b.x, c.y)));
}
__device__ __forceinline__ float sigmoidf_(float v) { return __fdividef(1.0f, 1.0f + expf(-v)); }

__device__ __forceinline__ void bulk_prefetch(const void* src, uint32_t bytes) {
    asm volatile(ONE "cp.async.bulk.prefetch.L2.global [%0], %1; }" ::"l"(src), "r"(bytes) : "memory");
}
__device__ __forceinline__ void bulk_store(void* dst, uint32_t src, uint32_t bytes) {
    asm volatile(ONE "cp.async.bulk.global.shared::cta.bulk_group [%0], [%1], %2; }" ::"l"(dst), "r"(src), "r"(bytes) : "memory");
}
__device__ __forceinline__ void stsm4(uint32_t a, uint32_t x, uint32_t y, uint32_t z, uint32_t w) {
    asm volatile("stmatrix.sync.aligned.m8n8.x4.shared.b16 [%0], {%1,%2,%3,%4};" ::"r"(a), "r"(x), "r"(y), "r"(z), "r"(w) : "memory");
}
__device__ __forceinline__ uint4 ldsm4(uint32_t a) {
    uint4 v;
    asm volatile("ldmatrix.sync.aligned.m8n8.x4.shared.b16 {%0,%1,%2,%3}, [%4];" : "=r"(v.x), "=r"(v.y), "=r"(v.z), "=r"(v.w) : "r"(a) : "memory");
    return v;
}
__device__ __forceinline__ void stg4_unless(float* p, float a, float b, float c, float d, uint32_t skip) {
    asm volatile("{ .reg .pred p; setp.eq.u32 p, %5, 0; @p st.global.v4.f32 [%0], {%1,%2,%3,%4}; }" ::"l"(p), "f"(a), "f"(b), "f"(c), "f"(d), "r"(skip) : "memory");
}
__device__ __forceinline__ void red4(float* p, float a, float b, float c, float d) {
    asm volatile("red.global.add.v4.f32 [%0], {%1,%2,%3,%4};" ::"l"(p), "f"(a), "f"(b), "f"(c), "f"(d) : "memory");
}

#define TT0 2900
#define PER 510
#define PCUT 60
#define PFIN 360
#define PF0 1500
#define PFX_PACE 400
#define PF1 700
#define T2 300
#define P2 520
#define G0 450
#define R0 2100
#define R_PACE 350
#define W_SHIFT 250
#define PROMO CU_TENSOR_MAP_L2_PROMOTION_L2_256B
#define POLL_S 0
#define ST_TOL 100
#define ST_SHIFT 300
#define CLK_NS 420
#define MARGIN 60
#define BP1 12
#define DV 15
#define FE 5
#define HP 4
#define AE 6
#define AG0 900
#define AB 17
#define HGE 39
constexpr uint32_t duration(int i) { return PER + (i >= RE0 && i < RE0 + 4 ? 72 : 0) + (i >= GU0 && i < GU0 + 32 ? 36 : 0); }
constexpr uint32_t cmax(uint32_t a, uint32_t b) { return a > b ? a : b; }
constexpr uint32_t issue_time(int i) {
    return i <= NST ? TT0 : i < XE ? issue_time(i - 1) + duration(i - NST) - (i >= XE - 3 && i > GU0 + 36 ? PCUT : 0) : issue_time(XE - 1) + cmax((i - XE + 1) * PFIN, (i - XE) * 512);
}
template <int I> struct Sched { static constexpr uint32_t t = issue_time(I); };
template <int LO, int HI, class F>
__device__ __forceinline__ void for_entries(uint32_t base, F body) {
    constexpr uint32_t per = Sched<LO + 1>::t - Sched<LO>::t;
    static_assert(Sched<HI - 1>::t - Sched<LO>::t == (HI - 1 - LO) * per, "period");
    uint32_t tt = base + Sched<LO>::t;
#pragma unroll 1
    for (int i = LO; i < HI; i++) {
        body(i, tt);
        tt += per;
    }
}

struct Ring { uint32_t prev; int slot; };
struct NoHook { __device__ void operator()() const {} };
template <int TA, int SM, class H = NoHook>
__device__ __forceinline__ void run_entries(Ring& r, int lo, int hi, float (&accA)[64], float (&accB)[64], float (&small)[4],
                                            bool fresh = false, bool sfresh = false, H released = H()) {
    const uint64_t d0 = make_desc(sb);
    const bool leader = (threadIdx.x & 31) == 0;
#pragma unroll 1
    for (int i = lo; i < hi; i++) {
        const uint32_t bar = sb + OFF_FULL + 8 * i;
        const uint64_t da = d0 + (uint64_t)(r.slot * (SLOT >> 4));
        const int n = i - (SM == 1 ? RE0 : GU0);
        const uint64_t dw = SM == 1 ? d0 + (uint64_t)((OFF_W >> 4) + n * 512)
                                    : (((uint64_t)2 << 62) | ((uint64_t)32 << 32) | (128u << 16) | ((sb + OFF_W) >> 4)) + (uint64_t)((n & 7) * 256);
        const uint64_t dt8 = d0 + (uint64_t)((OFF_XS >> 4) + (SM == 1 ? n * 64 : (n >> 1) * 64 + (n & 1) * 4));
        r.slot = r.slot == NST - 1 ? 0 : r.slot + 1;
        mbar_wait(bar);
        KSTAMP(i);
        wgmma_fence();
#pragma unroll
        for (int kk = 0; kk < 4; kk++) {
            wgmma_n128<TA>(accA, da + kk * (TA ? 128 : 2), da + 1024 + kk * 2, kk > 0 || !fresh);
            if (SM && kk == 3) {
#pragma unroll
                for (int u = 0; u < (SM == 1 ? 4 : 2); u++) wgmma_n8<SM - 1 + !SM>(small, dw + u * (SM == 1 ? 2 : 64), dt8 + u * 2, u > 0 || !sfresh);
            }
            wgmma_n128<TA>(accB, da + 512 + kk * (TA ? 128 : 2), da + 1024 + kk * 2, kk > 0 || !fresh);
            if (kk == 1) {
                wgmma_commit();
                wgmma_wait<1>();
                if (leader) mbar_arrive(r.prev);
                released();
            }
        }
        wgmma_commit();
        r.prev = bar + (OFF_EMPTY - OFF_FULL);
        fresh = sfresh = false;
    }
}
template <int HALF, int I>
__device__ __forceinline__ void run_small(float (&acc)[64]) {
    const uint64_t da = make_desc(sb) + (slot_off(I) >> 4);
    KSTAMP(I + HALF * (NENT - FIN));
    wgmma_fence();
#pragma unroll
    for (int kk = 0; kk < 4; kk++) wgmma_n128<1>(acc, da + HALF * 512 + kk * 128, da + 1024 + kk * 2, kk > 0 || !(HALF && I == FIN));
    wgmma_commit();
}
template <int V> struct Int { __host__ __device__ constexpr operator int() const { return V; } };
template <int N, class F> __device__ __forceinline__ void static_for(F f) {
    if constexpr (N > 0) { static_for<N - 1>(f); f(Int<N - 1>()); }
}

template <bool BY_SMID>
__global__ void __launch_bounds__(384, 1)
fused_kernel(const __grid_constant__ Params prm, const __grid_constant__ CUtensorMap mX, const __grid_constant__ CUtensorMap mB, const __grid_constant__ CUtensorMap mCre,
             const __grid_constant__ CUtensorMap mCim, const __grid_constant__ CUtensorMap mW,
             const __grid_constant__ CUtensorMap mWd, const __grid_constant__ CUtensorMap mXr, const __grid_constant__ CUtensorMap mXe) {
    extern __shared__ __align__(1024) uint8_t smem[];
    const uint32_t cstart = clk32();
    const int tid = threadIdx.x, lane = tid & 31;
    uint32_t id = blockIdx.x;
    if (BY_SMID) asm volatile("mov.u32 %0, %%smid;" : "=r"(id));
    {
        const uint32_t o = (tid * 2056) & 0x7880, b = (id & 127) * 8192;
        asm volatile("{ .reg .pred p, q; setp.lt.u32 p, %3, 32; setp.eq.u32 q, %4, 0;\n"
                     "@q prefetch.global.L2 [%1]; @p prefetch.global.L2 [%0]; @q prefetch.global.L2 [%2]; }"
                     ::"l"((const char*)prm.x + (b * 4 + o)), "l"((const char*)prm.b_re + (b + o)), "l"((const char*)prm.b_im + (b + o)), "r"(tid), "r"(tid & ~19) : "memory");
    }
    const int warp = __shfl_sync(0xffffffffu, tid >> 5, 0);
    gap();
    int cta;
    asm("{ .reg .pred p; .reg .u32 a, b, u, q;\n"
        "and.b32 a, %1, 14; shl.b32 a, a, 3; shr.u32 b, %1, 3; and.b32 b, b, 6; add.u32 a, a, b;\n"
        "and.b32 u, %1, 62; mul.lo.u32 q, u, 37; shr.u32 q, q, 9; shl.b32 u, u, 3; mad.lo.u32 u, q, -110, u; add.u32 u, u, 24;\n"
        "setp.lt.u32 p, %1, 64; selp.u32 a, a, u, p; lop3.b32 a, a, %1, 1, 0xF8;\n"
        "setp.lt.u32 p, %1, 124; selp.u32 b, 8, -116, p; add.u32 b, b, %1; setp.lt.u32 p, %1, 120; selp.u32 %0, a, b, p; }" : "=r"(cta) : "r"(id));
    const int chunk = (cta >> 5) * 4 + ((cta >> 2) & 3);
    const int dt = ((cta >> 4) & 1) * 4 + (cta & 3);
    if ((warp | (cta & NCTA)) == 5) {
        mbar_init_n<2>(sb + OFF_FULL, 1);
        tma5b(sb, &mB, 0, dt * 4, sb + OFF_FULL);
        gap();
        tma4(sb + 2 * ABYTES, &mX, 0, chunk * 64, sb + OFF_FULL);
        tma5b(sb + SLOT, &mB, 64, dt * 4, sb + OFF_FULL + 8);
        tma4(sb + SLOT + 2 * ABYTES, &mX, 64, chunk * 64, sb + OFF_FULL + 8);
    }
    if (cta >= NCTA) {
        if (smem_u32(smem) != sb) __trap();
        if (tid == 0) wait_count_slow(&prm.s->cnt[0], (atomicAdd(&prm.s->cnt[0], 1u) / NGRID + 1) * NGRID);
        return;
    }
    const bool has_gu = cta >= 16;
    constexpr uint32_t full = sb + OFF_FULL, empty = sb + OFF_EMPTY;
    constexpr uint32_t raw = full + 8 * 32;
    constexpr uint32_t bar_hraw = full + 8 * 97, bar_xs = full + 8 * 98, bar_xb = full + 8 * 100, bar_xa = full + 8 * 101,
        bar_retry = full + 8 * 102, bar_out = full + 8 * 104;
    constexpr uint32_t bar_base = empty - 64, bar_init3 = empty - 56, bar_rdone = empty - 48, bar_order0 = empty - 40, bar_init2 = empty - 32,
        bar_vec = empty - 24, bar_epoch = empty - 16, bar_dummy = empty - 8, bar_xs0 = empty + 8 * 69,
        bar_zero = empty + 8 * 70, bar_xafree = empty + 8 * 71, bar_order2 = empty + 8 * 72, bar_dn = empty + 8 * 73, bar_fp = empty + 8 * 74,
        bar_accb = empty + 8 * 76, bar_xbfree = empty + 8 * 78, bar_fold = empty + 8 * 79, bar_st = empty + 8 * 80,
        bar_order1 = empty + 8 * 67, bar_cand = empty + 8 * 68;

    if (warp == 5) {
        STAMP(31);
        if (lane < 2) mbar_expect_tx(full + 8 * lane, SLOT);
        __syncwarp();
        named_bar(0, 256);
#pragma unroll 1
        for (int i = 2; i < NST; i++) {
            pace_until(cstart + T2 + i * P2);
            tma5b(sb + i * SLOT, &mB, i * 64, dt * 4, full + 8 * i);
            tma4(sb + i * SLOT + 2 * ABYTES, &mX, i * 64, chunk * 64, full + 8 * i);
            STAMPIF(i == 4, 1);
        }
    } else if (warp == 4) {
        mbar_init_n<12>(bar_init2, 4);
        asm volatile("bar.arrive 0, 256;" ::: "memory");
        mbar_init_n<4>(bar_base, 4);
        mbar_init_n<8>(empty + 64, 4);
        *reinterpret_cast<uint2*>(smem + OFF_KEYS + 16) = make_uint2(0, 0);
        asm volatile("bar.arrive 1, 64;" ::: "memory");
        asm volatile("bar.arrive 5, 96;" ::: "memory");
        asm volatile("bar.arrive 6, 96;" ::: "memory");
        mbar_init_n<32>(full + 256, 3);
        if (lane < 2) mbar_arrive(bar_init2);
    } else if ((warp >> 1) == 3) {
        if (warp == 6) {
            mbar_init_n<8>(full + 16, 1);
            if (lane >= 2 && lane < 10) mbar_expect_tx(full + 8 * lane, lane >= RE0 && lane < RE0 + 4 ? SLOT + ABYTES : SLOT);
            __syncwarp();
            asm volatile("bar.arrive 0, 256;" ::: "memory");
        }
        const char* pf0 = (warp & 1) ? (const char*)((cta & 64) ? prm.b_im : prm.b_re) + (cta & 63) * 16384 : (const char*)prm.x + cta * 32768;
        pace_until(cstart + PF1);
        asm volatile("prefetch.global.L2 [%0];" ::"l"(pf0 + (lane & (30 >> (warp & 1) & 30)) * 1024 + (lane & 1) * 128 + 256));
        const int i0 = warp == 6 ? 10 : 21;
        mbar_init_n<11>(full + 8 * i0, 1);
        if (lane >= i0 && lane < i0 + 11) mbar_expect_tx(full + 8 * lane, lane >= GU0 && has_gu ? SLOT + WBYTES : SLOT);
        mbar_init_n<24>(full + 512 + 192 * (warp & 1), 1);
        named_bar(5, 96);
        if (lane == 0) mbar_arrive(bar_init2);
        STAMP(21);
    }
    __syncwarp();

    if (warp >= 8) {
        asm volatile("setmaxnreg.dec.sync.aligned.u32 72;");
        const uint32_t c0 = cstart;
        uint64_t stream;
        asm volatile("createpolicy.fractional.L2::evict_first.b64 %0, 1.0;" : "=l"(stream));
        const int dc = (cta & 15) * 64, dr = (cta >> 4) * 448;
        auto gutile = [&](int i) {
            const int n = i + 3 - GU0;
            if (has_gu) tma3s(sb + OFF_W + (n & 7) * WBYTES, &mW, cta * 32 - 512, n * 32, full + 8 * (i + 3), stream);
        };
        if (warp == 8) {
            named_bar(0, 256);
            asm volatile("prefetch.tensormap [%0];" ::"l"(&mXr));
#pragma unroll 1
            for (int u = 0; u < 2; u++) {
                sleep_until(c0 + R0 + u * R_PACE);
                tma3(sb + OFF_W + u * ABYTES, &mXr, u * 256, cta * 16, full + 8 * (RE0 + u));
            }
            uint32_t dst = sb;
            auto gemm1 = [&](int i, uint32_t tt) {
                mbar_wait(empty + 8 * (i - NST));
                LATE(i, tt);
                pace_until(tt);
                tma5b(dst, &mB, (i & 15) * 64, (i >> 4) * 64 + dt * 4, full + 8 * i);
                tma4(dst + 2 * ABYTES, &mX, (i & 15) * 64, chunk * 64, full + 8 * i);
                dst = dst == sb + (NST - 1) * SLOT ? sb : dst + SLOT;
            };
            mbar_wait(bar_init2);
            uint32_t tt = c0 + TT0;
#pragma unroll 1
            for (int i = NST; i < AB; i++) {
                gemm1(i, tt);
                if (i < 7) tma3(sb + OFF_W + (i - 3) * ABYTES, &mXr, (i - 3) * 256, cta * 16, full + 8 * (i + 1));
                tt += (i & ~3) == RE0 + 4 ? PER + 72 : PER;
            }
            mbar_wait(bar_base);
            const uint32_t base = uni(lds32(sb + OFF_EPOCH + 8));
            tt = base + Sched<AB>::t;
#pragma unroll 1
            for (int i = AB; i < 32; i++) {
                gemm1(i, tt);
                tt += i >= GU0 + 4 ? PER + 36 : PER;
            }
            const char* hsrc = reinterpret_cast<const char*>(prm.s->h) + (size_t)chunk * 524288;
            auto gemm2 = [&](int i, uint32_t d, int freed, uint32_t tt) {
                mbar_wait(empty + 8 * freed);
                LATE(i, tt);
                pace_until(tt);
                bulk_load(d, hsrc, 2 * ABYTES, raw + 8 * i);
                tma5(d + 2 * ABYTES, (i & 4) ? &mCim : &mCre, ((i & 3) + ((i >> 1) & 12)) * 64, dt * 8, full + 8 * i);
                hsrc += 2 * ABYTES;
            };
            for_entries<32, GU0 + 29>(base, [&](int i, uint32_t tt) {
                gemm2(i, dst, i - NST, tt);
                gutile(i);
                dst = dst == sb + (NST - 1) * SLOT ? sb : dst + SLOT;
            });
            for_entries<GU0 + 29, GU0 + 37>(base, [&](int i, uint32_t tt) {
                gemm2(i, dst, i - NST, tt);
                const int n = i - GU0 - 29;
                if ((n & 5) == 1) tma5(sb + OFF_W + (n & 2) * (ABYTES / 2), &mXe, dt * 128 + (n & 2) * 32, chunk * 64, bar_xa);
                else if (n < 6) asm volatile(ONE "cp.async.bulk.prefetch.tensor.2d.L2.global [%0, {%1, %2}]; }" ::"l"(&mWd), "r"(dc), "r"(dr + 64 * (n < 4 ? 3 + n / 2 : n + 1)) : "memory");
                dst = dst == sb + (NST - 1) * SLOT ? sb : dst + SLOT;
            });
            static_for<NENT - GU0 - 37>([&](auto u) {
                constexpr int i = GU0 + 37 + u;
                if (i == 60) mbar_wait(bar_out + 56);
                gemm2(i, sb + slot_off(i), i < XE ? i - NST : i == XE ? 71   : i - NST - 1, base + Sched<i>::t);
            });
            STAMP(4);
        } else if (warp == 9) {
#pragma unroll
            for (int u = 0; u < 8; u++) {
                const int row = (u >> 2) * 4 + (lane >> 3);
                asm volatile("cp.async.cg.shared.global [%0], [%1], 16;" ::"r"(sb + OFF_XS + (u & 3) * 1024 + row * 128 + (((lane & 7) ^ row) << 4)),
                             "l"((const char*)(u < 4 ? prm.w_r : prm.gate_w) + (u & 3) * 512 + lane * 16) : "memory");
            }
            uint32_t ticket = 0;
            if (lane == 0) ticket = atomicAdd(&prm.s->cnt[0], 1u);
            named_bar(1, 64);
            if (lane == 0) *reinterpret_cast<volatile uint32_t*>(smem + OFF_EPOCH) = ticket / NGRID;
            __syncwarp();
            if (lane < 4) mbar_arrive(bar_epoch);
            asm volatile("cp.async.wait_all;" ::: "memory");
            asm volatile("fence.proxy.async.shared::cta;" ::: "memory");
            __syncwarp();
            if (lane < 4) mbar_arrive(bar_vec);
            STAMP(18);
#pragma unroll 1
            for (int i = 4; i < 22; i++) mbar_init_n<4>(empty + 32 * i, 4, i >= 6 && i < 13);
            if (lane < 2) mbar_arrive(bar_init3);
            STAMP(19);
            mbar_wait(bar_cand);
            {
                const uint32_t* list = reinterpret_cast<const uint32_t*>(smem + OFF_LIST);
                const int n = (int)lds32(sb + OFF_KEYS + 16);
#pragma unroll 1
                for (int i0 = 0; i0 < n; i0 += 32) {
                    const uint32_t k = list[i0 + lane];
                    int rank = 0;
#pragma unroll 2
                    for (int o = 0; o < n; o += 4) {
                        const uint4 l4 = *reinterpret_cast<const uint4*>(list + o);
                        rank += (l4.x > k) + (l4.y > k) + (l4.z > k) + (l4.w > k);
                    }
                    if (rank < 8) reinterpret_cast<uint32_t*>(smem + OFF_SEL)[rank] = k;
                }
                __syncwarp();
                STAMP(6);
                const uint32_t key = lds32(sb + OFF_SEL + 4 * (lane & 7)), tok = ~key & 2047u, tag = lds32(sb + OFF_EPOCH) + 1;
                const uint32_t ta = __shfl_sync(0xffffffffu, tok, lane >> 3), tb = __shfl_sync(0xffffffffu, tok, 4 + (lane >> 3));
                const uint32_t da = sb + OFF_XS + (lane >> 3) * 128 + (((lane & 7) ^ (lane >> 3)) << 4), db = (da ^ 64) + 512;
                const char *sa = (const char*)prm.x + ta * 2048 + (lane & 7) * 16, *sc = (const char*)prm.x + tb * 2048 + (lane & 7) * 16;
#pragma unroll
                for (int u = 0; u < 16; u++) {
                    asm volatile("cp.async.cg.shared.global [%0], [%1], 16;" ::"r"(da + u * 1024), "l"(sa + u * 128) : "memory");
                    asm volatile("cp.async.cg.shared.global [%0], [%1], 16;" ::"r"(db + u * 1024), "l"(sc + u * 128) : "memory");
                    if (u == 3) {
                        asm volatile("cp.async.wait_all;" ::: "memory");
                        asm volatile("fence.proxy.async.shared::cta;" ::: "memory");
                        __syncwarp();
                        if (lane < 4) mbar_arrive(bar_xs0);
                        STAMP(17);
                    }
                }
                if ((tok >> 7) == (uint32_t)chunk) {
                    float4* zp = reinterpret_cast<float4*>(prm.out + tok * D_ + dt * 128) + (lane >> 3) * 2;
#pragma unroll
                    for (int u = 0; u < 8; u++) zp[(u >> 1) * 8 + (u & 1)] = make_float4(0.f, 0.f, 0.f, 0.f);
                }
                uint32_t it = 0;
                unsigned long long u;
                do {
                    u = ld_relaxed1(&prm.s->gpack[tok >> 1]);
                    if (++it > SPIN_LIMIT) __trap();
                } while (!__all_sync(0xffffffffu, (uint32_t)(u >> 32) == tag));
                const uint32_t kb = key >> 16;
                const float r = bf_lo((kb & 0x8000u) ? (kb & 0x7FFFu) : (~kb & 0xFFFFu)), gv = (tok & 1) ? bf_hi((uint32_t)u) : bf_lo((uint32_t)u);
                reinterpret_cast<float*>(smem + OFF_FAC)[lane & 7] = rbf(1.0f - gv) * rbf(sigmoidf_(r));
                asm volatile("cp.async.wait_all;" ::: "memory");
                asm volatile("fence.proxy.async.shared::cta;" ::: "memory");
                __syncwarp();
                if (lane == 0) mbar_arrive(bar_xs);
                STAMP(7);
            }
            char* hd = reinterpret_cast<char*>(prm.s->h) + (size_t)chunk * 524288 + (dt >> 1) * 16384 + (dt & 1) * 4096;
            mbar_wait(bar_base);
            const uint32_t cb = uni(lds32(sb + OFF_EPOCH + 8)) + ST_SHIFT;
            uint32_t tt = cb + Sched<GU0 + 4>::t;
#pragma unroll 1
            for (int np = 0; np < 16; np++) {
                if (!(np & (np & 4 ? 1 : 2))) mbar_wait(bar_st + 4 * (np & 12) + ((np & 3) ? 8 : 0));
                const uint32_t now = clk32() - ST_TOL;
#pragma unroll 1
                while ((int)(tt - now) < 0) tt += PER + 36;
                const uint32_t src = sb + OFF_STG + (np & 3) * 4096;
                pace_until(tt);
                bulk_store(hd, src, 4096);
                asm volatile("cp.async.bulk.commit_group;" ::: "memory");
                if (np & 2) {
                    if (np & 1) asm volatile("cp.async.bulk.wait_group.read 0;" ::: "memory");
                    else asm volatile("cp.async.bulk.wait_group.read 1;" ::: "memory");
                    __syncwarp();
                    const uint32_t u8 = 4 * (np & 12) + 8 * (np & 1);
                    if (lane < 2) mbar_arrive(lane ? (np < 15 ? empty + 8 * 27 + 4 * u8 : bar_dummy) : bar_out + u8);
                }
                STAMPIF(np & 2, 8 + ((np >> 1) & 6) + (np & 1));
                hd += (np & 1) ? 65536 - 8192 : 8192;
                tt += PER + 36;
            }
#pragma unroll 1
            for (int u = 0; u < 2; u++) {
                pace_until(tt);
                tma5(sb + OFF_STG + u * ABYTES, &mXe, dt * 128 + u * 64, chunk * 64 + 8, bar_xb);
                tt += PER + 36;
            }
            wait_count(&prm.s->cnt[32], (lds32(sb + OFF_EPOCH) + 1) * NCTA);
            auto load_hid = [&]() {
                if (lane == 0) mbar_expect_tx(bar_hraw, 7168);
                bulk_load(sb + OFF_XS, prm.s->hid + dr, 7168, bar_hraw);
            };
            static_for<7>([&](auto u) {
                if (u != 2) mbar_wait(u == 1 ? bar_xbfree : empty + 8 * (u == 0 ? GU0 + 31 : FIN - 2 + u));
                if (u < 3) sleep_until(cb + Sched<GU0 + HGE - 2 + u>::t);
                if (u == 2) load_hid();
                tma2(sb + dn_off(u), &mWd, dc, dr + u * 64, bar_dn, stream);
                if (u == 2) {
                    const uint32_t t2 = lds32(sb + OFF_EPOCH) + 1, tagw = (t2 & 1) | ((t2 & 2) << 15);
#pragma unroll 1
                    for (uint32_t it = 0;; it++) {
                        mbar_wait(bar_hraw, it & 1);
                        uint32_t bad = 0;
#pragma unroll
                        for (int i = 0; i < 14; i++) bad |= lds32(sb + OFF_XS + i * 512 + lane * 16 + (lane >> 3) * 4) ^ tagw;
                        if (__all_sync(0xffffffffu, (bad & 0x00010001u) == 0)) break;
                        if (it > SPIN_LIMIT) __trap();
                        load_hid();
                    }
                    if (lane < 4) mbar_arrive(bar_zero);
                    STAMP(48);
                }
            });
            STAMP(27);
        } else {
            named_bar(6, 96);
            if (warp == 10) {
                const char* pb = (const char*)((cta & 64) ? prm.b_im : prm.b_re) + (cta & 63) * 16384;
                const char* pf = (lane < 16 ? (const char*)prm.x + cta * 32768 : pb) + (lane & 15) * 2048 + 512;
#pragma unroll 1
                for (int k = 0; k < 11; k++) {
                    sleep_until(c0 + PF0 + k * PFX_PACE);
                    if (lane < 16 ? k < 6 : lane < 24 && !(k & 1)) prefetch_l2(pf + k * (lane < 16 ? 256 : 128));
                }
#pragma unroll 1
                for (int k = 0; k < 12; k++) {
                    sleep_until(c0 + Sched<12>::t + ST_SHIFT + (k + BP1 - 12) * PER);
                    bulk_prefetch((k < 4 ? pb + 1048576 : (const char*)(k < 8 ? prm.c_re : prm.c_im) + cta * 16384) + (k & 3) * 4096, 4096);
                    if (k == 4) { mbar_wait(bar_init2); mbar_wait(bar_init3); }
                    if (k >= 4 && lane < 8) mbar_expect_tx(full + 8 * (8 * k + lane), 8 * k + lane < GU0 + 32 && has_gu ? 2 * ABYTES + WBYTES : 2 * ABYTES);
                }
                asm volatile("prefetch.tensormap [%0];" ::"l"(&mCre));
                asm volatile("prefetch.tensormap [%0];" ::"l"(&mCim));
                asm volatile("prefetch.tensormap [%0];" ::"l"(&mWd));
                asm volatile("prefetch.tensormap [%0];" ::"l"(&mXe));
                if (lane < 2) mbar_expect_tx(bar_xb + 8 * lane, 2 * ABYTES);
                mbar_wait(bar_xs);
                mbar_wait(bar_st);
                if (lane == 0) red_release(&prm.s->cnt[32]);
                __syncwarp();
                STAMP(22);
            } else {
                asm volatile("prefetch.tensormap [%0];" ::"l"(&mW));
                mbar_wait(bar_epoch);
                const uint32_t tag = lds32(sb + OFF_EPOCH) + 1;
                st_cell(prm.s->time + cta, 0, 0, 0, 0, lane == 0);
                mbar_wait(empty + 8 * AE);
                uint32_t gown, tm[4][4] = {}, it = 0;
                asm volatile("mov.u32 %0, %%globaltimer_lo;" : "=r"(gown));
                const uint32_t town = clk32();
                st_cell(prm.s->time + cta, tag, town, gown, 0, lane == 0);
                sleep_until(town + AG0);
                do {
#pragma unroll
                    for (int m = 0; m < 4; m++) ld_cell(tm[m], prm.s->time + ((cta & 96) ^ (32 * m)) + lane);
                    if (++it > SPIN_LIMIT) __trap();
                } while (!__all_sync(0xffffffffu, tm[0][0] == tag && tm[1][0] == tag && tm[2][0] == tag && tm[3][0] == tag));
                const int last = __reduce_max_sync(0xffffffffu, max(max((int)(tm[0][2] - gown), (int)(tm[1][2] - gown)), max((int)(tm[2][2] - gown), (int)(tm[3][2] - gown))));
                const uint32_t cand = tm[0][1] + ((min((int)(gown + last - tm[0][2]), 4000) * CLK_NS) >> 8);
                const uint32_t b0 = __shfl_sync(0xffffffffu, cand, cta & 16), b1 = __shfl_sync(0xffffffffu, cand, cta & 30);
                const uint32_t b2 = __shfl_sync(0xffffffffu, cand, cta & 31);
                const uint32_t base = (b0 - b2 + 400u < 800u ? b0 : b1 - b2 + 400u < 800u ? b1 : b2) + MARGIN - Sched<AE + NST>::t;
                *reinterpret_cast<volatile uint32_t*>(smem + OFF_EPOCH + 8) = base;
                mbar_wait(bar_init3);
                if (lane < 4) mbar_arrive(bar_base);
                STAMP(23);
                const uint32_t cb = base + W_SHIFT;
                auto early = [&](int i, uint32_t tt) {
                    mbar_wait(empty + 8 * (i - NST));
                    pace_until(tt);
                    gutile(i);
                };
                for_entries<GU0 - 3, GU0 + 4>(cb, early);
                for_entries<GU0 + 4, 32>(cb, early);
            }
            mbar_wait(bar_epoch);
            const uint32_t t2 = lds32(sb + OFF_EPOCH) + 1, tagw = (t2 & 1) | ((t2 & 2) << 15), half = (warp & 1) * ABYTES;
            const uint32_t lo = half + lane * 32 + (lane & 4) * 4 + (lane >> 3) * 4, retry = bar_retry + (warp & 1) * 8;
            const bool leader = lane == 0;
            uint32_t slot = sb + (32 % NST) * SLOT, rpar = 0;
#pragma unroll 1
            for (int i = 32; i < NENT; i++) {
                const uint32_t src = i == XE ? sb + OFF_W : slot;
                if (i != XE) slot = slot == sb + (NST - 1) * SLOT ? sb : slot + SLOT;
                auto current = [&]() {
                    uint32_t v[8];
#pragma unroll
                    for (int u = 0; u < 8; u++) v[u] = lds32(src + lo + u * 1024);
#pragma unroll
                    for (int u = 0; u < 8; u += 2) asm("lop3.b32 %0, %0, %1, %2, 0x7e;" : "+r"(v[u]) : "r"(v[u + 1]), "r"(tagw));
                    return __all_sync(0xffffffffu, ((v[0] | v[2] | v[4] | v[6]) & 0x00010001u) == 0);
                };
                mbar_wait(raw + 8 * i);
                if (!current()) {
#pragma unroll 1
                    for (uint32_t it = 0;; it++) {
                        if (it > SPIN_LIMIT) __trap();
                        STAMP(16);
                        if (leader) mbar_expect_tx(retry, ABYTES);
                        bulk_load(src + half, reinterpret_cast<const char*>(prm.s->h) + (size_t)chunk * 524288 + (i - 32) * 16384 + half, ABYTES, retry);
                        mbar_wait(retry, rpar);
                        rpar ^= 1;
                        if (current()) break;
                    }
                }
                if (leader) mbar_arrive(full + 8 * i);
            }
        }
    } else {
        asm volatile("setmaxnreg.inc.sync.aligned.u32 216;");
        const int wg = warp >> 2, w = warp & 3, g = lane >> 2, c = lane & 3, at = tid & 127;
        float facc[4];
        float2 a[2], m0[2], a32[2], a128[2];
        auto load_const = [&]() {
            const float2* cp = reinterpret_cast<const float2*>(smem + OFF_CONST) + wg * 64 + w * 8 + g;
#pragma unroll
            for (int h = 0; h < 2; h++) { a[h] = cp[32 * h]; m0[h] = cp[128 + 32 * h]; a32[h] = cp[256 + 32 * h]; a128[h] = cp[384 + 32 * h]; }
        };
        if (wg == 0) {
            named_bar(0, 256);
            STAMPIF(tid == 0, 20);
        } else {
            const int pc = (at >> 5) * 256 + dt * 32 + (at & 31);
            const float lr = __bfloat162float(prm.lam_re[pc]), li = __bfloat162float(prm.lam_im[pc]), ld = __bfloat162float(prm.log_dt[pc]);
            const uint32_t dk = __ldg(reinterpret_cast<const uint32_t*>(prm.dskip + dt * 128) + (at & 63));
#pragma unroll
            for (int i = 0; i < 4; i++) sts128(sb + OFF_LIST + i * 2048 + at * 16, 0u, 0u, 0u, 0u);

            {
                reinterpret_cast<uint32_t*>(smem + OFF_DK)[at & 63] = dk;
                const float dtv = rbf(expf(ld));
                const float er = expf(dtv * lr);
                float sn, cs;
                sincospif(dtv * li * 0.318309886183790672f, &sn, &cs);
                const float ar = er * cs, ai = er * sn;
                const float nr = ar - 1.0f, ni = ai;
                const bool big = fabsf(lr) >= fabsf(li);
                const float t = (big ? li : lr) / (big ? lr : li), dn = big ? lr + li * t : lr * t + li;
                const float cr = (big ? nr + ni * t : nr * t + ni) / dn, ci = (big ? ni - nr * t : ni * t - nr) / dn;
                float2* cp = reinterpret_cast<float2*>(smem + OFF_CONST) + at;
                float2 pw = make_float2(ar, prm.swapped ? ai : -ai);
                cp[0] = pw;
                cp[128] = make_float2(prm.swapped ? -2.f * cr : 2.f * cr, -2.f * ci);
#pragma unroll
                for (int i = 1; i <= 7; i++) {
                    pw = cmul(pw, pw);
                    if (i == 5) cp[256] = pw;
                    if (i == 7) cp[384] = pw;
                }
                __syncwarp();
            }
            named_bar(2, 128);
            load_const();
            mbar_wait(bar_epoch);
            const uint32_t tag = *reinterpret_cast<volatile uint32_t*>(smem + OFF_EPOCH) + 1;
            asm volatile("st.relaxed.gpu.global.b64 [%0], %1;" ::"l"(&prm.s->carry[(chunk >> 2) * 4096 + pc * 4 + (chunk & 3)]), "l"((unsigned long long)(tag + 2)) : "memory");
            if (w == 2) st_cell(lane < 4 ? (uint4*)prm.s->rpack + cta * 4 + lane : (uint4*)prm.s->gpack + cta * 4 + (lane & 3), 0, 0, 0, 0, lane < 8);
            {
                const uint32_t nt = ((tag & 1) | ((tag & 2) << 15)) ^ 0x00010001u;
                st_cell(prm.s->hid + cta * 32 - 512 + lane, nt, nt, nt, nt, has_gu && w == 3);
            }
            named_bar(2, 128);
            if (at < 2) mbar_arrive(bar_init3);
            unsigned long long* pub = (w ? prm.s->gpack : prm.s->rpack) + cta * 8 + lane;
            asm volatile("" : "+l"(pub));
            STAMPIF(lane == 0, 52);
            mbar_wait(bar_rdone);

            if (w < 2) {
                const float2* red = reinterpret_cast<const float2*>(smem + OFF_RED) + w * 8 + (lane & 7);
                const float2 r0 = red[0], r1 = red[16], r2 = red[32], r3 = red[48];
                const float v0 = (r0.x + r1.x) + (r2.x + r3.x), v1 = (r0.y + r1.y) + (r2.y + r3.y);
                uint32_t pk2;
                if (w == 0) {
                    pk2 = pack_bf(v0, v1);
                    pk2 ^= (((pk2 >> 15) & 0x00010001u) * 0x7FFFu) ^ 0x80008000u;
                } else pk2 = pack_bf(sigmoidf_(rbf(v0)), sigmoidf_(rbf(v1)));
                if (lane < 8) asm volatile("st.relaxed.gpu.global.b64 [%0], %1;" ::"l"(pub), "l"(((unsigned long long)tag << 32) | pk2) : "memory");
                __syncwarp();
            }
            STAMPIF(at == 0, 24);
            uint32_t it = 0, pr[8], g1;
            mbar_wait(bar_init3);
            sleep_until(clk32() + (w < 2 ? G0 : G0 + 250));
            while (true) {
                bool ok = true;
#pragma unroll
                for (int k = 0; k < 4; k++) {
                    const ulonglong2 u = ld_relaxed2(&prm.s->rpack[k * 256 + 2 * at]);
                    ok = ok && (uint32_t)(u.x >> 32) == tag && (uint32_t)(u.y >> 32) == tag;
                    pr[2 * k] = (uint32_t)u.x; pr[2 * k + 1] = (uint32_t)u.y;
                }
                const unsigned long long u1 = ld_relaxed1(&prm.s->gpack[chunk * 64 + (at & 63)]);
                ok = ok && (uint32_t)(u1 >> 32) == tag;
                g1 = (uint32_t)u1;
                if (__all_sync(0xffffffffu, ok)) break;
                if (++it > SPIN_LIMIT) __trap();
            }
            STAMPIF(lane == 0, 25);
            uint32_t m = __vmaxu2(__vimax3_u16x2(__vimax3_u16x2(pr[0], pr[1], pr[2]), pr[3], pr[4]), __vimax3_u16x2(pr[5], pr[6], pr[7]));
            m = (max(m, m << 16) & 0xFFFF0000u) | (uint32_t)lane;
            const uint32_t m1 = __reduce_max_sync(0xffffffffu, m), m2 = __reduce_max_sync(0xffffffffu, m == m1 ? 0u : m);
            uint32_t* keys = reinterpret_cast<uint32_t*>(smem + OFF_KEYS);
            if (lane == 0) keys[w] = m2;
            sts128(sb + OFF_XS + 4096 + at * 16, pr[0], pr[1], pr[2], pr[3]);
            sts128(sb + OFF_XS + 6144 + at * 16, pr[4], pr[5], pr[6], pr[7]);
            *reinterpret_cast<uint32_t*>(smem + OFF_G + 4 * (at & 63)) = g1;
            named_bar(2, 128);
            const uint4 th4 = *reinterpret_cast<const uint4*>(keys);
            const uint32_t th = (max(min(min(th4.x, th4.y), min(th4.z, th4.w)) >> 16, 1u) - 1u) * 0x00010001u;
            uint32_t mask = 0;
#pragma unroll
            for (int k = 7; k >= 0; k--) mask = mask * 2 + __vminu2(__vmaxu2(pr[k], th) ^ th, 0x00010001u);
            uint32_t pos = 0;
            asm volatile("{ .reg .pred p; setp.ne.u32 p, %2, 0; @p atom.shared.add.u32 %0, [%1], %2; }" : "+r"(pos) : "r"(sb + OFF_KEYS + 16), "r"(__popc(mask)) : "memory");
            while (mask) {
                const int bit = __ffs(mask) - 1, k = bit & 7, hi = bit >> 4;
                mask &= mask - 1;
                const uint32_t sc = *reinterpret_cast<const uint16_t*>(smem + OFF_XS + 4096 + (k >> 2) * 2048 + at * 16 + (k & 3) * 4 + hi * 2);
                *reinterpret_cast<uint32_t*>(smem + OFF_LIST + 4 * pos++) = (sc << 16) | (0x8000u + 2047u - (uint32_t)((k >> 1) * 512 + 4 * at + 2 * (k & 1) + hi));
            }
            __syncwarp();
            if (lane == 0) mbar_arrive(bar_cand);
            STAMPIF(lane == 0, 26);
            mbar_wait(bar_order0);
        }

        float accA[64], accB[64];
        Ring ring = {bar_dummy, wg};
        {
            run_entries<0, 0>(ring, wg * 16, wg ? GU0 : RE0, accA, accB, facc, true);
            if (wg == 0) {
                float racc[4];
                mbar_wait(bar_vec);
                run_entries<0, 1>(ring, RE0, RE0 + 4, accA, accB, racc, false, true);
                mbar_wait(bar_init2);
                const uint32_t red = sb + OFF_RED + 4 * (w * 32 + (c >> 1) * 16 + g);
                run_entries<0, 0>(ring, RE0 + 4, RE0 + 5, accA, accB, facc, false, false, [&]() {
                    pin4(racc);
                    asm volatile("{ .reg .pred p; setp.ne.u32 p, %3, 0; @p st.shared.f32 [%0], %1; @p st.shared.f32 [%0 + 32], %2; }" ::"r"(red),
                                 "f"((w & 1) ? racc[1] : racc[0]), "f"((w & 1) ? racc[3] : racc[2]), "r"((uint32_t)((c & 1) == (w >> 1))) : "memory");
                    __syncwarp();
                    if (lane == 0) mbar_arrive(bar_rdone);
                    STAMPIF(lane == 0, 5);
                });
                run_entries<0, 0>(ring, RE0 + 5, 16, accA, accB, facc);
                if (lane == 0) mbar_arrive(bar_order0);
                mbar_wait(bar_init3);
                load_const();
                named_bar(3, 128);
            } else {
#pragma unroll
                for (int u = 0; u < 2; u++) {
                    mbar_wait(u ? bar_xs : bar_xs0);
                    run_entries<0, 2>(ring, GU0 + 8 * u, u ? 32 : GU0 + 8, accA, accB, facc, false, u == 0);
                }
                if (lane == 0) mbar_arrive(bar_order1);
            }
        }
        const uint32_t tag = *reinterpret_cast<volatile uint32_t*>(smem + OFF_EPOCH) + 1;
        const float2 a64[2] = {cmul(a32[0], a32[0]), cmul(a32[1], a32[1])};
        wgmma_wait<0>();
        pin64(accA); pin64(accB); pin4(facc);
        if (lane == 0) mbar_arrive(ring.prev);
        STAMPIF(at == 0, 28 + wg);
        GSTAMP(tid == 0, 1);
        LP(1);

        const int tl = 32 * (g >> 1) + (g & 1) + 4 * w + 16 * wg, t0 = chunk * 128 + tl;
        float* op = prm.out + (size_t)t0 * D_ + dt * 128 + 4 * c;
        uint2 xv[8][2], dk[8];
        uint32_t gp[2], om[2], routed[2];
        auto row_setup = [&]() {
            const uint4 sa = *reinterpret_cast<const uint4*>(smem + OFF_SEL), sc = *reinterpret_cast<const uint4*>(smem + OFF_SEL + 16);
#pragma unroll
            for (int r = 0; r < 2; r++) {
                const uint32_t id = 0x8000u + 2047u - (uint32_t)(t0 + 2 * r);
                routed[r] = (uint16_t)sa.x == id || (uint16_t)sa.y == id || (uint16_t)sa.z == id || (uint16_t)sa.w == id ||
                            (uint16_t)sc.x == id || (uint16_t)sc.y == id || (uint16_t)sc.z == id || (uint16_t)sc.w == id;
                gp[r] = reinterpret_cast<const uint16_t*>(smem + OFF_G)[tl + 2 * r] * 0x00010001u;
                om[r] = pack_bf(1.0f - bf_hi(gp[r]), 1.0f - bf_hi(gp[r]));
            }
#pragma unroll
            for (int j = 0; j < 8; j++) dk[j] = lds64(sb + OFF_DK + 32 * j + 8 * c);
        };
        auto release = [&](uint32_t bar) {
            asm volatile("fence.proxy.async.shared::cta;" ::: "memory");
            __syncwarp();
            if (lane == 0) mbar_arrive(bar);
        };

        {
            const uint32_t t2 = tag & 3u;
            float2* cslot = &prm.s->carry[(wg * 512 + dt * 32 + w * 8 + g) * 4];
            const int j1 = chunk - 1 - c;
            unsigned long long v[2][4] = {{t2, t2, t2, t2}, {t2, t2, t2, t2}};
            auto poll = [&](int h) {
#pragma unroll
                for (int m = 0; m < 4; m++)
                    asm volatile("{ .reg .pred p; setp.ge.s32 p, %2, %3; @p ld.relaxed.gpu.global.b64 %0, [%1]; }"
                                 : "+l"(v[h][m]) : "l"(cslot + (j1 >> 2) * 4096 + c - m * 4096 + h * 1024), "r"(j1), "r"(4 * m) : "memory");
            };
            float2 e[2], w0[2];
            auto chain = [&](int h, int s0, int s1) {
                float (&acc)[64] = h ? accB : accA;
                if (s0 == 1) e[h] = make_float2(acc[0], acc[2]);
#pragma unroll
                for (int s = s0; s < s1; s++) {
                    const int i0 = 4 * (s >> 1) + (s & 1);
                    e[h] = cfma(make_float2(a[h].x, -a[h].y), e[h], make_float2(acc[i0], acc[i0 + 2]));
                }
                asm volatile("" : "+f"(e[h].x), "+f"(e[h].y), "+f"(accB[0]), "+f"(accB[2]));
                gap();
            };
            auto publish = [&](int h) {
                float2 f = make_float2(fmaf(m0[h].x, e[h].x, m0[h].y * e[h].y), fmaf(-m0[h].x, e[h].y, m0[h].y * e[h].x));
                float2 y = make_float2(__shfl_up_sync(0xffffffffu, f.x, 1, 4), __shfl_up_sync(0xffffffffu, f.y, 1, 4));
                if (c >= 1) f = cfma(a32[h], y, f);
                y = make_float2(__shfl_up_sync(0xffffffffu, f.x, 2, 4), __shfl_up_sync(0xffffffffu, f.y, 2, 4));
                if (c >= 2) f = cfma(a64[h], y, f);
                asm volatile("{ .reg .pred p; .reg .b64 t; setp.eq.u32 p, %3, 3; mov.b64 t, {%1, %2}; @p st.relaxed.gpu.global.b64 [%0], t; }"
                             ::"l"(cslot + (chunk >> 2) * 4096 + (chunk & 3) + h * 1024), "r"((__float_as_uint(f.x) & ~3u) | t2), "r"(__float_as_uint(f.y)), "r"(c) : "memory");
                w0[h] = make_float2(__shfl_up_sync(0xffffffffu, f.x, 1, 4), __shfl_up_sync(0xffffffffu, f.y, 1, 4));
                if (c == 0) w0[h] = make_float2(0.f, 0.f);
            };
            auto scale = [&](int h, int n0, int n1) {
                float (&acc)[64] = h ? accB : accA;
#pragma unroll
                for (int n = n0; n < n1; n++) {
                    asm volatile("{ .reg .f32 a, b, c, d, n; neg.f32 n, %4; mul.f32 a, %1, %5; mul.f32 b, %0, %5; mul.f32 c, %3, %5; mul.f32 d, %2, %5;\n"
                                 "fma.rn.f32 %0, %0, %4, a; fma.rn.f32 %1, %1, n, b; fma.rn.f32 %2, %2, %4, c; fma.rn.f32 %3, %3, n, d; }"
                                 : "+f"(acc[4 * n]), "+f"(acc[4 * n + 2]), "+f"(acc[4 * n + 1]), "+f"(acc[4 * n + 3]) : "f"(m0[h].x), "f"(m0[h].y));
                    gap();
                }
            };
            auto carry = [&](int h) {
                const float2 one = make_float2(1.f, 0.f), a256 = cmul(a128[h], a128[h]);
                float2 a512 = cmul(a256, a256), pw128 = cmul((j1 & 1) ? a128[h] : one, (j1 & 2) ? a256 : one);
                float2 pw32 = cmul((c & 1) ? a32[h] : one, (c & 2) ? a64[h] : one);
                asm volatile("" : "+f"(a512.x), "+f"(a512.y), "+f"(pw128.x), "+f"(pw128.y), "+f"(pw32.x), "+f"(pw32.y));
                STAMPIF(lane == 0 && !h, 34 + 2 * wg);
                uint32_t it = 0;
                while (!__all_sync(0xffffffffu, ((((uint32_t)v[h][0] ^ t2) | ((uint32_t)v[h][1] ^ t2) | ((uint32_t)v[h][2] ^ t2) | ((uint32_t)v[h][3] ^ t2)) & 3u) == 0)) {
                    poll(h);
                    if (++it > SPIN_LIMIT) __trap();
                }
                STAMPIF(lane == 0 && !h, 35 + 2 * wg);
                float2 hin = make_float2(__uint_as_float((uint32_t)v[h][3]), __uint_as_float((uint32_t)(v[h][3] >> 32)));
#pragma unroll
                for (int m = 2; m >= 0; m--) hin = cfma(a512, hin, make_float2(__uint_as_float((uint32_t)v[h][m]), __uint_as_float((uint32_t)(v[h][m] >> 32))));
                hin = cmul(pw128, hin);
                hin.x += __shfl_xor_sync(0xffffffffu, hin.x, 1); hin.y += __shfl_xor_sync(0xffffffffu, hin.y, 1);
                hin.x += __shfl_xor_sync(0xffffffffu, hin.x, 2); hin.y += __shfl_xor_sync(0xffffffffu, hin.y, 2);
                w0[h] = cfma(pw32, hin, w0[h]);
            };
            chain(0, 1, 32);
            publish(0);
            chain(1, 1, 8);
            STAMPIF(lane == 0, 30 + 2 * wg);
            chain(1, 8, 32);
            publish(1);
            gap();
            scale(0, 0, POLL_S);
            poll(0);
            scale(0, POLL_S, 16);
            carry(0);
            if (wg) mbar_wait(bar_out + 24);
            STAMPIF(lane == 0, 38 + 2 * wg);
            const uint32_t stg = sb + OFF_STG + prm.swapped * 8192 + w * 1024 + (lane & 7) * 128 + (((lane >> 3) ^ (lane & 7)) << 4);
            const uint32_t second = prm.swapped ? -8192 : 8192;
            uint32_t hold = prm.swapped >> 1, last[8];
            const uint32_t keep = c == (g >> 1) ? 0xFFFEFFFEu : 0xFFFFFFFFu, tagw = ((t2 & 1) | ((t2 & 2) << 15)) & ~keep;
#pragma unroll
            for (int h = 0; h < 2; h++) {
                float (&acc)[64] = h ? accB : accA;
                uint32_t ra[16], ia[16];
                if (h) {
                    scale(1, 0, 4);
#pragma unroll
                    for (int u = 0; u < 4; u++) asm volatile("lop3.b32 %0, %0, %1, %2, 0x80;" : "+r"(hold) : "r"(last[u]), "r"(last[4 + u]));
                    release(bar_st + 32 * wg + 8 + hold);
                    poll(1);
                    scale(1, 4, 16);
                    mbar_wait(bar_xs);
                    row_setup();
                    carry(1);
                }
                auto stage = [&](uint32_t (&r)[16], uint32_t base, int j) {
                    stsm4((base ^ ((j & 1) * 64)) + (j >> 1) * 4096, r[4 * j], r[4 * j + 1], r[4 * j + 2], r[4 * j + 3]);
                };
#pragma unroll
                for (int n = 0; n < 16; n++) {
                    const float2 y = cfma(a[h], w0[h], make_float2(acc[4 * n], acc[4 * n + 2]));
                    w0[h] = cfma(a[h], y, make_float2(acc[4 * n + 1], acc[4 * n + 3]));
                    ra[n] = pack_bf(y.x, w0[h].x);
                    ia[n] = pack_bf(y.y, w0[h].y);
                    if (!(n & 1)) { ra[n] = (ra[n] & keep) | tagw; ia[n] = (ia[n] & keep) | tagw; }
                    if (!h && (n & 3) == 3) {
                        if (n > 3) {
                            gap();
#pragma unroll
                            for (int u = n - 7; u < n - 3; u++) asm volatile("lop3.b32 %0, %0, %1, %2, 0x80;" : "+r"(hold) : "r"(ra[u]), "r"(ia[u]));
                        }
                        if (n == 15) {
#pragma unroll
                            for (int u = 0; u < 4; u++) { last[u] = ra[12 + u]; last[4 + u] = ia[12 + u]; }
                        }
                        if (n == 11) { asm volatile("" : "+r"(ra[n]), "+r"(ia[n])); gap(); release(bar_st + 32 * wg); }
                        stage(ra, stg, n >> 2); stage(ia, stg + second, n >> 2);
                        gap();
                    }
                }
                if (h) {
                    STAMPIF(lane == 0, 39 + 2 * wg);
                    mbar_wait(bar_out + 32 * wg);
                    if (prm.swapped) {
#pragma unroll
                        for (int n = 0; n < 16; n++) { const uint32_t t = ra[n]; ra[n] = ia[n]; ia[n] = t; }
                    }
                    const uint32_t st0 = stg - prm.swapped * 8192;
#pragma unroll
                    for (int j = 0; j < 4; j++) stage(ra, st0, j);
                    release(bar_st + 32 * wg + 16);
                    mbar_wait(bar_out + 32 * wg + 8);
#pragma unroll
                    for (int j = 0; j < 4; j++) stage(ia, st0 + 8192, j);
                    release(bar_st + 32 * wg + 24);
                }
                STAMPIF(lane == 0, 42 + 2 * wg + h);
            }
        }

        const uint32_t xr = 2 * (g & 3) + (g >> 2), xa = sb + (wg ? OFF_STG : OFF_W) + (16 * w + xr) * 128 + (((c >> 1) ^ xr) << 4) + (c & 1) * 8;
        auto handover = [&](uint32_t bar) {
            const uint4 z = ldsm4(sb + OFF_KEYS + 16);
            if (lane == 1) mbar_arrive(bar + z.x);
        };
        auto load_x = [&](int j0, int j1) {
#pragma unroll
            for (int j = j0; j < j1; j++)
#pragma unroll
                for (int r = 0; r < 2; r++) xv[j][r] = lds64((xa ^ (32 * (j & 3))) + (j >> 2) * ABYTES + r * 1024);
        };
        auto skip_term = [&](int j0, int j1) {
#pragma unroll
            for (int j = j0; j < j1; j++)
#pragma unroll
                for (int r = 0; r < 2; r++) {
                    xv[j][r].x = mul_bf2(xv[j][r].x, fma_bf2(gp[r], dk[j].x, om[r]));
                    xv[j][r].y = mul_bf2(xv[j][r].y, fma_bf2(gp[r], dk[j].y, om[r]));
                    asm volatile("" : "+r"(xv[j][r].x), "+r"(xv[j][r].y));
                }
        };
        auto finish = [&](float (&acc)[64], int j, bool gaps) {
#pragma unroll
            for (int r = 0; r < 2; r++) {
                const int o = 8 * j + 2 * r;
                const float gv = bf_hi(gp[r]);
                acc[o] = fmaf(gv, acc[o], bf_lo(xv[j][r].x)); acc[o + 1] = fmaf(gv, acc[o + 1], bf_hi(xv[j][r].x));
                acc[o + 4] = fmaf(gv, acc[o + 4], bf_lo(xv[j][r].y)); acc[o + 5] = fmaf(gv, acc[o + 5], bf_hi(xv[j][r].y));
                stg4_unless(op + r * 2 * D_ + 16 * j, acc[o], acc[o + 1], acc[o + 4], acc[o + 5], routed[r]);
                if (gaps) gap();
            }
        };
        auto finish_routed = [&](float (&acc)[64]) {
#pragma unroll
            for (int r = 0; r < 2; r++)
                if (routed[r]) {
#pragma unroll
                    for (int j = 0; j < 8; j++) red4(op + r * 2 * D_ + 16 * j, acc[8 * j + 2 * r], acc[8 * j + 2 * r + 1], acc[8 * j + 2 * r + 4], acc[8 * j + 2 * r + 5]);
                }
            __syncwarp();
        };
        const uint32_t xbuf = sb + w * 2048 + lane * 16;

        if (wg == 1) {
            float outB[64];
            {
                sts128(sb + OFF_XS + at * 16, __float_as_uint(facc[0]), __float_as_uint(facc[1]), __float_as_uint(facc[2]), __float_as_uint(facc[3]));
                named_bar(2, 128);
                const uint32_t pg = sb + OFF_XS + prm.up_first * 1024 + (at & 63) * 16 + (w >> 1) * 8, pu = pg + 1024 - prm.up_first * 2048;
                const uint2 g1 = lds64(pg), u1 = lds64(pu);
                uint4* hp = prm.s->hid + cta * 32 - 512 + 16 * (w & 1) + 8 * (w >> 1) + g;
                asm volatile("" : "+l"(hp));
                mbar_wait(bar_fp);
                const uint2 g2 = lds64(pg + 2048), u2 = lds64(pu + 2048);
                const float ga = rbf(__uint_as_float(g1.x) + __uint_as_float(g2.x)), gb = rbf(__uint_as_float(g1.y) + __uint_as_float(g2.y));
                uint32_t hw = mul_bf2(pack_bf(__fdividef(ga, 1.0f + __expf(-ga)), __fdividef(gb, 1.0f + __expf(-gb))),
                                      pack_bf(__uint_as_float(u1.x) + __uint_as_float(u2.x), __uint_as_float(u1.y) + __uint_as_float(u2.y)));
                if (c == 2 * (w & 1) + (w >> 1)) hw = (hw & 0xFFFEFFFEu) | (tag & 1) | ((tag & 2) << 15);
                st_cell(hp, hw, __shfl_down_sync(0xffffffffu, hw, 1), __shfl_down_sync(0xffffffffu, hw, 2), __shfl_down_sync(0xffffffffu, hw, 3), has_gu && c == 0);
            }
            STAMPIF(lane == 0, 47);
            mbar_wait(bar_xb);
            load_x(0, 8);
            release(bar_xbfree);
            skip_term(0, 8);
            STAMPIF(lane == 0, 46);
            mbar_wait(bar_order2);
            static_for<NENT - FIN>([&](auto u) {
                run_small<1, FIN + u>(outB);
                if (u == FE) { wgmma_wait<2>(); if (lane == 0) mbar_arrive(bar_fold); }
            });
            wgmma_wait<0>();
            pin64(outB);
            KSTAMP(2 * NENT - FIN);
            STAMPIF(at == 0, 50);
            LT(0);
#pragma unroll
            for (int q = 0; q < 2; q++) {
                uint4 pb[16];
                mbar_wait(bar_accb + 8 * q);
                if (q) LT(1);
#pragma unroll
                for (int v = q * HP; v < (q ? 16 : HP); v++) pb[v] = ldsm4(xbuf + sum_off(v));
#pragma unroll
                for (int v = q * HP; v < (q ? 16 : HP); v++) {
                    outB[4 * v] += __uint_as_float(pb[v].x); outB[4 * v + 1] += __uint_as_float(pb[v].y);
                    outB[4 * v + 2] += __uint_as_float(pb[v].z); outB[4 * v + 3] += __uint_as_float(pb[v].w);
                    if (v & 1) finish(outB, v >> 1, false);
                    if (v == DV) { gap(); if (lane == 0) mbar_expect_tx(bar_dn, w ? 0 : 7 * ABYTES); }
                }
            }
            finish_routed(outB);
            STAMPIF(lane == 0, 51);
            LT(2);
        } else {
            float outA[64], outB[64], gacc[4];
            ring.slot = 32 % NST;
            ring.prev = bar_dummy;
            mbar_wait(bar_order1);
            run_entries<1, 2>(ring, 32, GU0 + 32, outA, outB, gacc, true, true);
            run_entries<1, 0>(ring, GU0 + 32, GU0 + 33, outA, outB, gacc, false, false, [&]() {
                LP(2);
                pin4(gacc);
                sts128(sb + OFF_XS + 2048 + at * 16, __float_as_uint(gacc[0]), __float_as_uint(gacc[1]), __float_as_uint(gacc[2]), __float_as_uint(gacc[3]));
                __syncwarp();
                if (lane == 0) mbar_arrive(bar_fp);
            });
            mbar_wait(bar_xa);
            load_x(0, 2);
            run_entries<1, 0>(ring, GU0 + 33, GU0 + 34, outA, outB, gacc, false, false, [&]() { load_x(2, 3); });
            load_x(3, 5);
            run_entries<1, 0>(ring, GU0 + 34, GU0 + 35, outA, outB, gacc, false, false, [&]() { load_x(5, 6); });
            load_x(6, 8);
            run_entries<1, 0>(ring, GU0 + 35, GU0 + 36, outA, outB, gacc, false, false, [&]() { handover(bar_xafree); });
            skip_term(0, 3);
            run_entries<1, 0>(ring, GU0 + 36, GU0 + 37, outA, outB, gacc, false, false, [&]() { skip_term(3, 5); });
            skip_term(5, 8);
            run_entries<1, 0>(ring, GU0 + 37, FIN, outA, outB, gacc);
            auto dump = [&](int v) {
                stsm4(xbuf + sum_off(v), __float_as_uint(outB[4 * v]), __float_as_uint(outB[4 * v + 1]), __float_as_uint(outB[4 * v + 2]),
                      __float_as_uint(outB[4 * v + 3]));
            };
            static_for<NENT - FIN>([&](auto u) {
                mbar_wait(full + 8 * (FIN + u));
                run_small<0, FIN + u>(outA);
                if (u == 5 && lane == 0) mbar_arrive(bar_order2);
                wgmma_wait<1>();
                if (lane == 0) mbar_arrive(empty + 8 * (FIN + u - 1));
                if (u == 0) { pin64(outB); LP(3); }
                if (u == 2) mbar_wait(empty + 8 * FIN);
                if (u >= 2) dump(u - 2);
            });
            const uint2 sk = lds64(sb + OFF_SEL + 8 * c), fk = lds64(sb + OFF_FAC + 8 * c);
            float* y0 = prm.out + (~sk.x & 2047u) * D_ + (cta & 15) * 64 + w * 16 + g;
            float* y1 = prm.out + (~sk.y & 2047u) * D_ + (cta & 15) * 64 + w * 16 + g;
            asm volatile("" : "+l"(y0), "+l"(y1));
            handover(bar_accb);
            wgmma_wait<0>();
            pin64(outA);
            STAMPIF(at == 0, 53);
            GSTAMP(at == 0, 2);
#pragma unroll
            for (int j = 0; j < 8; j++) {
                finish(outA, j, true);
            }
            STAMPIF(lane == 0, 54);
            LT(0);
            mbar_wait(bar_fold);
#pragma unroll
            for (int v = 4; v < 16; v++) dump(v);
            handover(bar_accb + 8);
            STAMPIF(lane == 0, 55);
            finish_routed(outA);
            float yacc[4];
            const uint64_t dw = make_desc(sb), dh = (uint64_t)(((sb + OFF_XS) & 0x3FFFF) >> 4) | ((uint64_t)8 << 16) | ((uint64_t)8 << 32);
            mbar_wait(bar_zero);
            mbar_wait(bar_dn);
            STAMPIF(at == 0, 2);
            LT(1);
            wgmma_fence();
#pragma unroll
            for (int n = 0; n < 28; n++) wgmma_n8<1, 1>(yacc, dw + (dn_off(n >> 2) >> 4) + (n & 3) * 128, dh + n * 16, n > 0);
            wgmma_commit();
            wgmma_wait<0>();
            pin4(yacc);
            LT(2);
            asm volatile("red.global.add.f32 [%0], %2; red.global.add.f32 [%1], %3; red.global.add.f32 [%0 + 32], %4; red.global.add.f32 [%1 + 32], %5;"
                         ::"l"(y0), "l"(y1), "f"(yacc[0] * __uint_as_float(fk.x)), "f"(yacc[1] * __uint_as_float(fk.y)), "f"(yacc[2] * __uint_as_float(fk.x)),
                         "f"(yacc[3] * __uint_as_float(fk.y)) : "memory");
            STAMPIF(lane == 0, 3);
            LT(3);
        }
    }
}

typedef CUresult (*EncodeFn)(CUtensorMap*, CUtensorMapDataType, cuuint32_t, void*, const cuuint64_t*, const cuuint64_t*, const cuuint32_t*,
                             const cuuint32_t*, CUtensorMapInterleave, CUtensorMapSwizzle, CUtensorMapL2promotion, CUtensorMapFloatOOBfill);

bool encode(EncodeFn fn, CUtensorMap* m, const void* ptr, int rank, const cuuint64_t* dims, const cuuint64_t* strides, const cuuint32_t* box,
            CUtensorMapSwizzle sw = CU_TENSOR_MAP_SWIZZLE_128B, CUtensorMapL2promotion promo = CU_TENSOR_MAP_L2_PROMOTION_NONE) {
    const cuuint32_t es[5] = {1, 1, 1, 1, 1};
    return fn(m, CU_TENSOR_MAP_DATA_TYPE_BFLOAT16, rank, const_cast<void*>(ptr), dims, strides, box, es, CU_TENSOR_MAP_INTERLEAVE_NONE,
              sw, promo, CU_TENSOR_MAP_FLOAT_OOB_FILL_NONE) == CUDA_SUCCESS;
}

}

extern "C" void kernel_launch(void* const* d_in, const int* in_sizes, int n_in, void* d_out, int out_size) {
    (void)in_sizes; (void)n_in; (void)out_size;
    Params prm;
    prm.x = (const __nv_bfloat16*)d_in[0];
    prm.lam_re = (const __nv_bfloat16*)d_in[1];
    prm.lam_im = (const __nv_bfloat16*)d_in[2];
    prm.b_re = (const __nv_bfloat16*)d_in[3];
    prm.b_im = (const __nv_bfloat16*)d_in[4];
    prm.c_re = (const __nv_bfloat16*)d_in[5];
    prm.c_im = (const __nv_bfloat16*)d_in[6];
    prm.log_dt = (const __nv_bfloat16*)d_in[7];
    prm.dskip = (const __nv_bfloat16*)d_in[8];
    prm.w_r = (const __nv_bfloat16*)d_in[10];
    prm.gate_w = (const __nv_bfloat16*)d_in[14];
    prm.out = (float*)d_out;
    cudaGetSymbolAddress((void**)&prm.s, g_scratch);
    int dev = 0, sms = 0;
    cudaGetDevice(&dev);
    cudaDeviceGetAttribute(&sms, cudaDevAttrMultiProcessorCount, dev);
    auto kernel = sms == NGRID ? fused_kernel<true> : fused_kernel<false>;
    prm.swapped = prm.b_im < prm.b_re;

    void* fnp = nullptr;
    cudaDriverEntryPointQueryResult qr;
    cudaGetDriverEntryPoint("cuTensorMapEncodeTiled", &fnp, cudaEnableDefault, &qr);
    EncodeFn fn = (EncodeFn)fnp;
    cudaFuncSetAttribute(kernel, cudaFuncAttributeMaxDynamicSharedMemorySize, SMEM_BYTES);

    CUtensorMap mX, mB, mCre, mCim, mW, mWd, mXr, mXe;
    const cuuint64_t row = 2048;
    {
        const cuuint64_t dims[4] = {1024, 2, 4, 976}, st[3] = {row, 32 * row, 2 * row};
        const cuuint32_t box[4] = {64, 2, 4, 16};
        encode(fn, &mX, prm.x, 4, dims, st, box, CU_TENSOR_MAP_SWIZZLE_128B, PROMO);
    }
    {
        const char *lo = (const char*)(prm.swapped ? prm.b_im : prm.b_re), *hi = (const char*)(prm.swapped ? prm.b_re : prm.b_im);
        const cuuint64_t dims[5] = {1024, 8, 2, 96, 2}, st[4] = {row, (cuuint64_t)(hi - lo), 8 * row, 256 * row};
        const cuuint32_t box[5] = {64, 8, 2, 4, 2};
        encode(fn, &mB, lo, 5, dims, st, box, CU_TENSOR_MAP_SWIZZLE_128B, PROMO);
    }
    {
        const cuuint64_t dims[5] = {1024, 2, 4, 2, 64}, st[4] = {row, 4 * row, 2 * row, 16 * row};
        const cuuint32_t box[5] = {64, 2, 4, 2, 8};
        encode(fn, &mCre, prm.c_re, 5, dims, st, box);
        encode(fn, &mCim, prm.c_im, 5, dims, st, box);
    }
    {
        const char *pg = (const char*)d_in[11], *pu = (const char*)d_in[12];
        prm.up_first = pu < pg;
        const cuuint64_t dims[3] = {F_, D_, 2}, st[2] = {F_ * 2, (cuuint64_t)(pu < pg ? pg - pu : pu - pg)}, dimsd[2] = {D_, F_}, std_[1] = {row};
        const cuuint32_t box[3] = {32, 32, 2}, boxd[2] = {64, 64};
        encode(fn, &mW, pu < pg ? pu : pg, 3, dims, st, box, CU_TENSOR_MAP_SWIZZLE_64B, CU_TENSOR_MAP_L2_PROMOTION_NONE);
        encode(fn, &mWd, d_in[13], 2, dimsd, std_, boxd, CU_TENSOR_MAP_SWIZZLE_128B, CU_TENSOR_MAP_L2_PROMOTION_NONE);
    }
    {
        const cuuint64_t dims[3] = {D_ - 192, S_, 4}, st[2] = {row, 128};
        const cuuint32_t box[3] = {64, 16, 4};
        encode(fn, &mXr, prm.x, 3, dims, st, box, CU_TENSOR_MAP_SWIZZLE_128B, CU_TENSOR_MAP_L2_PROMOTION_NONE);
    }
    {
        const cuuint64_t dims[5] = {D_, 2, 2, 2, 976}, st[4] = {64 * row, row, 32 * row, 2 * row};
        const cuuint32_t box[5] = {64, 2, 2, 2, 8};
        encode(fn, &mXe, prm.x, 5, dims, st, box);
    }
    kernel<<<NGRID, 384, SMEM_BYTES, cudaStreamPerThread>>>(prm, mX, mB, mCre, mCim, mW, mWd, mXr, mXe);
}
```

```cpp
#include <cuda_runtime.h>
#include <cuda_bf16.h>
#include <cuda.h>
#include <stdint.h>

namespace {

constexpr int S_ = 2048, D_ = 1024, F_ = 3584;
constexpr int NCTA = 128, NGRID = 132;
#define XE_ 58
#define GU0_ 18
constexpr int NENT = 64, FIN = 58, XE = XE_;
constexpr int NST = 5;
constexpr int RE0 = 4;
constexpr int GU0 = GU0_;
constexpr uint32_t SLOT = 32768, ABYTES = 8192, WBYTES = 4096;
constexpr uint32_t OFF_XS = NST * SLOT;
constexpr uint32_t OFF_LIST = OFF_XS + 8192;
constexpr uint32_t OFF_W = OFF_XS + 16384;
constexpr uint32_t OFF_STG = OFF_W + 32768;
__host__ __device__ constexpr uint32_t slot_off(int i) { return i < XE ? (i % NST) * SLOT : i == XE ? OFF_W : ((i - 1) % NST) * SLOT; }
__host__ __device__ constexpr uint32_t dn_off(int u) { return u == 0 ? OFF_XS + ABYTES : u < 3 ? OFF_STG + (u - 1) * ABYTES : slot_off(FIN - 2 + u); }
__host__ __device__ constexpr uint32_t sum_off(int v) { return slot_off(FIN) + (v >> 2) * ABYTES + (v & 3) * 512; }
constexpr uint32_t OFF_CONST = OFF_STG;
constexpr uint32_t OFF_RED = OFF_STG + 4096;
constexpr uint32_t OFF_FULL = OFF_STG + 16384;
constexpr uint32_t OFF_EMPTY = OFF_FULL + 120 * 8;
constexpr uint32_t OFF_G = OFF_EMPTY + 88 * 8;
constexpr uint32_t OFF_DK = OFF_G + 256;
constexpr uint32_t OFF_KEYS = OFF_DK + 256;
constexpr uint32_t OFF_SEL = OFF_KEYS + 32;
constexpr uint32_t OFF_FAC = OFF_SEL + 32;
constexpr uint32_t OFF_EPOCH = OFF_FAC + 32;
constexpr uint32_t OFF_PROF = OFF_EPOCH + 16;
constexpr uint32_t SMEM_BYTES = OFF_PROF + 768;
static_assert(SMEM_BYTES <= 232448, "smem");

constexpr uint32_t sb = 1024;
constexpr uint32_t SPIN_LIMIT = 1u << 18;

struct Scratch {
    unsigned int cnt[2 * 32];
    unsigned long long rpack[S_ / 2];
    unsigned long long gpack[S_ / 2];
    uint4 time[NCTA];
    float2 carry[16 * 1024];
    uint4 hid[F_];
    uint4 h[8 * 4 * 256 * 64];
};
__device__ __align__(128) Scratch g_scratch;
#define LT(i) do {} while (0)
#define STAMPW(cond, w) do {} while (0)
#define LATE(i, tt) do {} while (0)
#define LANDED(i) do {} while (0)
#define GSTAMP(cond, w) do {} while (0)
#define LP(i) do {} while (0)
#define STAMPIF(cond, i) STAMPW(cond, 72 + (i))
#define STAMP(i) STAMPW(1, 72 + (i))
#define KSTAMP(i) STAMPW((threadIdx.x & 127) == 0, i)

struct Params {
    const __nv_bfloat16 *x, *b_re, *b_im;
    Scratch* s;
    int up_first;
    int swapped;
    const __nv_bfloat16 *lam_re, *lam_im, *c_re, *c_im, *log_dt, *dskip, *w_r, *gate_w;
    float* out;
};

__device__ __forceinline__ uint32_t smem_u32(const void* p) { return (uint32_t)__cvta_generic_to_shared(p); }
__device__ __forceinline__ void mbar_init(uint32_t bar, uint32_t cnt) { asm volatile("mbarrier.init.shared::cta.b64 [%0], %1;" ::"r"(bar), "r"(cnt) : "memory"); }
__device__ __forceinline__ void mbar_expect_tx(uint32_t bar, uint32_t bytes) { asm volatile("mbarrier.arrive.expect_tx.shared::cta.b64 _, [%0], %1;" ::"r"(bar), "r"(bytes) : "memory"); }
__device__ __forceinline__ void mbar_arrive(uint32_t bar) { asm volatile("mbarrier.arrive.shared::cta.b64 _, [%0];" ::"r"(bar) : "memory"); }
__device__ __forceinline__ void mbar_wait(uint32_t bar, uint32_t parity = 0) {
    asm volatile("{ .reg .pred p; .reg .u32 n;\n"
                 "mov.u32 n, 0;\n"
                 "AGAIN: mbarrier.try_wait.parity.shared::cta.b64 p, [%0], %1;\n"
                 "@p bra.uni DONE;\n"
                 "add.u32 n, n, 1;\n"
                 "setp.lt.u32 p, n, %2;\n"
                 "@p bra.uni AGAIN;\n"
                 "trap;\n"
                 "DONE: }" ::"r"(bar), "r"(parity), "n"(SPIN_LIMIT) : "memory");
}
__device__ __forceinline__ bool elect_one() {
    uint32_t pred;
    asm volatile("{ .reg .pred P; elect.sync _|P, 0xffffffff; selp.b32 %0, 1, 0, P; }" : "=r"(pred));
    return pred;
}
__device__ __forceinline__ void named_bar(int id, int n) { asm volatile("bar.sync %0, %1;" ::"r"(id), "r"(n) : "memory"); }

#define ONE "{ .reg .pred e; elect.sync _|e, 0xffffffff;\n@e "
template <int N> __device__ __forceinline__ void mbar_init_n(uint32_t bar, uint32_t cnt, uint32_t extra = 0) {
    if (elect_one()) {
#pragma unroll
        for (int i = 0; i < N; i++) mbar_init(bar + 8 * i, i == N - 1 ? cnt + extra : cnt);
        asm volatile("fence.mbarrier_init.release.cluster;" ::: "memory");
    }
    __syncwarp();
}
__device__ __forceinline__ void bulk_load(uint32_t dst, const void* src, uint32_t bytes, uint32_t bar) {
    asm volatile(ONE "cp.async.bulk.shared::cluster.global.mbarrier::complete_tx::bytes [%0], [%1], %2, [%3]; }" ::"r"(dst), "l"(src), "r"(bytes), "r"(bar) : "memory");
}
__device__ __forceinline__ void sts128(uint32_t a, uint32_t x, uint32_t y, uint32_t z, uint32_t w) {
    asm volatile("st.shared.v4.u32 [%0], {%1,%2,%3,%4};" ::"r"(a), "r"(x), "r"(y), "r"(z), "r"(w) : "memory");
}
__device__ __forceinline__ uint2 lds64(uint32_t a) {
    uint2 v;
    asm volatile("ld.shared.v2.u32 {%0,%1}, [%2];" : "=r"(v.x), "=r"(v.y) : "r"(a) : "memory");
    return v;
}
__device__ __forceinline__ uint32_t clk32() { uint32_t c; asm volatile("mov.u32 %0, %%clock;" : "=r"(c)); return c; }
__device__ __forceinline__ void gap() { asm volatile("pmevent 1;" ::: "memory"); }
__device__ __forceinline__ void pace_until(uint32_t t) { while ((int)(clk32() - t) < 0) {} }
#define SLEEP_MARGIN 200
__device__ __forceinline__ void sleep_until(uint32_t t) {
    while ((int)(clk32() + SLEEP_MARGIN - t) < 0) __nanosleep(40);
    pace_until(t);
}
__device__ __forceinline__ void tma2(uint32_t dst, const CUtensorMap* m, int c0, int c1, uint32_t bar, uint64_t pol) {
    asm volatile(ONE "cp.async.bulk.tensor.2d.shared::cluster.global.mbarrier::complete_tx::bytes.L2::cache_hint [%0], [%1, {%3, %4}], [%2], %5; }"
                 ::"r"(dst), "l"(m), "r"(bar), "r"(c0), "r"(c1), "l"(pol) : "memory");
}
__device__ __forceinline__ void tma3s(uint32_t dst, const CUtensorMap* m, int c0, int c1, uint32_t bar, uint64_t pol) {
    asm volatile(ONE "cp.async.bulk.tensor.3d.shared::cluster.global.mbarrier::complete_tx::bytes.L2::cache_hint [%0], [%1, {%3, %4, %5}], [%2], %6; }"
                 ::"r"(dst), "l"(m), "r"(bar), "r"(c0), "r"(c1), "r"(0), "l"(pol) : "memory");
}
__device__ __forceinline__ void tma3(uint32_t dst, const CUtensorMap* m, int c0, int c1, uint32_t bar) {
    asm volatile(ONE "cp.async.bulk.tensor.3d.shared::cluster.global.mbarrier::complete_tx::bytes [%0], [%1, {%3, %4, %5}], [%2]; }"
                 ::"r"(dst), "l"(m), "r"(bar), "r"(c0), "r"(c1), "r"(0) : "memory");
}
__device__ __forceinline__ void tma4(uint32_t dst, const CUtensorMap* m, int c0, int c3, uint32_t bar) {
    asm volatile(ONE "cp.async.bulk.tensor.4d.shared::cluster.global.mbarrier::complete_tx::bytes [%0], [%1, {%3, %5, %5, %4}], [%2]; }"
                 ::"r"(dst), "l"(m), "r"(bar), "r"(c0), "r"(c3), "r"(0) : "memory");
}
__device__ __forceinline__ void tma5(uint32_t dst, const CUtensorMap* m, int c0, int c4, uint32_t bar) {
    asm volatile(ONE "cp.async.bulk.tensor.5d.shared::cluster.global.mbarrier::complete_tx::bytes [%0], [%1, {%3, %5, %5, %5, %4}], [%2]; }"
                 ::"r"(dst), "l"(m), "r"(bar), "r"(c0), "r"(c4), "r"(0) : "memory");
}
__device__ __forceinline__ void tma5b(uint32_t dst, const CUtensorMap* m, int c0, int c3, uint32_t bar) {
    asm volatile(ONE "cp.async.bulk.tensor.5d.shared::cluster.global.mbarrier::complete_tx::bytes [%0], [%1, {%3, %5, %5, %4, %5}], [%2]; }"
                 ::"r"(dst), "l"(m), "r"(bar), "r"(c0), "r"(c3), "r"(0) : "memory");
}
__device__ __forceinline__ void prefetch_l2(const void* p) {
    asm volatile("cp.async.ca.shared.global.L2::256B [%0], [%1], 4;" ::"r"(sb + OFF_EPOCH + 12), "l"(p) : "memory");
}

__device__ __forceinline__ uint32_t lds32(uint32_t a) {
    uint32_t v;
    asm volatile("ld.volatile.shared.u32 %0, [%1];" : "=r"(v) : "r"(a) : "memory");
    return v;
}
__device__ __forceinline__ uint32_t uni(uint32_t v) { return __shfl_sync(0xffffffffu, v, 0); }   __device__ __forceinline__ uint32_t ld_acquire(const unsigned int* p) {
    uint32_t v;
    asm volatile("ld.acquire.gpu.global.u32 %0, [%1];" : "=r"(v) : "l"(p) : "memory");
    return v;
}
__device__ __forceinline__ void red_release(unsigned int* p) { asm volatile("red.release.gpu.global.add.u32 [%0], 1;" ::"l"(p) : "memory"); }
__device__ __forceinline__ void wait_count(const unsigned int* p, uint32_t target) {
#pragma unroll 1
    for (uint32_t it = 0; it < SPIN_LIMIT; ++it)
        if ((int)(ld_acquire(p) - target) >= 0) return;
    __trap();
}
__device__ __forceinline__ void wait_count_slow(const unsigned int* p, uint32_t target) {
#pragma unroll 1
    for (uint32_t it = 0; it < SPIN_LIMIT; ++it) {
        if ((int)(ld_acquire(p) - target) >= 0) return;
        __nanosleep(200);
    }
    __trap();
}
__device__ __forceinline__ unsigned long long ld_relaxed1(const void* p) {
    unsigned long long v;
    asm volatile("ld.relaxed.gpu.global.b64 %0, [%1];" : "=l"(v) : "l"(p) : "memory");
    return v;
}
__device__ __forceinline__ ulonglong2 ld_relaxed2(const void* p) {
    ulonglong2 v;
    asm volatile("ld.relaxed.gpu.global.v2.b64 {%0, %1}, [%2];" : "=l"(v.x), "=l"(v.y) : "l"(p) : "memory");
    return v;
}
__device__ __forceinline__ void ld_cell(uint32_t (&v)[4], const void* p, bool on = true) {
    asm volatile("{ .reg .pred p; .reg .b64 l, h; .reg .b128 t; setp.ne.u32 p, %5, 0; mov.b64 l, {%0, %1}; mov.b64 h, {%2, %3}; mov.b128 t, {l, h};\n"
                 "@p ld.relaxed.gpu.global.b128 t, [%4]; mov.b128 {l, h}, t; mov.b64 {%0, %1}, l; mov.b64 {%2, %3}, h; }"
                 : "+r"(v[0]), "+r"(v[1]), "+r"(v[2]), "+r"(v[3]) : "l"(p), "r"((uint32_t)on) : "memory");
}
__device__ __forceinline__ void st_cell(void* p, uint32_t a, uint32_t b, uint32_t c, uint32_t d, bool on) {
    asm volatile("{ .reg .pred p; .reg .b64 l, h; .reg .b128 t; setp.ne.u32 p, %5, 0; mov.b64 l, {%1, %2}; mov.b64 h, {%3, %4}; mov.b128 t, {l, h};\n"
                 "@p st.relaxed.gpu.global.b128 [%0], t; }" ::"l"(p), "r"(a), "r"(b), "r"(c), "r"(d), "r"((uint32_t)on) : "memory");
}

__device__ __forceinline__ uint64_t make_desc(uint32_t addr, uint32_t sbo = 1024) {
    return (uint64_t)((addr & 0x3FFFF) >> 4) | ((uint64_t)1 << 16) | ((uint64_t)(sbo >> 4) << 32) | ((uint64_t)1 << 62);
}
__device__ __forceinline__ void wgmma_fence() { asm volatile("wgmma.fence.sync.aligned;" ::: "memory"); }
__device__ __forceinline__ void wgmma_commit() { asm volatile("wgmma.commit_group.sync.aligned;" ::: "memory"); }
template <int N> __device__ __forceinline__ void wgmma_wait() { asm volatile("wgmma.wait_group.sync.aligned %0;" ::"n"(N) : "memory"); }

#define R8(d, i) "+f"(d[i]), "+f"(d[i + 1]), "+f"(d[i + 2]), "+f"(d[i + 3]), "+f"(d[i + 4]), "+f"(d[i + 5]), "+f"(d[i + 6]), "+f"(d[i + 7])
#define R64(d) R8(d, 0), R8(d, 8), R8(d, 16), R8(d, 24), R8(d, 32), R8(d, 40), R8(d, 48), R8(d, 56)
template <int TA>
__device__ __forceinline__ void wgmma_n128(float (&d)[64], uint64_t da, uint64_t db, int scale_d = 1) {
    asm volatile("{ .reg .pred p; setp.ne.b32 p, %66, 0;\n"
                 "wgmma.mma_async.sync.aligned.m64n128k16.f32.bf16.bf16 "
                 "{%0,%1,%2,%3,%4,%5,%6,%7,%8,%9,%10,%11,%12,%13,%14,%15,%16,%17,%18,%19,%20,%21,%22,%23,%24,%25,%26,%27,%28,%29,%30,%31,"
                 "%32,%33,%34,%35,%36,%37,%38,%39,%40,%41,%42,%43,%44,%45,%46,%47,%48,%49,%50,%51,%52,%53,%54,%55,%56,%57,%58,%59,%60,%61,%62,%63}, "
                 "%64, %65, p, 1, 1, %67, 0; }"
                 : R64(d)
                 : "l"(da), "l"(db), "r"(scale_d), "n"(TA));
}
__device__ __forceinline__ void pin4(float (&d)[4]) { asm volatile("" : "+f"(d[0]), "+f"(d[1]), "+f"(d[2]), "+f"(d[3])::"memory"); }
__device__ __forceinline__ void pin64(float (&d)[64]) { asm volatile("" : R64(d)::"memory"); }

template <int TA, int TB = 0>
__device__ __forceinline__ void wgmma_n8(float (&d)[4], uint64_t da, uint64_t db, int scale_d = 1) {
    asm volatile("{ .reg .pred p; setp.ne.b32 p, %7, 0;\n"
                 "wgmma.mma_async.sync.aligned.m64n8k16.f32.bf16.bf16 {%0,%1,%2,%3}, %4, %5, p, 1, 1, %6, %8; }"
                 : "+f"(d[0]), "+f"(d[1]), "+f"(d[2]), "+f"(d[3])
                 : "l"(da), "l"(db), "n"(TA), "r"(scale_d), "n"(TB));
}

__device__ __forceinline__ float bf_lo(uint32_t u) { return __uint_as_float(u << 16); }
__device__ __forceinline__ float bf_hi(uint32_t u) { return __uint_as_float(u & 0xFFFF0000u); }
__device__ __forceinline__ float rbf(float v) { return __bfloat162float(__float2bfloat16_rn(v)); }
__device__ __forceinline__ uint32_t pack_bf(float lo, float hi) {
    uint32_t r;
    asm("cvt.rn.bf16x2.f32 %0, %1, %2;" : "=r"(r) : "f"(hi), "f"(lo));
    return r;
}
__device__ __forceinline__ uint32_t mul_bf2(uint32_t a, uint32_t b) {
    __nv_bfloat162 r = __hmul2(*reinterpret_cast<__nv_bfloat162*>(&a), *reinterpret_cast<__nv_bfloat162*>(&b));
    return *reinterpret_cast<uint32_t*>(&r);
}
__device__ __forceinline__ uint32_t fma_bf2(uint32_t a, uint32_t b, uint32_t c) {
    uint32_t r;
    asm("fma.rn.bf16x2 %0, %1, %2, %3;" : "=r"(r) : "r"(a), "r"(b), "r"(c));
    return r;
}
__device__ __forceinline__ float2 cmul(float2 a, float2 b) { return make_float2(a.x * b.x - a.y * b.y, a.x * b.y + a.y * b.x); }
__device__ __forceinline__ float2 cfma(float2 a, float2 b, float2 c) {
    return make_float2(fmaf(a.x, b.x, fmaf(-a.y, b.y, c.x)), fmaf(a.x, b.y, fmaf(a.y, b.x, c.y)));
}
__device__ __forceinline__ float sigmoidf_(float v) { return __fdividef(1.0f, 1.0f + expf(-v)); }

__device__ __forceinline__ void bulk_prefetch(const void* src, uint32_t bytes) {
    asm volatile(ONE "cp.async.bulk.prefetch.L2.global [%0], %1; }" ::"l"(src), "r"(bytes) : "memory");
}
__device__ __forceinline__ void bulk_store(void* dst, uint32_t src, uint32_t bytes) {
    asm volatile(ONE "cp.async.bulk.global.shared::cta.bulk_group [%0], [%1], %2; }" ::"l"(dst), "r"(src), "r"(bytes) : "memory");
}
__device__ __forceinline__ void stsm4(uint32_t a, uint32_t x, uint32_t y, uint32_t z, uint32_t w) {
    asm volatile("stmatrix.sync.aligned.m8n8.x4.shared.b16 [%0], {%1,%2,%3,%4};" ::"r"(a), "r"(x), "r"(y), "r"(z), "r"(w) : "memory");
}
__device__ __forceinline__ uint4 ldsm4(uint32_t a) {
    uint4 v;
    asm volatile("ldmatrix.sync.aligned.m8n8.x4.shared.b16 {%0,%1,%2,%3}, [%4];" : "=r"(v.x), "=r"(v.y), "=r"(v.z), "=r"(v.w) : "r"(a) : "memory");
    return v;
}
__device__ __forceinline__ void stg4_unless(float* p, float a, float b, float c, float d, uint32_t skip) {
    asm volatile("{ .reg .pred p; setp.eq.u32 p, %5, 0; @p st.global.v4.f32 [%0], {%1,%2,%3,%4}; }" ::"l"(p), "f"(a), "f"(b), "f"(c), "f"(d), "r"(skip) : "memory");
}
__device__ __forceinline__ void red4(float* p, float a, float b, float c, float d) {
    asm volatile("red.global.add.v4.f32 [%0], {%1,%2,%3,%4};" ::"l"(p), "f"(a), "f"(b), "f"(c), "f"(d) : "memory");
}

#define TT0 2900
#define PER 510
#define PCUT 60
#define PFIN 360
#define PF0 1500
#define PFX_PACE 400
#define PF1 700
#define T2 300
#define P2 520
#define G0 450
#define R0 1900
#define R_PACE 250
#define W_SHIFT 250
#define PROMO CU_TENSOR_MAP_L2_PROMOTION_L2_256B
#define POLL_S 0
#define ST_TOL 100
#define ST_SHIFT 300
#define CLK_NS 420
#define MARGIN 60
#define BP1 12
#define DV 15
#define HOLD 450
#define RD 1500
#define FE 5
#define HP 4
#define AE 6
#define AG0 900
#define AB 17
#define HGE 39
constexpr uint32_t duration(int i) { return PER + (i >= RE0 && i < RE0 + 4 ? 72 : 0) + (i >= GU0 && i < GU0 + 32 ? 36 : 0); }
constexpr uint32_t cmax(uint32_t a, uint32_t b) { return a > b ? a : b; }
constexpr uint32_t issue_time(int i) {
    return i <= NST ? TT0 : i < XE ? issue_time(i - 1) + duration(i - NST) - (i >= XE - 3 && i > GU0 + 36 ? PCUT : 0) : issue_time(XE - 1) + cmax((i - XE + 1) * PFIN, (i - XE) * 512);
}
template <int I> struct Sched { static constexpr uint32_t t = issue_time(I); };
template <int LO, int HI, class F>
__device__ __forceinline__ void for_entries(uint32_t base, F body) {
    constexpr uint32_t per = Sched<LO + 1>::t - Sched<LO>::t;
    static_assert(Sched<HI - 1>::t - Sched<LO>::t == (HI - 1 - LO) * per, "period");
    uint32_t tt = base + Sched<LO>::t;
#pragma unroll 1
    for (int i = LO; i < HI; i++) {
        body(i, tt);
        tt += per;
    }
}

struct Ring { uint32_t prev; int slot; };
struct NoHook { __device__ void operator()() const {} };
template <int TA, int SM, class H = NoHook>
__device__ __forceinline__ void run_entries(Ring& r, int lo, int hi, float (&accA)[64], float (&accB)[64], float (&small)[4],
                                            bool fresh = false, bool sfresh = false, H released = H()) {
    const uint64_t d0 = make_desc(sb);
    const bool leader = (threadIdx.x & 31) == 0;
#pragma unroll 1
    for (int i = lo; i < hi; i++) {
        const uint32_t bar = sb + OFF_FULL + 8 * i;
        const uint64_t da = d0 + (uint64_t)(r.slot * (SLOT >> 4));
        const int n = i - (SM == 1 ? RE0 : GU0);
        const uint64_t dw = SM == 1 ? d0 + (uint64_t)((OFF_W >> 4) + n * 512)
                                    : (((uint64_t)2 << 62) | ((uint64_t)32 << 32) | (128u << 16) | ((sb + OFF_W) >> 4)) + (uint64_t)((n & 7) * 256);
        const uint64_t dt8 = d0 + (uint64_t)((OFF_XS >> 4) + (SM == 1 ? n * 64 : (n >> 1) * 64 + (n & 1) * 4));
        r.slot = r.slot == NST - 1 ? 0 : r.slot + 1;
        mbar_wait(bar);
        KSTAMP(i);
        wgmma_fence();
#pragma unroll
        for (int kk = 0; kk < 4; kk++) {
            wgmma_n128<TA>(accA, da + kk * (TA ? 128 : 2), da + 1024 + kk * 2, kk > 0 || !fresh);
            if (SM && kk == 3) {
#pragma unroll
                for (int u = 0; u < (SM == 1 ? 4 : 2); u++) wgmma_n8<SM - 1 + !SM>(small, dw + u * (SM == 1 ? 2 : 64), dt8 + u * 2, u > 0 || !sfresh);
            }
            wgmma_n128<TA>(accB, da + 512 + kk * (TA ? 128 : 2), da + 1024 + kk * 2, kk > 0 || !fresh);
            if (kk == 1) {
                wgmma_commit();
                wgmma_wait<1>();
                if (leader) mbar_arrive(r.prev);
                released();
            }
        }
        wgmma_commit();
        r.prev = bar + (OFF_EMPTY - OFF_FULL);
        fresh = sfresh = false;
    }
}
template <int HALF, int I>
__device__ __forceinline__ void run_small(float (&acc)[64]) {
    const uint64_t da = make_desc(sb) + (slot_off(I) >> 4);
    KSTAMP(I + HALF * (NENT - FIN));
    wgmma_fence();
#pragma unroll
    for (int kk = 0; kk < 4; kk++) wgmma_n128<1>(acc, da + HALF * 512 + kk * 128, da + 1024 + kk * 2, kk > 0 || !(HALF && I == FIN));
    wgmma_commit();
}
template <int V> struct Int { __host__ __device__ constexpr operator int() const { return V; } };
template <int N, class F> __device__ __forceinline__ void static_for(F f) {
    if constexpr (N > 0) { static_for<N - 1>(f); f(Int<N - 1>()); }
}

template <bool BY_SMID>
__global__ void __launch_bounds__(384, 1)
fused_kernel(const __grid_constant__ Params prm, const __grid_constant__ CUtensorMap mX, const __grid_constant__ CUtensorMap mB, const __grid_constant__ CUtensorMap mCre,
             const __grid_constant__ CUtensorMap mCim, const __grid_constant__ CUtensorMap mW,
             const __grid_constant__ CUtensorMap mWd, const __grid_constant__ CUtensorMap mXr, const __grid_constant__ CUtensorMap mXe) {
    extern __shared__ __align__(1024) uint8_t smem[];
    const uint32_t cstart = clk32();
    const int tid = threadIdx.x, lane = tid & 31;
    uint32_t id = blockIdx.x;
    if (BY_SMID) asm volatile("mov.u32 %0, %%smid;" : "=r"(id));
    {
        const uint32_t o = (tid * 2056) & 0x7880, b = (id & 127) * 8192;
        asm volatile("{ .reg .pred p, q; setp.lt.u32 p, %3, 32; setp.eq.u32 q, %4, 0;\n"
                     "@q prefetch.global.L2 [%1]; @p prefetch.global.L2 [%0]; @q prefetch.global.L2 [%2]; }"
                     ::"l"((const char*)prm.x + (b * 4 + o)), "l"((const char*)prm.b_re + (b + o)), "l"((const char*)prm.b_im + (b + o)), "r"(tid), "r"(tid & ~19) : "memory");
    }
    const int warp = __shfl_sync(0xffffffffu, tid >> 5, 0);
    gap();
    int cta;
    asm("{ .reg .pred p; .reg .u32 a, b, u, q;\n"
        "and.b32 a, %1, 14; shl.b32 a, a, 3; shr.u32 b, %1, 3; and.b32 b, b, 6; add.u32 a, a, b;\n"
        "and.b32 u, %1, 62; mul.lo.u32 q, u, 37; shr.u32 q, q, 9; shl.b32 u, u, 3; mad.lo.u32 u, q, -110, u; add.u32 u, u, 24;\n"
        "setp.lt.u32 p, %1, 64; selp.u32 a, a, u, p; lop3.b32 a, a, %1, 1, 0xF8;\n"
        "setp.lt.u32 p, %1, 124; selp.u32 b, 8, -116, p; add.u32 b, b, %1; setp.lt.u32 p, %1, 120; selp.u32 %0, a, b, p; }" : "=r"(cta) : "r"(id));
    const int chunk = (cta >> 5) * 4 + ((cta >> 2) & 3);
    const int dt = ((cta >> 4) & 1) * 4 + (cta & 3);
    if ((warp | (cta & NCTA)) == 5) {
        mbar_init_n<2>(sb + OFF_FULL, 1);
        tma5b(sb, &mB, 0, dt * 4, sb + OFF_FULL);
        gap();
        tma4(sb + 2 * ABYTES, &mX, 0, chunk * 64, sb + OFF_FULL);
        tma5b(sb + SLOT, &mB, 64, dt * 4, sb + OFF_FULL + 8);
        tma4(sb + SLOT + 2 * ABYTES, &mX, 64, chunk * 64, sb + OFF_FULL + 8);
    }
    else pace_until(cstart + HOLD);
    if (cta >= NCTA) {
        if (smem_u32(smem) != sb) __trap();
        if (tid == 0) wait_count_slow(&prm.s->cnt[0], (atomicAdd(&prm.s->cnt[0], 1u) / NGRID + 1) * NGRID);
        return;
    }
    const bool has_gu = cta >= 16;
    constexpr uint32_t full = sb + OFF_FULL, empty = sb + OFF_EMPTY;
    constexpr uint32_t raw = full + 8 * 32;
    constexpr uint32_t bar_hraw = full + 8 * 97, bar_xs = full + 8 * 98, bar_xb = full + 8 * 100, bar_xa = full + 8 * 101,
        bar_retry = full + 8 * 102, bar_out = full + 8 * 104;
    constexpr uint32_t bar_base = empty - 64, bar_init3 = empty - 56, bar_rdone = empty - 48, bar_order0 = empty - 40, bar_init2 = empty - 32,
        bar_vec = empty - 24, bar_epoch = empty - 16, bar_dummy = empty - 8, bar_xs0 = empty + 8 * 69,
        bar_zero = empty + 8 * 70, bar_xafree = empty + 8 * 71, bar_order2 = empty + 8 * 72, bar_dn = empty + 8 * 73, bar_fp = empty + 8 * 74,
        bar_accb = empty + 8 * 76, bar_xbfree = empty + 8 * 78, bar_fold = empty + 8 * 79, bar_st = empty + 8 * 80,
        bar_order1 = empty + 8 * 67, bar_cand = empty + 8 * 68;

    if (warp == 5) {
        STAMP(31);
        if (lane < 2) mbar_expect_tx(full + 8 * lane, SLOT);
        __syncwarp();
        named_bar(0, 256);
#pragma unroll 1
        for (int i = 2; i < NST; i++) {
            pace_until(cstart + T2 + i * P2);
            tma5b(sb + i * SLOT, &mB, i * 64, dt * 4, full + 8 * i);
            tma4(sb + i * SLOT + 2 * ABYTES, &mX, i * 64, chunk * 64, full + 8 * i);
            STAMPIF(i == 4, 1);
        }
    } else if (warp == 4) {
        mbar_init_n<12>(bar_init2, 4);
        asm volatile("bar.arrive 0, 256;" ::: "memory");
        mbar_init_n<4>(bar_base, 4);
        mbar_init_n<8>(empty + 64, 4);
        *reinterpret_cast<uint2*>(smem + OFF_KEYS + 16) = make_uint2(0, 0);
        asm volatile("bar.arrive 1, 64;" ::: "memory");
        asm volatile("bar.arrive 5, 96;" ::: "memory");
        asm volatile("bar.arrive 6, 96;" ::: "memory");
        mbar_init_n<32>(full + 256, 3);
        if (lane < 2) mbar_arrive(bar_init2);
    } else if ((warp >> 1) == 3) {
        if (warp == 6) {
            mbar_init_n<8>(full + 16, 1);
            if (lane >= 2 && lane < 10) mbar_expect_tx(full + 8 * lane, lane >= RE0 && lane < RE0 + 4 ? SLOT + ABYTES : SLOT);
            __syncwarp();
            asm volatile("bar.arrive 0, 256;" ::: "memory");
        }
        const char* pf0 = (warp & 1) ? (const char*)((cta & 64) ? prm.b_im : prm.b_re) + (cta & 63) * 16384 : (const char*)prm.x + cta * 32768;
        pace_until(cstart + PF1);
        asm volatile("prefetch.global.L2 [%0];" ::"l"(pf0 + (lane & (30 >> (warp & 1) & 30)) * 1024 + (lane & 1) * 128 + 256));
        const int i0 = warp == 6 ? 10 : 21;
        mbar_init_n<11>(full + 8 * i0, 1);
        if (lane >= i0 && lane < i0 + 11) mbar_expect_tx(full + 8 * lane, lane >= GU0 && has_gu ? SLOT + WBYTES : SLOT);
        mbar_init_n<24>(full + 512 + 192 * (warp & 1), 1);
        named_bar(5, 96);
        if (lane == 0) mbar_arrive(bar_init2);
        STAMP(21);
    }
    __syncwarp();

    if (warp >= 8) {
        asm volatile("setmaxnreg.dec.sync.aligned.u32 72;");
        const uint32_t c0 = cstart;
        uint64_t stream;
        asm volatile("createpolicy.fractional.L2::evict_first.b64 %0, 1.0;" : "=l"(stream));
        const int dc = (cta & 15) * 64, dr = (cta >> 4) * 448;
        auto gutile = [&](int i) {
            const int n = i + 3 - GU0;
            if (has_gu) tma3s(sb + OFF_W + (n & 7) * WBYTES, &mW, cta * 32 - 512, n * 32, full + 8 * (i + 3), stream);
        };
        if (warp == 8) {
            named_bar(0, 256);
            sleep_until(c0 + RD);
            asm volatile("prefetch.tensormap [%0];" ::"l"(&mXr));
#pragma unroll 1
            for (int u = 0; u < 2; u++) {
                sleep_until(c0 + R0 + u * R_PACE);
                tma3(sb + OFF_W + u * ABYTES, &mXr, u * 256, cta * 16, full + 8 * (RE0 + u));
            }
            uint32_t dst = sb;
            auto gemm1 = [&](int i, uint32_t tt) {
                mbar_wait(empty + 8 * (i - NST));
                LATE(i, tt);
                pace_until(tt);
                tma5b(dst, &mB, (i & 15) * 64, (i >> 4) * 64 + dt * 4, full + 8 * i);
                tma4(dst + 2 * ABYTES, &mX, (i & 15) * 64, chunk * 64, full + 8 * i);
                dst = dst == sb + (NST - 1) * SLOT ? sb : dst + SLOT;
            };
            mbar_wait(bar_init2);
            uint32_t tt = c0 + TT0;
#pragma unroll 1
            for (int i = NST; i < AB; i++) {
                gemm1(i, tt);
                if (i < 7) tma3(sb + OFF_W + (i - 3) * ABYTES, &mXr, (i - 3) * 256, cta * 16, full + 8 * (i + 1));
                tt += (i & ~3) == RE0 + 4 ? PER + 72 : PER;
            }
            mbar_wait(bar_base);
            const uint32_t base = uni(lds32(sb + OFF_EPOCH + 8));
            tt = base + Sched<AB>::t;
#pragma unroll 1
            for (int i = AB; i < 32; i++) {
                gemm1(i, tt);
                tt += i >= GU0 + 4 ? PER + 36 : PER;
            }
            const char* hsrc = reinterpret_cast<const char*>(prm.s->h) + (size_t)chunk * 524288;
            auto gemm2 = [&](int i, uint32_t d, int freed, uint32_t tt) {
                mbar_wait(empty + 8 * freed);
                LATE(i, tt);
                pace_until(tt);
                bulk_load(d, hsrc, 2 * ABYTES, raw + 8 * i);
                tma5(d + 2 * ABYTES, (i & 4) ? &mCim : &mCre, ((i & 3) + ((i >> 1) & 12)) * 64, dt * 8, full + 8 * i);
                hsrc += 2 * ABYTES;
            };
            for_entries<32, GU0 + 29>(base, [&](int i, uint32_t tt) {
                gemm2(i, dst, i - NST, tt);
                gutile(i);
                dst = dst == sb + (NST - 1) * SLOT ? sb : dst + SLOT;
            });
            for_entries<GU0 + 29, GU0 + 37>(base, [&](int i, uint32_t tt) {
                gemm2(i, dst, i - NST, tt);
                const int n = i - GU0 - 29;
                if ((n & 5) == 1) tma5(sb + OFF_W + (n & 2) * (ABYTES / 2), &mXe, dt * 128 + (n & 2) * 32, chunk * 64, bar_xa);
                else if (n < 6) asm volatile(ONE "cp.async.bulk.prefetch.tensor.2d.L2.global [%0, {%1, %2}]; }" ::"l"(&mWd), "r"(dc), "r"(dr + 64 * (n < 4 ? 3 + n / 2 : n + 1)) : "memory");
                dst = dst == sb + (NST - 1) * SLOT ? sb : dst + SLOT;
            });
            static_for<NENT - GU0 - 37>([&](auto u) {
                constexpr int i = GU0 + 37 + u;
                if (i == 60) mbar_wait(bar_out + 56);
                gemm2(i, sb + slot_off(i), i < XE ? i - NST : i == XE ? 71   : i - NST - 1, base + Sched<i>::t);
            });
            STAMP(4);
        } else if (warp == 9) {
#pragma unroll
            for (int u = 0; u < 8; u++) {
                const int row = (u >> 2) * 4 + (lane >> 3);
                asm volatile("cp.async.cg.shared.global [%0], [%1], 16;" ::"r"(sb + OFF_XS + (u & 3) * 1024 + row * 128 + (((lane & 7) ^ row) << 4)),
                             "l"((const char*)(u < 4 ? prm.w_r : prm.gate_w) + (u & 3) * 512 + lane * 16) : "memory");
            }
            uint32_t ticket = 0;
            if (lane == 0) ticket = atomicAdd(&prm.s->cnt[0], 1u);
            named_bar(1, 64);
            if (lane == 0) *reinterpret_cast<volatile uint32_t*>(smem + OFF_EPOCH) = ticket / NGRID;
            __syncwarp();
            if (lane < 4) mbar_arrive(bar_epoch);
            asm volatile("cp.async.wait_all;" ::: "memory");
            asm volatile("fence.proxy.async.shared::cta;" ::: "memory");
            __syncwarp();
            if (lane < 4) mbar_arrive(bar_vec);
            STAMP(18);
#pragma unroll 1
            for (int i = 4; i < 22; i++) mbar_init_n<4>(empty + 32 * i, 4, i >= 6 && i < 13);
            if (lane < 2) mbar_arrive(bar_init3);
            STAMP(19);
            mbar_wait(bar_cand);
            {
                const uint32_t* list = reinterpret_cast<const uint32_t*>(smem + OFF_LIST);
                const int n = (int)lds32(sb + OFF_KEYS + 16);
#pragma unroll 1
                for (int i0 = 0; i0 < n; i0 += 32) {
                    const uint32_t k = list[i0 + lane];
                    int rank = 0;
#pragma unroll 2
                    for (int o = 0; o < n; o += 4) {
                        const uint4 l4 = *reinterpret_cast<const uint4*>(list + o);
                        rank += (l4.x > k) + (l4.y > k) + (l4.z > k) + (l4.w > k);
                    }
                    if (rank < 8) reinterpret_cast<uint32_t*>(smem + OFF_SEL)[rank] = k;
                }
                __syncwarp();
                STAMP(6);
                const uint32_t key = lds32(sb + OFF_SEL + 4 * (lane & 7)), tok = ~key & 2047u, tag = lds32(sb + OFF_EPOCH) + 1;
                const uint32_t ta = __shfl_sync(0xffffffffu, tok, lane >> 3), tb = __shfl_sync(0xffffffffu, tok, 4 + (lane >> 3));
                const uint32_t da = sb + OFF_XS + (lane >> 3) * 128 + (((lane & 7) ^ (lane >> 3)) << 4), db = (da ^ 64) + 512;
                const char *sa = (const char*)prm.x + ta * 2048 + (lane & 7) * 16, *sc = (const char*)prm.x + tb * 2048 + (lane & 7) * 16;
#pragma unroll
                for (int u = 0; u < 16; u++) {
                    asm volatile("cp.async.cg.shared.global [%0], [%1], 16;" ::"r"(da + u * 1024), "l"(sa + u * 128) : "memory");
                    asm volatile("cp.async.cg.shared.global [%0], [%1], 16;" ::"r"(db + u * 1024), "l"(sc + u * 128) : "memory");
                    if (u == 3) {
                        asm volatile("cp.async.wait_all;" ::: "memory");
                        asm volatile("fence.proxy.async.shared::cta;" ::: "memory");
                        __syncwarp();
                        if (lane < 4) mbar_arrive(bar_xs0);
                        STAMP(17);
                    }
                }
                if ((tok >> 7) == (uint32_t)chunk) {
                    float4* zp = reinterpret_cast<float4*>(prm.out + tok * D_ + dt * 128) + (lane >> 3) * 2;
#pragma unroll
                    for (int u = 0; u < 8; u++) zp[(u >> 1) * 8 + (u & 1)] = make_float4(0.f, 0.f, 0.f, 0.f);
                }
                uint32_t it = 0;
                unsigned long long u;
                do {
                    u = ld_relaxed1(&prm.s->gpack[tok >> 1]);
                    if (++it > SPIN_LIMIT) __trap();
                } while (!__all_sync(0xffffffffu, (uint32_t)(u >> 32) == tag));
                const uint32_t kb = key >> 16;
                const float r = bf_lo((kb & 0x8000u) ? (kb & 0x7FFFu) : (~kb & 0xFFFFu)), gv = (tok & 1) ? bf_hi((uint32_t)u) : bf_lo((uint32_t)u);
                reinterpret_cast<float*>(smem + OFF_FAC)[lane & 7] = rbf(1.0f - gv) * rbf(sigmoidf_(r));
                asm volatile("cp.async.wait_all;" ::: "memory");
                asm volatile("fence.proxy.async.shared::cta;" ::: "memory");
                __syncwarp();
                if (lane == 0) mbar_arrive(bar_xs);
                STAMP(7);
            }
            char* hd = reinterpret_cast<char*>(prm.s->h) + (size_t)chunk * 524288 + (dt >> 1) * 16384 + (dt & 1) * 4096;
            mbar_wait(bar_base);
            const uint32_t cb = uni(lds32(sb + OFF_EPOCH + 8)) + ST_SHIFT;
            uint32_t tt = cb + Sched<GU0 + 4>::t;
#pragma unroll 1
            for (int np = 0; np < 16; np++) {
                if (!(np & (np & 4 ? 1 : 2))) mbar_wait(bar_st + 4 * (np & 12) + ((np & 3) ? 8 : 0));
                const uint32_t now = clk32() - ST_TOL;
#pragma unroll 1
                while ((int)(tt - now) < 0) tt += PER + 36;
                const uint32_t src = sb + OFF_STG + (np & 3) * 4096;
                pace_until(tt);
                bulk_store(hd, src, 4096);
                asm volatile("cp.async.bulk.commit_group;" ::: "memory");
                if (np & 2) {
                    if (np & 1) asm volatile("cp.async.bulk.wait_group.read 0;" ::: "memory");
                    else asm volatile("cp.async.bulk.wait_group.read 1;" ::: "memory");
                    __syncwarp();
                    const uint32_t u8 = 4 * (np & 12) + 8 * (np & 1);
                    if (lane < 2) mbar_arrive(lane ? (np < 15 ? empty + 8 * 27 + 4 * u8 : bar_dummy) : bar_out + u8);
                }
                STAMPIF(np & 2, 8 + ((np >> 1) & 6) + (np & 1));
                hd += (np & 1) ? 65536 - 8192 : 8192;
                tt += PER + 36;
            }
#pragma unroll 1
            for (int u = 0; u < 2; u++) {
                pace_until(tt);
                tma5(sb + OFF_STG + u * ABYTES, &mXe, dt * 128 + u * 64, chunk * 64 + 8, bar_xb);
                tt += PER + 36;
            }
            wait_count(&prm.s->cnt[32], (lds32(sb + OFF_EPOCH) + 1) * NCTA);
            auto load_hid = [&]() {
                if (lane == 0) mbar_expect_tx(bar_hraw, 7168);
                bulk_load(sb + OFF_XS, prm.s->hid + dr, 7168, bar_hraw);
            };
            static_for<7>([&](auto u) {
                if (u != 2) mbar_wait(u == 1 ? bar_xbfree : empty + 8 * (u == 0 ? GU0 + 31 : FIN - 2 + u));
                if (u < 3) sleep_until(cb + Sched<GU0 + HGE - 2 + u>::t);
                if (u == 2) load_hid();
                tma2(sb + dn_off(u), &mWd, dc, dr + u * 64, bar_dn, stream);
                if (u == 2) {
                    const uint32_t t2 = lds32(sb + OFF_EPOCH) + 1, tagw = (t2 & 1) | ((t2 & 2) << 15);
#pragma unroll 1
                    for (uint32_t it = 0;; it++) {
                        mbar_wait(bar_hraw, it & 1);
                        uint32_t bad = 0;
#pragma unroll
                        for (int i = 0; i < 14; i++) bad |= lds32(sb + OFF_XS + i * 512 + lane * 16 + (lane >> 3) * 4) ^ tagw;
                        if (__all_sync(0xffffffffu, (bad & 0x00010001u) == 0)) break;
                        if (it > SPIN_LIMIT) __trap();
                        load_hid();
                    }
                    if (lane < 4) mbar_arrive(bar_zero);
                    STAMP(48);
                }
            });
            STAMP(27);
        } else {
            named_bar(6, 96);
            if (warp == 10) {
                const char* pb = (const char*)((cta & 64) ? prm.b_im : prm.b_re) + (cta & 63) * 16384;
                const char* pf = (lane < 16 ? (const char*)prm.x + cta * 32768 : pb) + (lane & 15) * 2048 + 512;
#pragma unroll 1
                for (int k = 0; k < 11; k++) {
                    sleep_until(c0 + PF0 + k * PFX_PACE);
                    if (lane < 16 ? k < 6 : lane < 24 && !(k & 1)) prefetch_l2(pf + k * (lane < 16 ? 256 : 128));
                }
#pragma unroll 1
                for (int k = 0; k < 12; k++) {
                    sleep_until(c0 + Sched<12>::t + ST_SHIFT + (k + BP1 - 12) * PER);
                    bulk_prefetch((k < 4 ? pb + 1048576 : (const char*)(k < 8 ? prm.c_re : prm.c_im) + cta * 16384) + (k & 3) * 4096, 4096);
                    if (k == 4) { mbar_wait(bar_init2); mbar_wait(bar_init3); }
                    if (k >= 4 && lane < 8) mbar_expect_tx(full + 8 * (8 * k + lane), 8 * k + lane < GU0 + 32 && has_gu ? 2 * ABYTES + WBYTES : 2 * ABYTES);
                }
                asm volatile("prefetch.tensormap [%0];" ::"l"(&mCre));
                asm volatile("prefetch.tensormap [%0];" ::"l"(&mCim));
                asm volatile("prefetch.tensormap [%0];" ::"l"(&mWd));
                asm volatile("prefetch.tensormap [%0];" ::"l"(&mXe));
                if (lane < 2) mbar_expect_tx(bar_xb + 8 * lane, 2 * ABYTES);
                mbar_wait(bar_xs);
                mbar_wait(bar_st);
                if (lane == 0) red_release(&prm.s->cnt[32]);
                __syncwarp();
                STAMP(22);
            } else {
                mbar_wait(bar_epoch);
                const uint32_t tag = lds32(sb + OFF_EPOCH) + 1;
                st_cell(prm.s->time + cta, 0, 0, 0, 0, lane == 0);
                asm volatile("prefetch.tensormap [%0];" ::"l"(&mW));
                mbar_wait(empty + 8 * AE);
                uint32_t gown, tm[4][4] = {}, it = 0;
                asm volatile("mov.u32 %0, %%globaltimer_lo;" : "=r"(gown));
                const uint32_t town = clk32();
                st_cell(prm.s->time + cta, tag, town, gown, 0, lane == 0);
                sleep_until(town + AG0);
                do {
#pragma unroll
                    for (int m = 0; m < 4; m++) ld_cell(tm[m], prm.s->time + ((cta & 96) ^ (32 * m)) + lane);
                    if (++it > SPIN_LIMIT) __trap();
                } while (!__all_sync(0xffffffffu, tm[0][0] == tag && tm[1][0] == tag && tm[2][0] == tag && tm[3][0] == tag));
                const int last = __reduce_max_sync(0xffffffffu, max(max((int)(tm[0][2] - gown), (int)(tm[1][2] - gown)), max((int)(tm[2][2] - gown), (int)(tm[3][2] - gown))));
                const uint32_t cand = tm[0][1] + ((min((int)(gown + last - tm[0][2]), 4000) * CLK_NS) >> 8);
                const uint32_t b0 = __shfl_sync(0xffffffffu, cand, cta & 16), b1 = __shfl_sync(0xffffffffu, cand, cta & 30);
                const uint32_t b2 = __shfl_sync(0xffffffffu, cand, cta & 31);
                const uint32_t base = (b0 - b2 + 400u < 800u ? b0 : b1 - b2 + 400u < 800u ? b1 : b2) + MARGIN - Sched<AE + NST>::t;
                *reinterpret_cast<volatile uint32_t*>(smem + OFF_EPOCH + 8) = base;
                mbar_wait(bar_init3);
                if (lane < 4) mbar_arrive(bar_base);
                STAMP(23);
                const uint32_t cb = base + W_SHIFT;
                auto early = [&](int i, uint32_t tt) {
                    mbar_wait(empty + 8 * (i - NST));
                    pace_until(tt);
                    gutile(i);
                };
                for_entries<GU0 - 3, GU0 + 4>(cb, early);
                for_entries<GU0 + 4, 32>(cb, early);
            }
            mbar_wait(bar_epoch);
            const uint32_t t2 = lds32(sb + OFF_EPOCH) + 1, tagw = (t2 & 1) | ((t2 & 2) << 15), half = (warp & 1) * ABYTES;
            const uint32_t lo = half + lane * 32 + (lane & 4) * 4 + (lane >> 3) * 4, retry = bar_retry + (warp & 1) * 8;
            const bool leader = lane == 0;
            uint32_t slot = sb + (32 % NST) * SLOT, rpar = 0;
#pragma unroll 1
            for (int i = 32; i < NENT; i++) {
                const uint32_t src = i == XE ? sb + OFF_W : slot;
                if (i != XE) slot = slot == sb + (NST - 1) * SLOT ? sb : slot + SLOT;
                auto current = [&]() {
                    uint32_t v[8];
#pragma unroll
                    for (int u = 0; u < 8; u++) v[u] = lds32(src + lo + u * 1024);
#pragma unroll
                    for (int u = 0; u < 8; u += 2) asm("lop3.b32 %0, %0, %1, %2, 0x7e;" : "+r"(v[u]) : "r"(v[u + 1]), "r"(tagw));
                    return __all_sync(0xffffffffu, ((v[0] | v[2] | v[4] | v[6]) & 0x00010001u) == 0);
                };
                mbar_wait(raw + 8 * i);
                if (!current()) {
#pragma unroll 1
                    for (uint32_t it = 0;; it++) {
                        if (it > SPIN_LIMIT) __trap();
                        STAMP(16);
                        if (leader) mbar_expect_tx(retry, ABYTES);
                        bulk_load(src + half, reinterpret_cast<const char*>(prm.s->h) + (size_t)chunk * 524288 + (i - 32) * 16384 + half, ABYTES, retry);
                        mbar_wait(retry, rpar);
                        rpar ^= 1;
                        if (current()) break;
                    }
                }
                if (leader) mbar_arrive(full + 8 * i);
            }
        }
    } else {
        asm volatile("setmaxnreg.inc.sync.aligned.u32 216;");
        const int wg = warp >> 2, w = warp & 3, g = lane >> 2, c = lane & 3, at = tid & 127;
        float facc[4];
        float2 a[2], m0[2], a32[2], a128[2];
        auto load_const = [&]() {
            const float2* cp = reinterpret_cast<const float2*>(smem + OFF_CONST) + wg * 64 + w * 8 + g;
#pragma unroll
            for (int h = 0; h < 2; h++) { a[h] = cp[32 * h]; m0[h] = cp[128 + 32 * h]; a32[h] = cp[256 + 32 * h]; a128[h] = cp[384 + 32 * h]; }
        };
        if (wg == 0) {
            named_bar(0, 256);
            STAMPIF(tid == 0, 20);
        } else {
            const int pc = (at >> 5) * 256 + dt * 32 + (at & 31);
            const float lr = __bfloat162float(prm.lam_re[pc]), li = __bfloat162float(prm.lam_im[pc]), ld = __bfloat162float(prm.log_dt[pc]);
            const uint32_t dk = __ldg(reinterpret_cast<const uint32_t*>(prm.dskip + dt * 128) + (at & 63));
#pragma unroll
            for (int i = 0; i < 4; i++) sts128(sb + OFF_LIST + i * 2048 + at * 16, 0u, 0u, 0u, 0u);

            {
                reinterpret_cast<uint32_t*>(smem + OFF_DK)[at & 63] = dk;
                const float dtv = rbf(expf(ld));
                const float er = expf(dtv * lr);
                float sn, cs;
                sincospif(dtv * li * 0.318309886183790672f, &sn, &cs);
                const float ar = er * cs, ai = er * sn;
                const float nr = ar - 1.0f, ni = ai;
                const bool big = fabsf(lr) >= fabsf(li);
                const float t = (big ? li : lr) / (big ? lr : li), dn = big ? lr + li * t : lr * t + li;
                const float cr = (big ? nr + ni * t : nr * t + ni) / dn, ci = (big ? ni - nr * t : ni * t - nr) / dn;
                float2* cp = reinterpret_cast<float2*>(smem + OFF_CONST) + at;
                float2 pw = make_float2(ar, prm.swapped ? ai : -ai);
                cp[0] = pw;
                cp[128] = make_float2(prm.swapped ? -2.f * cr : 2.f * cr, -2.f * ci);
#pragma unroll
                for (int i = 1; i <= 7; i++) {
                    pw = cmul(pw, pw);
                    if (i == 5) cp[256] = pw;
                    if (i == 7) cp[384] = pw;
                }
                __syncwarp();
            }
            named_bar(2, 128);
            load_const();
            mbar_wait(bar_epoch);
            const uint32_t tag = *reinterpret_cast<volatile uint32_t*>(smem + OFF_EPOCH) + 1;
            asm volatile("st.relaxed.gpu.global.b64 [%0], %1;" ::"l"(&prm.s->carry[(chunk >> 2) * 4096 + pc * 4 + (chunk & 3)]), "l"((unsigned long long)(tag + 2)) : "memory");
            if (w == 2) st_cell(lane < 4 ? (uint4*)prm.s->rpack + cta * 4 + lane : (uint4*)prm.s->gpack + cta * 4 + (lane & 3), 0, 0, 0, 0, lane < 8);
            {
                const uint32_t nt = ((tag & 1) | ((tag & 2) << 15)) ^ 0x00010001u;
                st_cell(prm.s->hid + cta * 32 - 512 + lane, nt, nt, nt, nt, has_gu && w == 3);
            }
            named_bar(2, 128);
            if (at < 2) mbar_arrive(bar_init3);
            unsigned long long* pub = (w ? prm.s->gpack : prm.s->rpack) + cta * 8 + lane;
            asm volatile("" : "+l"(pub));
            STAMPIF(lane == 0, 52);
            mbar_wait(bar_rdone);

            if (w < 2) {
                const float2* red = reinterpret_cast<const float2*>(smem + OFF_RED) + w * 8 + (lane & 7);
                const float2 r0 = red[0], r1 = red[16], r2 = red[32], r3 = red[48];
                const float v0 = (r0.x + r1.x) + (r2.x + r3.x), v1 = (r0.y + r1.y) + (r2.y + r3.y);
                uint32_t pk2;
                if (w == 0) {
                    pk2 = pack_bf(v0, v1);
                    pk2 ^= (((pk2 >> 15) & 0x00010001u) * 0x7FFFu) ^ 0x80008000u;
                } else pk2 = pack_bf(sigmoidf_(rbf(v0)), sigmoidf_(rbf(v1)));
                if (lane < 8) asm volatile("st.relaxed.gpu.global.b64 [%0], %1;" ::"l"(pub), "l"(((unsigned long long)tag << 32) | pk2) : "memory");
                __syncwarp();
            }
            STAMPIF(at == 0, 24);
            uint32_t it = 0, pr[8], g1;
            mbar_wait(bar_init3);
            sleep_until(clk32() + (w < 2 ? G0 : G0 + 250));
            while (true) {
                bool ok = true;
#pragma unroll
                for (int k = 0; k < 4; k++) {
                    const ulonglong2 u = ld_relaxed2(&prm.s->rpack[k * 256 + 2 * at]);
                    ok = ok && (uint32_t)(u.x >> 32) == tag && (uint32_t)(u.y >> 32) == tag;
                    pr[2 * k] = (uint32_t)u.x; pr[2 * k + 1] = (uint32_t)u.y;
                }
                const unsigned long long u1 = ld_relaxed1(&prm.s->gpack[chunk * 64 + (at & 63)]);
                ok = ok && (uint32_t)(u1 >> 32) == tag;
                g1 = (uint32_t)u1;
                if (__all_sync(0xffffffffu, ok)) break;
                if (++it > SPIN_LIMIT) __trap();
            }
            STAMPIF(lane == 0, 25);
            uint32_t m = __vmaxu2(__vimax3_u16x2(__vimax3_u16x2(pr[0], pr[1], pr[2]), pr[3], pr[4]), __vimax3_u16x2(pr[5], pr[6], pr[7]));
            m = (max(m, m << 16) & 0xFFFF0000u) | (uint32_t)lane;
            const uint32_t m1 = __reduce_max_sync(0xffffffffu, m), m2 = __reduce_max_sync(0xffffffffu, m == m1 ? 0u : m);
            uint32_t* keys = reinterpret_cast<uint32_t*>(smem + OFF_KEYS);
            if (lane == 0) keys[w] = m2;
            sts128(sb + OFF_XS + 4096 + at * 16, pr[0], pr[1], pr[2], pr[3]);
            sts128(sb + OFF_XS + 6144 + at * 16, pr[4], pr[5], pr[6], pr[7]);
            *reinterpret_cast<uint32_t*>(smem + OFF_G + 4 * (at & 63)) = g1;
            named_bar(2, 128);
            const uint4 th4 = *reinterpret_cast<const uint4*>(keys);
            const uint32_t th = (max(min(min(th4.x, th4.y), min(th4.z, th4.w)) >> 16, 1u) - 1u) * 0x00010001u;
            uint32_t mask = 0;
#pragma unroll
            for (int k = 7; k >= 0; k--) mask = mask * 2 + __vminu2(__vmaxu2(pr[k], th) ^ th, 0x00010001u);
            uint32_t pos = 0;
            asm volatile("{ .reg .pred p; setp.ne.u32 p, %2, 0; @p atom.shared.add.u32 %0, [%1], %2; }" : "+r"(pos) : "r"(sb + OFF_KEYS + 16), "r"(__popc(mask)) : "memory");
            while (mask) {
                const int bit = __ffs(mask) - 1, k = bit & 7, hi = bit >> 4;
                mask &= mask - 1;
                const uint32_t sc = *reinterpret_cast<const uint16_t*>(smem + OFF_XS + 4096 + (k >> 2) * 2048 + at * 16 + (k & 3) * 4 + hi * 2);
                *reinterpret_cast<uint32_t*>(smem + OFF_LIST + 4 * pos++) = (sc << 16) | (0x8000u + 2047u - (uint32_t)((k >> 1) * 512 + 4 * at + 2 * (k & 1) + hi));
            }
            __syncwarp();
            if (lane == 0) mbar_arrive(bar_cand);
            STAMPIF(lane == 0, 26);
            mbar_wait(bar_order0);
        }

        float accA[64], accB[64];
        Ring ring = {bar_dummy, wg};
        {
            run_entries<0, 0>(ring, wg * 16, wg ? GU0 : RE0, accA, accB, facc, true);
            if (wg == 0) {
                float racc[4];
                mbar_wait(bar_vec);
                run_entries<0, 1>(ring, RE0, RE0 + 4, accA, accB, racc, false, true);
                mbar_wait(bar_init2);
                const uint32_t red = sb + OFF_RED + 4 * (w * 32 + (c >> 1) * 16 + g);
                run_entries<0, 0>(ring, RE0 + 4, RE0 + 5, accA, accB, facc, false, false, [&]() {
                    pin4(racc);
                    asm volatile("{ .reg .pred p; setp.ne.u32 p, %3, 0; @p st.shared.f32 [%0], %1; @p st.shared.f32 [%0 + 32], %2; }" ::"r"(red),
                                 "f"((w & 1) ? racc[1] : racc[0]), "f"((w & 1) ? racc[3] : racc[2]), "r"((uint32_t)((c & 1) == (w >> 1))) : "memory");
                    __syncwarp();
                    if (lane == 0) mbar_arrive(bar_rdone);
                    STAMPIF(lane == 0, 5);
                });
                run_entries<0, 0>(ring, RE0 + 5, 16, accA, accB, facc);
                if (lane == 0) mbar_arrive(bar_order0);
                mbar_wait(bar_init3);
                load_const();
                named_bar(3, 128);
            } else {
#pragma unroll
                for (int u = 0; u < 2; u++) {
                    mbar_wait(u ? bar_xs : bar_xs0);
                    run_entries<0, 2>(ring, GU0 + 8 * u, u ? 32 : GU0 + 8, accA, accB, facc, false, u == 0);
                }
                if (lane == 0) mbar_arrive(bar_order1);
            }
        }
        const uint32_t tag = *reinterpret_cast<volatile uint32_t*>(smem + OFF_EPOCH) + 1;
        const float2 a64[2] = {cmul(a32[0], a32[0]), cmul(a32[1], a32[1])};
        wgmma_wait<0>();
        pin64(accA); pin64(accB); pin4(facc);
        if (lane == 0) mbar_arrive(ring.prev);
        STAMPIF(at == 0, 28 + wg);
        GSTAMP(tid == 0, 1);
        LP(1);

        const int tl = 32 * (g >> 1) + (g & 1) + 4 * w + 16 * wg, t0 = chunk * 128 + tl;
        float* op = prm.out + (size_t)t0 * D_ + dt * 128 + 4 * c;
        uint2 xv[8][2], dk[8];
        uint32_t gp[2], om[2], routed[2];
        auto row_setup = [&]() {
            const uint4 sa = *reinterpret_cast<const uint4*>(smem + OFF_SEL), sc = *reinterpret_cast<const uint4*>(smem + OFF_SEL + 16);
#pragma unroll
            for (int r = 0; r < 2; r++) {
                const uint32_t id = 0x8000u + 2047u - (uint32_t)(t0 + 2 * r);
                routed[r] = (uint16_t)sa.x == id || (uint16_t)sa.y == id || (uint16_t)sa.z == id || (uint16_t)sa.w == id ||
                            (uint16_t)sc.x == id || (uint16_t)sc.y == id || (uint16_t)sc.z == id || (uint16_t)sc.w == id;
                gp[r] = reinterpret_cast<const uint16_t*>(smem + OFF_G)[tl + 2 * r] * 0x00010001u;
                om[r] = pack_bf(1.0f - bf_hi(gp[r]), 1.0f - bf_hi(gp[r]));
            }
#pragma unroll
            for (int j = 0; j < 8; j++) dk[j] = lds64(sb + OFF_DK + 32 * j + 8 * c);
        };
        auto release = [&](uint32_t bar) {
            asm volatile("fence.proxy.async.shared::cta;" ::: "memory");
            __syncwarp();
            if (lane == 0) mbar_arrive(bar);
        };

        {
            const uint32_t t2 = tag & 3u;
            float2* cslot = &prm.s->carry[(wg * 512 + dt * 32 + w * 8 + g) * 4];
            const int j1 = chunk - 1 - c;
            unsigned long long v[2][4] = {{t2, t2, t2, t2}, {t2, t2, t2, t2}};
            auto poll = [&](int h) {
#pragma unroll
                for (int m = 0; m < 4; m++)
                    asm volatile("{ .reg .pred p; setp.ge.s32 p, %2, %3; @p ld.relaxed.gpu.global.b64 %0, [%1]; }"
                                 : "+l"(v[h][m]) : "l"(cslot + (j1 >> 2) * 4096 + c - m * 4096 + h * 1024), "r"(j1), "r"(4 * m) : "memory");
            };
            float2 e[2], w0[2];
            auto chain = [&](int h, int s0, int s1) {
                float (&acc)[64] = h ? accB : accA;
                if (s0 == 1) e[h] = make_float2(acc[0], acc[2]);
#pragma unroll
                for (int s = s0; s < s1; s++) {
                    const int i0 = 4 * (s >> 1) + (s & 1);
                    e[h] = cfma(make_float2(a[h].x, -a[h].y), e[h], make_float2(acc[i0], acc[i0 + 2]));
                }
                asm volatile("" : "+f"(e[h].x), "+f"(e[h].y), "+f"(accB[0]), "+f"(accB[2]));
                gap();
            };
            auto publish = [&](int h) {
                float2 f = make_float2(fmaf(m0[h].x, e[h].x, m0[h].y * e[h].y), fmaf(-m0[h].x, e[h].y, m0[h].y * e[h].x));
                float2 y = make_float2(__shfl_up_sync(0xffffffffu, f.x, 1, 4), __shfl_up_sync(0xffffffffu, f.y, 1, 4));
                if (c >= 1) f = cfma(a32[h], y, f);
                y = make_float2(__shfl_up_sync(0xffffffffu, f.x, 2, 4), __shfl_up_sync(0xffffffffu, f.y, 2, 4));
                if (c >= 2) f = cfma(a64[h], y, f);
                asm volatile("{ .reg .pred p; .reg .b64 t; setp.eq.u32 p, %3, 3; mov.b64 t, {%1, %2}; @p st.relaxed.gpu.global.b64 [%0], t; }"
                             ::"l"(cslot + (chunk >> 2) * 4096 + (chunk & 3) + h * 1024), "r"((__float_as_uint(f.x) & ~3u) | t2), "r"(__float_as_uint(f.y)), "r"(c) : "memory");
                w0[h] = make_float2(__shfl_up_sync(0xffffffffu, f.x, 1, 4), __shfl_up_sync(0xffffffffu, f.y, 1, 4));
                if (c == 0) w0[h] = make_float2(0.f, 0.f);
            };
            auto scale = [&](int h, int n0, int n1) {
                float (&acc)[64] = h ? accB : accA;
#pragma unroll
                for (int n = n0; n < n1; n++) {
                    asm volatile("{ .reg .f32 a, b, c, d, n; neg.f32 n, %4; mul.f32 a, %1, %5; mul.f32 b, %0, %5; mul.f32 c, %3, %5; mul.f32 d, %2, %5;\n"
                                 "fma.rn.f32 %0, %0, %4, a; fma.rn.f32 %1, %1, n, b; fma.rn.f32 %2, %2, %4, c; fma.rn.f32 %3, %3, n, d; }"
                                 : "+f"(acc[4 * n]), "+f"(acc[4 * n + 2]), "+f"(acc[4 * n + 1]), "+f"(acc[4 * n + 3]) : "f"(m0[h].x), "f"(m0[h].y));
                    gap();
                }
            };
            auto carry = [&](int h) {
                const float2 one = make_float2(1.f, 0.f), a256 = cmul(a128[h], a128[h]);
                float2 a512 = cmul(a256, a256), pw128 = cmul((j1 & 1) ? a128[h] : one, (j1 & 2) ? a256 : one);
                float2 pw32 = cmul((c & 1) ? a32[h] : one, (c & 2) ? a64[h] : one);
                asm volatile("" : "+f"(a512.x), "+f"(a512.y), "+f"(pw128.x), "+f"(pw128.y), "+f"(pw32.x), "+f"(pw32.y));
                STAMPIF(lane == 0 && !h, 34 + 2 * wg);
                uint32_t it = 0;
                while (!__all_sync(0xffffffffu, ((((uint32_t)v[h][0] ^ t2) | ((uint32_t)v[h][1] ^ t2) | ((uint32_t)v[h][2] ^ t2) | ((uint32_t)v[h][3] ^ t2)) & 3u) == 0)) {
                    poll(h);
                    if (++it > SPIN_LIMIT) __trap();
                }
                STAMPIF(lane == 0 && !h, 35 + 2 * wg);
                float2 hin = make_float2(__uint_as_float((uint32_t)v[h][3]), __uint_as_float((uint32_t)(v[h][3] >> 32)));
#pragma unroll
                for (int m = 2; m >= 0; m--) hin = cfma(a512, hin, make_float2(__uint_as_float((uint32_t)v[h][m]), __uint_as_float((uint32_t)(v[h][m] >> 32))));
                hin = cmul(pw128, hin);
                hin.x += __shfl_xor_sync(0xffffffffu, hin.x, 1); hin.y += __shfl_xor_sync(0xffffffffu, hin.y, 1);
                hin.x += __shfl_xor_sync(0xffffffffu, hin.x, 2); hin.y += __shfl_xor_sync(0xffffffffu, hin.y, 2);
                w0[h] = cfma(pw32, hin, w0[h]);
            };
            chain(0, 1, 32);
            publish(0);
            chain(1, 1, 8);
            STAMPIF(lane == 0, 30 + 2 * wg);
            chain(1, 8, 32);
            publish(1);
            gap();
            scale(0, 0, POLL_S);
            poll(0);
            scale(0, POLL_S, 16);
            carry(0);
            if (wg) mbar_wait(bar_out + 24);
            STAMPIF(lane == 0, 38 + 2 * wg);
            const uint32_t stg = sb + OFF_STG + prm.swapped * 8192 + w * 1024 + (lane & 7) * 128 + (((lane >> 3) ^ (lane & 7)) << 4);
            const uint32_t second = prm.swapped ? -8192 : 8192;
            uint32_t hold = prm.swapped >> 1, last[8];
            const uint32_t keep = c == (g >> 1) ? 0xFFFEFFFEu : 0xFFFFFFFFu, tagw = ((t2 & 1) | ((t2 & 2) << 15)) & ~keep;
#pragma unroll
            for (int h = 0; h < 2; h++) {
                float (&acc)[64] = h ? accB : accA;
                uint32_t ra[16], ia[16];
                if (h) {
                    scale(1, 0, 4);
#pragma unroll
                    for (int u = 0; u < 4; u++) asm volatile("lop3.b32 %0, %0, %1, %2, 0x80;" : "+r"(hold) : "r"(last[u]), "r"(last[4 + u]));
                    release(bar_st + 32 * wg + 8 + hold);
                    poll(1);
                    scale(1, 4, 16);
                    mbar_wait(bar_xs);
                    row_setup();
                    carry(1);
                }
                auto stage = [&](uint32_t (&r)[16], uint32_t base, int j) {
                    stsm4((base ^ ((j & 1) * 64)) + (j >> 1) * 4096, r[4 * j], r[4 * j + 1], r[4 * j + 2], r[4 * j + 3]);
                };
#pragma unroll
                for (int n = 0; n < 16; n++) {
                    const float2 y = cfma(a[h], w0[h], make_float2(acc[4 * n], acc[4 * n + 2]));
                    w0[h] = cfma(a[h], y, make_float2(acc[4 * n + 1], acc[4 * n + 3]));
                    ra[n] = pack_bf(y.x, w0[h].x);
                    ia[n] = pack_bf(y.y, w0[h].y);
                    if (!(n & 1)) { ra[n] = (ra[n] & keep) | tagw; ia[n] = (ia[n] & keep) | tagw; }
                    if (!h && (n & 3) == 3) {
                        if (n > 3) {
                            gap();
#pragma unroll
                            for (int u = n - 7; u < n - 3; u++) asm volatile("lop3.b32 %0, %0, %1, %2, 0x80;" : "+r"(hold) : "r"(ra[u]), "r"(ia[u]));
                        }
                        if (n == 15) {
#pragma unroll
                            for (int u = 0; u < 4; u++) { last[u] = ra[12 + u]; last[4 + u] = ia[12 + u]; }
                        }
                        if (n == 11) { asm volatile("" : "+r"(ra[n]), "+r"(ia[n])); gap(); release(bar_st + 32 * wg); }
                        stage(ra, stg, n >> 2); stage(ia, stg + second, n >> 2);
                        gap();
                    }
                }
                if (h) {
                    STAMPIF(lane == 0, 39 + 2 * wg);
                    mbar_wait(bar_out + 32 * wg);
                    if (prm.swapped) {
#pragma unroll
                        for (int n = 0; n < 16; n++) { const uint32_t t = ra[n]; ra[n] = ia[n]; ia[n] = t; }
                    }
                    const uint32_t st0 = stg - prm.swapped * 8192;
#pragma unroll
                    for (int j = 0; j < 4; j++) stage(ra, st0, j);
                    release(bar_st + 32 * wg + 16);
                    mbar_wait(bar_out + 32 * wg + 8);
#pragma unroll
                    for (int j = 0; j < 4; j++) stage(ia, st0 + 8192, j);
                    release(bar_st + 32 * wg + 24);
                }
                STAMPIF(lane == 0, 42 + 2 * wg + h);
            }
        }

        const uint32_t xr = 2 * (g & 3) + (g >> 2), xa = sb + (wg ? OFF_STG : OFF_W) + (16 * w + xr) * 128 + (((c >> 1) ^ xr) << 4) + (c & 1) * 8;
        auto handover = [&](uint32_t bar) {
            const uint4 z = ldsm4(sb + OFF_KEYS + 16);
            if (lane == 1) mbar_arrive(bar + z.x);
        };
        auto load_x = [&](int j0, int j1) {
#pragma unroll
            for (int j = j0; j < j1; j++)
#pragma unroll
                for (int r = 0; r < 2; r++) xv[j][r] = lds64((xa ^ (32 * (j & 3))) + (j >> 2) * ABYTES + r * 1024);
        };
        auto skip_term = [&](int j0, int j1) {
#pragma unroll
            for (int j = j0; j < j1; j++)
#pragma unroll
                for (int r = 0; r < 2; r++) {
                    xv[j][r].x = mul_bf2(xv[j][r].x, fma_bf2(gp[r], dk[j].x, om[r]));
                    xv[j][r].y = mul_bf2(xv[j][r].y, fma_bf2(gp[r], dk[j].y, om[r]));
                    asm volatile("" : "+r"(xv[j][r].x), "+r"(xv[j][r].y));
                }
        };
        auto finish = [&](float (&acc)[64], int j, bool gaps) {
#pragma unroll
            for (int r = 0; r < 2; r++) {
                const int o = 8 * j + 2 * r;
                const float gv = bf_hi(gp[r]);
                acc[o] = fmaf(gv, acc[o], bf_lo(xv[j][r].x)); acc[o + 1] = fmaf(gv, acc[o + 1], bf_hi(xv[j][r].x));
                acc[o + 4] = fmaf(gv, acc[o + 4], bf_lo(xv[j][r].y)); acc[o + 5] = fmaf(gv, acc[o + 5], bf_hi(xv[j][r].y));
                stg4_unless(op + r * 2 * D_ + 16 * j, acc[o], acc[o + 1], acc[o + 4], acc[o + 5], routed[r]);
                if (gaps) gap();
            }
        };
        auto finish_routed = [&](float (&acc)[64]) {
#pragma unroll
            for (int r = 0; r < 2; r++)
                if (routed[r]) {
#pragma unroll
                    for (int j = 0; j < 8; j++) red4(op + r * 2 * D_ + 16 * j, acc[8 * j + 2 * r], acc[8 * j + 2 * r + 1], acc[8 * j + 2 * r + 4], acc[8 * j + 2 * r + 5]);
                }
            __syncwarp();
        };
        const uint32_t xbuf = sb + w * 2048 + lane * 16;

        if (wg == 1) {
            float outB[64];
            {
                sts128(sb + OFF_XS + at * 16, __float_as_uint(facc[0]), __float_as_uint(facc[1]), __float_as_uint(facc[2]), __float_as_uint(facc[3]));
                named_bar(2, 128);
                const uint32_t pg = sb + OFF_XS + prm.up_first * 1024 + (at & 63) * 16 + (w >> 1) * 8, pu = pg + 1024 - prm.up_first * 2048;
                const uint2 g1 = lds64(pg), u1 = lds64(pu);
                uint4* hp = prm.s->hid + cta * 32 - 512 + 16 * (w & 1) + 8 * (w >> 1) + g;
                asm volatile("" : "+l"(hp));
                mbar_wait(bar_fp);
                const uint2 g2 = lds64(pg + 2048), u2 = lds64(pu + 2048);
                const float ga = rbf(__uint_as_float(g1.x) + __uint_as_float(g2.x)), gb = rbf(__uint_as_float(g1.y) + __uint_as_float(g2.y));
                uint32_t hw = mul_bf2(pack_bf(__fdividef(ga, 1.0f + __expf(-ga)), __fdividef(gb, 1.0f + __expf(-gb))),
                                      pack_bf(__uint_as_float(u1.x) + __uint_as_float(u2.x), __uint_as_float(u1.y) + __uint_as_float(u2.y)));
                if (c == 2 * (w & 1) + (w >> 1)) hw = (hw & 0xFFFEFFFEu) | (tag & 1) | ((tag & 2) << 15);
                st_cell(hp, hw, __shfl_down_sync(0xffffffffu, hw, 1), __shfl_down_sync(0xffffffffu, hw, 2), __shfl_down_sync(0xffffffffu, hw, 3), has_gu && c == 0);
            }
            STAMPIF(lane == 0, 47);
            mbar_wait(bar_xb);
            load_x(0, 8);
            release(bar_xbfree);
            skip_term(0, 8);
            STAMPIF(lane == 0, 46);
            mbar_wait(bar_order2);
            static_for<NENT - FIN>([&](auto u) {
                run_small<1, FIN + u>(outB);
                if (u == FE) { wgmma_wait<2>(); if (lane == 0) mbar_arrive(bar_fold); }
            });
            wgmma_wait<0>();
            pin64(outB);
            KSTAMP(2 * NENT - FIN);
            STAMPIF(at == 0, 50);
            LT(0);
#pragma unroll
            for (int q = 0; q < 2; q++) {
                uint4 pb[16];
                mbar_wait(bar_accb + 8 * q);
                if (q) LT(1);
#pragma unroll
                for (int v = q * HP; v < (q ? 16 : HP); v++) pb[v] = ldsm4(xbuf + sum_off(v));
#pragma unroll
                for (int v = q * HP; v < (q ? 16 : HP); v++) {
                    outB[4 * v] += __uint_as_float(pb[v].x); outB[4 * v + 1] += __uint_as_float(pb[v].y);
                    outB[4 * v + 2] += __uint_as_float(pb[v].z); outB[4 * v + 3] += __uint_as_float(pb[v].w);
                    if (v & 1) finish(outB, v >> 1, false);
                    if (v == DV) { gap(); if (lane == 0) mbar_expect_tx(bar_dn, w ? 0 : 7 * ABYTES); }
                }
            }
            finish_routed(outB);
            STAMPIF(lane == 0, 51);
            LT(2);
        } else {
            float outA[64], outB[64], gacc[4];
            ring.slot = 32 % NST;
            ring.prev = bar_dummy;
            mbar_wait(bar_order1);
            run_entries<1, 2>(ring, 32, GU0 + 32, outA, outB, gacc, true, true);
            run_entries<1, 0>(ring, GU0 + 32, GU0 + 33, outA, outB, gacc, false, false, [&]() {
                LP(2);
                pin4(gacc);
                sts128(sb + OFF_XS + 2048 + at * 16, __float_as_uint(gacc[0]), __float_as_uint(gacc[1]), __float_as_uint(gacc[2]), __float_as_uint(gacc[3]));
                __syncwarp();
                if (lane == 0) mbar_arrive(bar_fp);
            });
            mbar_wait(bar_xa);
            load_x(0, 2);
            run_entries<1, 0>(ring, GU0 + 33, GU0 + 34, outA, outB, gacc, false, false, [&]() { load_x(2, 3); });
            load_x(3, 5);
            run_entries<1, 0>(ring, GU0 + 34, GU0 + 35, outA, outB, gacc, false, false, [&]() { load_x(5, 6); });
            load_x(6, 8);
            run_entries<1, 0>(ring, GU0 + 35, GU0 + 36, outA, outB, gacc, false, false, [&]() { handover(bar_xafree); });
            skip_term(0, 3);
            run_entries<1, 0>(ring, GU0 + 36, GU0 + 37, outA, outB, gacc, false, false, [&]() { skip_term(3, 5); });
            skip_term(5, 8);
            run_entries<1, 0>(ring, GU0 + 37, FIN, outA, outB, gacc);
            auto dump = [&](int v) {
                stsm4(xbuf + sum_off(v), __float_as_uint(outB[4 * v]), __float_as_uint(outB[4 * v + 1]), __float_as_uint(outB[4 * v + 2]),
                      __float_as_uint(outB[4 * v + 3]));
            };
            static_for<NENT - FIN>([&](auto u) {
                mbar_wait(full + 8 * (FIN + u));
                run_small<0, FIN + u>(outA);
                if (u == 5 && lane == 0) mbar_arrive(bar_order2);
                wgmma_wait<1>();
                if (lane == 0) mbar_arrive(empty + 8 * (FIN + u - 1));
                if (u == 0) { pin64(outB); LP(3); }
                if (u == 2) mbar_wait(empty + 8 * FIN);
                if (u >= 2) dump(u - 2);
            });
            const uint2 sk = lds64(sb + OFF_SEL + 8 * c), fk = lds64(sb + OFF_FAC + 8 * c);
            float* y0 = prm.out + (~sk.x & 2047u) * D_ + (cta & 15) * 64 + w * 16 + g;
            float* y1 = prm.out + (~sk.y & 2047u) * D_ + (cta & 15) * 64 + w * 16 + g;
            asm volatile("" : "+l"(y0), "+l"(y1));
            handover(bar_accb);
            wgmma_wait<0>();
            pin64(outA);
            STAMPIF(at == 0, 53);
            GSTAMP(at == 0, 2);
#pragma unroll
            for (int j = 0; j < 8; j++) {
                finish(outA, j, true);
            }
            STAMPIF(lane == 0, 54);
            LT(0);
            mbar_wait(bar_fold);
#pragma unroll
            for (int v = 4; v < 16; v++) dump(v);
            handover(bar_accb + 8);
            STAMPIF(lane == 0, 55);
            finish_routed(outA);
            float yacc[4];
            const uint64_t dw = make_desc(sb), dh = (uint64_t)(((sb + OFF_XS) & 0x3FFFF) >> 4) | ((uint64_t)8 << 16) | ((uint64_t)8 << 32);
            mbar_wait(bar_zero);
            mbar_wait(bar_dn);
            STAMPIF(at == 0, 2);
            LT(1);
            wgmma_fence();
#pragma unroll
            for (int n = 0; n < 28; n++) wgmma_n8<1, 1>(yacc, dw + (dn_off(n >> 2) >> 4) + (n & 3) * 128, dh + n * 16, n > 0);
            wgmma_commit();
            wgmma_wait<0>();
            pin4(yacc);
            LT(2);
            asm volatile("red.global.add.f32 [%0], %2; red.global.add.f32 [%1], %3; red.global.add.f32 [%0 + 32], %4; red.global.add.f32 [%1 + 32], %5;"
                         ::"l"(y0), "l"(y1), "f"(yacc[0] * __uint_as_float(fk.x)), "f"(yacc[1] * __uint_as_float(fk.y)), "f"(yacc[2] * __uint_as_float(fk.x)),
                         "f"(yacc[3] * __uint_as_float(fk.y)) : "memory");
            STAMPIF(lane == 0, 3);
            LT(3);
        }
    }
}

typedef CUresult (*EncodeFn)(CUtensorMap*, CUtensorMapDataType, cuuint32_t, void*, const cuuint64_t*, const cuuint64_t*, const cuuint32_t*,
                             const cuuint32_t*, CUtensorMapInterleave, CUtensorMapSwizzle, CUtensorMapL2promotion, CUtensorMapFloatOOBfill);

bool encode(EncodeFn fn, CUtensorMap* m, const void* ptr, int rank, const cuuint64_t* dims, const cuuint64_t* strides, const cuuint32_t* box,
            CUtensorMapSwizzle sw = CU_TENSOR_MAP_SWIZZLE_128B, CUtensorMapL2promotion promo = CU_TENSOR_MAP_L2_PROMOTION_NONE) {
    const cuuint32_t es[5] = {1, 1, 1, 1, 1};
    return fn(m, CU_TENSOR_MAP_DATA_TYPE_BFLOAT16, rank, const_cast<void*>(ptr), dims, strides, box, es, CU_TENSOR_MAP_INTERLEAVE_NONE,
              sw, promo, CU_TENSOR_MAP_FLOAT_OOB_FILL_NONE) == CUDA_SUCCESS;
}

}

extern "C" void kernel_launch(void* const* d_in, const int* in_sizes, int n_in, void* d_out, int out_size) {
    (void)in_sizes; (void)n_in; (void)out_size;
    Params prm;
    prm.x = (const __nv_bfloat16*)d_in[0];
    prm.lam_re = (const __nv_bfloat16*)d_in[1];
    prm.lam_im = (const __nv_bfloat16*)d_in[2];
    prm.b_re = (const __nv_bfloat16*)d_in[3];
    prm.b_im = (const __nv_bfloat16*)d_in[4];
    prm.c_re = (const __nv_bfloat16*)d_in[5];
    prm.c_im = (const __nv_bfloat16*)d_in[6];
    prm.log_dt = (const __nv_bfloat16*)d_in[7];
    prm.dskip = (const __nv_bfloat16*)d_in[8];
    prm.w_r = (const __nv_bfloat16*)d_in[10];
    prm.gate_w = (const __nv_bfloat16*)d_in[14];
    prm.out = (float*)d_out;
    cudaGetSymbolAddress((void**)&prm.s, g_scratch);
    int dev = 0, sms = 0;
    cudaGetDevice(&dev);
    cudaDeviceGetAttribute(&sms, cudaDevAttrMultiProcessorCount, dev);
    auto kernel = sms == NGRID ? fused_kernel<true> : fused_kernel<false>;
    prm.swapped = prm.b_im < prm.b_re;

    void* fnp = nullptr;
    cudaDriverEntryPointQueryResult qr;
    cudaGetDriverEntryPoint("cuTensorMapEncodeTiled", &fnp, cudaEnableDefault, &qr);
    EncodeFn fn = (EncodeFn)fnp;
    cudaFuncSetAttribute(kernel, cudaFuncAttributeMaxDynamicSharedMemorySize, SMEM_BYTES);

    CUtensorMap mX, mB, mCre, mCim, mW, mWd, mXr, mXe;
    const cuuint64_t row = 2048;
    {
        const cuuint64_t dims[4] = {1024, 2, 4, 976}, st[3] = {row, 32 * row, 2 * row};
        const cuuint32_t box[4] = {64, 2, 4, 16};
        encode(fn, &mX, prm.x, 4, dims, st, box, CU_TENSOR_MAP_SWIZZLE_128B, PROMO);
    }
    {
        const char *lo = (const char*)(prm.swapped ? prm.b_im : prm.b_re), *hi = (const char*)(prm.swapped ? prm.b_re : prm.b_im);
        const cuuint64_t dims[5] = {1024, 8, 2, 96, 2}, st[4] = {row, (cuuint64_t)(hi - lo), 8 * row, 256 * row};
        const cuuint32_t box[5] = {64, 8, 2, 4, 2};
        encode(fn, &mB, lo, 5, dims, st, box, CU_TENSOR_MAP_SWIZZLE_128B, PROMO);
    }
    {
        const cuuint64_t dims[5] = {1024, 2, 4, 2, 64}, st[4] = {row, 4 * row, 2 * row, 16 * row};
        const cuuint32_t box[5] = {64, 2, 4, 2, 8};
        encode(fn, &mCre, prm.c_re, 5, dims, st, box);
        encode(fn, &mCim, prm.c_im, 5, dims, st, box);
    }
    {
        const char *pg = (const char*)d_in[11], *pu = (const char*)d_in[12];
        prm.up_first = pu < pg;
        const cuuint64_t dims[3] = {F_, D_, 2}, st[2] = {F_ * 2, (cuuint64_t)(pu < pg ? pg - pu : pu - pg)}, dimsd[2] = {D_, F_}, std_[1] = {row};
        const cuuint32_t box[3] = {32, 32, 2}, boxd[2] = {64, 64};
        encode(fn, &mW, pu < pg ? pu : pg, 3, dims, st, box, CU_TENSOR_MAP_SWIZZLE_64B, CU_TENSOR_MAP_L2_PROMOTION_NONE);
        encode(fn, &mWd, d_in[13], 2, dimsd, std_, boxd, CU_TENSOR_MAP_SWIZZLE_128B, CU_TENSOR_MAP_L2_PROMOTION_NONE);
    }
    {
        const cuuint64_t dims[3] = {D_ - 192, S_, 4}, st[2] = {row, 128};
        const cuuint32_t box[3] = {64, 16, 4};
        encode(fn, &mXr, prm.x, 3, dims, st, box, CU_TENSOR_MAP_SWIZZLE_128B, CU_TENSOR_MAP_L2_PROMOTION_NONE);
    }
    {
        const cuuint64_t dims[5] = {D_, 2, 2, 2, 976}, st[4] = {64 * row, row, 32 * row, 2 * row};
        const cuuint32_t box[5] = {64, 2, 2, 2, 8};
        encode(fn, &mXe, prm.x, 5, dims, st, box);
    }
    kernel<<<NGRID, 384, SMEM_BYTES, cudaStreamPerThread>>>(prm, mX, mB, mCre, mCim, mW, mWd, mXr, mXe);
}
```

```cpp
#include <cuda_runtime.h>
#include <cuda_bf16.h>
#include <cuda.h>
#include <stdint.h>

namespace {

constexpr int S_ = 2048, D_ = 1024, F_ = 3584;
constexpr int NCTA = 128, NGRID = 132;
#define XE_ 58
#define GU0_ 18
constexpr int NENT = 64, FIN = 58, XE = XE_;
constexpr int NST = 5;
constexpr int RE0 = 4;
constexpr int GU0 = GU0_;
constexpr uint32_t SLOT = 32768, ABYTES = 8192, WBYTES = 4096;
constexpr uint32_t OFF_XS = NST * SLOT;
constexpr uint32_t OFF_LIST = OFF_XS + 8192;
constexpr uint32_t OFF_W = OFF_XS + 16384;
constexpr uint32_t OFF_STG = OFF_W + 32768;
__host__ __device__ constexpr uint32_t slot_off(int i) { return i < XE ? (i % NST) * SLOT : i == XE ? OFF_W : ((i - 1) % NST) * SLOT; }
__host__ __device__ constexpr uint32_t dn_off(int u) { return u == 0 ? OFF_XS + ABYTES : u < 3 ? OFF_STG + (u - 1) * ABYTES : slot_off(FIN - 2 + u); }
__host__ __device__ constexpr uint32_t sum_off(int v) { return slot_off(FIN) + (v >> 2) * ABYTES + (v & 3) * 512; }
constexpr uint32_t OFF_CONST = OFF_STG;
constexpr uint32_t OFF_RED = OFF_STG + 4096;
constexpr uint32_t OFF_FULL = OFF_STG + 16384;
constexpr uint32_t OFF_EMPTY = OFF_FULL + 120 * 8;
constexpr uint32_t OFF_G = OFF_EMPTY + 88 * 8;
constexpr uint32_t OFF_DK = OFF_G + 256;
constexpr uint32_t OFF_KEYS = OFF_DK + 256;
constexpr uint32_t OFF_SEL = OFF_KEYS + 32;
constexpr uint32_t OFF_FAC = OFF_SEL + 32;
constexpr uint32_t OFF_EPOCH = OFF_FAC + 32;
constexpr uint32_t OFF_PROF = OFF_EPOCH + 16;
constexpr uint32_t SMEM_BYTES = OFF_PROF + 768;
static_assert(SMEM_BYTES <= 232448, "smem");

constexpr uint32_t sb = 1024;
constexpr uint32_t SPIN_LIMIT = 1u << 18;

struct Scratch {
    unsigned int cnt[2 * 32];
    unsigned long long rpack[S_ / 2];
    unsigned long long gpack[S_ / 2];
    uint4 time[NCTA];
    float2 carry[16 * 1024];
    uint4 hid[F_];
    uint4 h[8 * 4 * 256 * 64];
};
__device__ __align__(128) Scratch g_scratch;
#define LT(i) do {} while (0)
#define STAMPW(cond, w) do {} while (0)
#define LATE(i, tt) do {} while (0)
#define LANDED(i) do {} while (0)
#define GSTAMP(cond, w) do {} while (0)
#define LP(i) do {} while (0)
#define STAMPIF(cond, i) STAMPW(cond, 72 + (i))
#define STAMP(i) STAMPW(1, 72 + (i))
#define KSTAMP(i) STAMPW((threadIdx.x & 127) == 0, i)

struct Params {
    const __nv_bfloat16 *x, *b_re, *b_im;
    Scratch* s;
    int up_first;
    int swapped;
    const __nv_bfloat16 *lam_re, *lam_im, *c_re, *c_im, *log_dt, *dskip, *w_r, *gate_w;
    float* out;
};

__device__ __forceinline__ uint32_t smem_u32(const void* p) { return (uint32_t)__cvta_generic_to_shared(p); }
__device__ __forceinline__ void mbar_init(uint32_t bar, uint32_t cnt) { asm volatile("mbarrier.init.shared::cta.b64 [%0], %1;" ::"r"(bar), "r"(cnt) : "memory"); }
__device__ __forceinline__ void mbar_expect_tx(uint32_t bar, uint32_t bytes) { asm volatile("mbarrier.arrive.expect_tx.shared::cta.b64 _, [%0], %1;" ::"r"(bar), "r"(bytes) : "memory"); }
__device__ __forceinline__ void mbar_arrive(uint32_t bar) { asm volatile("mbarrier.arrive.shared::cta.b64 _, [%0];" ::"r"(bar) : "memory"); }
__device__ __forceinline__ void mbar_wait(uint32_t bar, uint32_t parity = 0) {
    asm volatile("{ .reg .pred p; .reg .u32 n;\n"
                 "mov.u32 n, 0;\n"
                 "AGAIN: mbarrier.try_wait.parity.shared::cta.b64 p, [%0], %1;\n"
                 "@p bra.uni DONE;\n"
                 "add.u32 n, n, 1;\n"
                 "setp.lt.u32 p, n, %2;\n"
                 "@p bra.uni AGAIN;\n"
                 "trap;\n"
                 "DONE: }" ::"r"(bar), "r"(parity), "n"(SPIN_LIMIT) : "memory");
}
__device__ __forceinline__ bool elect_one() {
    uint32_t pred;
    asm volatile("{ .reg .pred P; elect.sync _|P, 0xffffffff; selp.b32 %0, 1, 0, P; }" : "=r"(pred));
    return pred;
}
__device__ __forceinline__ void named_bar(int id, int n) { asm volatile("bar.sync %0, %1;" ::"r"(id), "r"(n) : "memory"); }

#define ONE "{ .reg .pred e; elect.sync _|e, 0xffffffff;\n@e "
template <int N> __device__ __forceinline__ void mbar_init_n(uint32_t bar, uint32_t cnt, uint32_t extra = 0) {
    if (elect_one()) {
#pragma unroll
        for (int i = 0; i < N; i++) mbar_init(bar + 8 * i, i == N - 1 ? cnt + extra : cnt);
        asm volatile("fence.mbarrier_init.release.cluster;" ::: "memory");
    }
    __syncwarp();
}
__device__ __forceinline__ void bulk_load(uint32_t dst, const void* src, uint32_t bytes, uint32_t bar) {
    asm volatile(ONE "cp.async.bulk.shared::cluster.global.mbarrier::complete_tx::bytes [%0], [%1], %2, [%3]; }" ::"r"(dst), "l"(src), "r"(bytes), "r"(bar) : "memory");
}
__device__ __forceinline__ void sts128(uint32_t a, uint32_t x, uint32_t y, uint32_t z, uint32_t w) {
    asm volatile("st.shared.v4.u32 [%0], {%1,%2,%3,%4};" ::"r"(a), "r"(x), "r"(y), "r"(z), "r"(w) : "memory");
}
__device__ __forceinline__ uint2 lds64(uint32_t a) {
    uint2 v;
    asm volatile("ld.shared.v2.u32 {%0,%1}, [%2];" : "=r"(v.x), "=r"(v.y) : "r"(a) : "memory");
    return v;
}
__device__ __forceinline__ uint32_t clk32() { uint32_t c; asm volatile("mov.u32 %0, %%clock;" : "=r"(c)); return c; }
__device__ __forceinline__ void gap() { asm volatile("pmevent 1;" ::: "memory"); }
__device__ __forceinline__ void pace_until(uint32_t t) { while ((int)(clk32() - t) < 0) {} }
#define SLEEP_MARGIN 200
__device__ __forceinline__ void sleep_until(uint32_t t) {
    while ((int)(clk32() + SLEEP_MARGIN - t) < 0) __nanosleep(40);
    pace_until(t);
}
__device__ __forceinline__ void tma2(uint32_t dst, const CUtensorMap* m, int c0, int c1, uint32_t bar, uint64_t pol) {
    asm volatile(ONE "cp.async.bulk.tensor.2d.shared::cluster.global.mbarrier::complete_tx::bytes.L2::cache_hint [%0], [%1, {%3, %4}], [%2], %5; }"
                 ::"r"(dst), "l"(m), "r"(bar), "r"(c0), "r"(c1), "l"(pol) : "memory");
}
__device__ __forceinline__ void tma3s(uint32_t dst, const CUtensorMap* m, int c0, int c1, uint32_t bar, uint64_t pol) {
    asm volatile(ONE "cp.async.bulk.tensor.3d.shared::cluster.global.mbarrier::complete_tx::bytes.L2::cache_hint [%0], [%1, {%3, %4, %5}], [%2], %6; }"
                 ::"r"(dst), "l"(m), "r"(bar), "r"(c0), "r"(c1), "r"(0), "l"(pol) : "memory");
}
__device__ __forceinline__ void tma3(uint32_t dst, const CUtensorMap* m, int c0, int c1, uint32_t bar) {
    asm volatile(ONE "cp.async.bulk.tensor.3d.shared::cluster.global.mbarrier::complete_tx::bytes [%0], [%1, {%3, %4, %5}], [%2]; }"
                 ::"r"(dst), "l"(m), "r"(bar), "r"(c0), "r"(c1), "r"(0) : "memory");
}
__device__ __forceinline__ void tma4(uint32_t dst, const CUtensorMap* m, int c0, int c3, uint32_t bar) {
    asm volatile(ONE "cp.async.bulk.tensor.4d.shared::cluster.global.mbarrier::complete_tx::bytes [%0], [%1, {%3, %5, %5, %4}], [%2]; }"
                 ::"r"(dst), "l"(m), "r"(bar), "r"(c0), "r"(c3), "r"(0) : "memory");
}
__device__ __forceinline__ void tma5(uint32_t dst, const CUtensorMap* m, int c0, int c4, uint32_t bar) {
    asm volatile(ONE "cp.async.bulk.tensor.5d.shared::cluster.global.mbarrier::complete_tx::bytes [%0], [%1, {%3, %5, %5, %5, %4}], [%2]; }"
                 ::"r"(dst), "l"(m), "r"(bar), "r"(c0), "r"(c4), "r"(0) : "memory");
}
__device__ __forceinline__ void tma5b(uint32_t dst, const CUtensorMap* m, int c0, int c3, uint32_t bar) {
    asm volatile(ONE "cp.async.bulk.tensor.5d.shared::cluster.global.mbarrier::complete_tx::bytes [%0], [%1, {%3, %5, %5, %4, %5}], [%2]; }"
                 ::"r"(dst), "l"(m), "r"(bar), "r"(c0), "r"(c3), "r"(0) : "memory");
}
__device__ __forceinline__ void prefetch_l2(const void* p) {
    asm volatile("cp.async.ca.shared.global.L2::256B [%0], [%1], 4;" ::"r"(sb + OFF_EPOCH + 12), "l"(p) : "memory");
}

__device__ __forceinline__ uint32_t lds32(uint32_t a) {
    uint32_t v;
    asm volatile("ld.volatile.shared.u32 %0, [%1];" : "=r"(v) : "r"(a) : "memory");
    return v;
}
__device__ __forceinline__ uint32_t uni(uint32_t v) { return __shfl_sync(0xffffffffu, v, 0); }   __device__ __forceinline__ uint32_t ld_acquire(const unsigned int* p) {
    uint32_t v;
    asm volatile("ld.acquire.gpu.global.u32 %0, [%1];" : "=r"(v) : "l"(p) : "memory");
    return v;
}
__device__ __forceinline__ void red_release(unsigned int* p) { asm volatile("red.release.gpu.global.add.u32 [%0], 1;" ::"l"(p) : "memory"); }
__device__ __forceinline__ void wait_count(const unsigned int* p, uint32_t target) {
#pragma unroll 1
    for (uint32_t it = 0; it < SPIN_LIMIT; ++it)
        if ((int)(ld_acquire(p) - target) >= 0) return;
    __trap();
}
__device__ __forceinline__ void wait_count_slow(const unsigned int* p, uint32_t target) {
#pragma unroll 1
    for (uint32_t it = 0; it < SPIN_LIMIT; ++it) {
        if ((int)(ld_acquire(p) - target) >= 0) return;
        __nanosleep(200);
    }
    __trap();
}
__device__ __forceinline__ unsigned long long ld_relaxed1(const void* p) {
    unsigned long long v;
    asm volatile("ld.relaxed.gpu.global.b64 %0, [%1];" : "=l"(v) : "l"(p) : "memory");
    return v;
}
__device__ __forceinline__ ulonglong2 ld_relaxed2(const void* p) {
    ulonglong2 v;
    asm volatile("ld.relaxed.gpu.global.v2.b64 {%0, %1}, [%2];" : "=l"(v.x), "=l"(v.y) : "l"(p) : "memory");
    return v;
}
__device__ __forceinline__ void ld_cell(uint32_t (&v)[4], const void* p, bool on = true) {
    asm volatile("{ .reg .pred p; .reg .b64 l, h; .reg .b128 t; setp.ne.u32 p, %5, 0; mov.b64 l, {%0, %1}; mov.b64 h, {%2, %3}; mov.b128 t, {l, h};\n"
                 "@p ld.relaxed.gpu.global.b128 t, [%4]; mov.b128 {l, h}, t; mov.b64 {%0, %1}, l; mov.b64 {%2, %3}, h; }"
                 : "+r"(v[0]), "+r"(v[1]), "+r"(v[2]), "+r"(v[3]) : "l"(p), "r"((uint32_t)on) : "memory");
}
__device__ __forceinline__ void st_cell(void* p, uint32_t a, uint32_t b, uint32_t c, uint32_t d, bool on) {
    asm volatile("{ .reg .pred p; .reg .b64 l, h; .reg .b128 t; setp.ne.u32 p, %5, 0; mov.b64 l, {%1, %2}; mov.b64 h, {%3, %4}; mov.b128 t, {l, h};\n"
                 "@p st.relaxed.gpu.global.b128 [%0], t; }" ::"l"(p), "r"(a), "r"(b), "r"(c), "r"(d), "r"((uint32_t)on) : "memory");
}

__device__ __forceinline__ uint64_t make_desc(uint32_t addr, uint32_t sbo = 1024) {
    return (uint64_t)((addr & 0x3FFFF) >> 4) | ((uint64_t)1 << 16) | ((uint64_t)(sbo >> 4) << 32) | ((uint64_t)1 << 62);
}
__device__ __forceinline__ void wgmma_fence() { asm volatile("wgmma.fence.sync.aligned;" ::: "memory"); }
__device__ __forceinline__ void wgmma_commit() { asm volatile("wgmma.commit_group.sync.aligned;" ::: "memory"); }
template <int N> __device__ __forceinline__ void wgmma_wait() { asm volatile("wgmma.wait_group.sync.aligned %0;" ::"n"(N) : "memory"); }

#define R8(d, i) "+f"(d[i]), "+f"(d[i + 1]), "+f"(d[i + 2]), "+f"(d[i + 3]), "+f"(d[i + 4]), "+f"(d[i + 5]), "+f"(d[i + 6]), "+f"(d[i + 7])
#define R64(d) R8(d, 0), R8(d, 8), R8(d, 16), R8(d, 24), R8(d, 32), R8(d, 40), R8(d, 48), R8(d, 56)
template <int TA>
__device__ __forceinline__ void wgmma_n128(float (&d)[64], uint64_t da, uint64_t db, int scale_d = 1) {
    asm volatile("{ .reg .pred p; setp.ne.b32 p, %66, 0;\n"
                 "wgmma.mma_async.sync.aligned.m64n128k16.f32.bf16.bf16 "
                 "{%0,%1,%2,%3,%4,%5,%6,%7,%8,%9,%10,%11,%12,%13,%14,%15,%16,%17,%18,%19,%20,%21,%22,%23,%24,%25,%26,%27,%28,%29,%30,%31,"
                 "%32,%33,%34,%35,%36,%37,%38,%39,%40,%41,%42,%43,%44,%45,%46,%47,%48,%49,%50,%51,%52,%53,%54,%55,%56,%57,%58,%59,%60,%61,%62,%63}, "
                 "%64, %65, p, 1, 1, %67, 0; }"
                 : R64(d)
                 : "l"(da), "l"(db), "r"(scale_d), "n"(TA));
}
__device__ __forceinline__ void pin4(float (&d)[4]) { asm volatile("" : "+f"(d[0]), "+f"(d[1]), "+f"(d[2]), "+f"(d[3])::"memory"); }
__device__ __forceinline__ void pin64(float (&d)[64]) { asm volatile("" : R64(d)::"memory"); }

template <int TA, int TB = 0>
__device__ __forceinline__ void wgmma_n8(float (&d)[4], uint64_t da, uint64_t db, int scale_d = 1) {
    asm volatile("{ .reg .pred p; setp.ne.b32 p, %7, 0;\n"
                 "wgmma.mma_async.sync.aligned.m64n8k16.f32.bf16.bf16 {%0,%1,%2,%3}, %4, %5, p, 1, 1, %6, %8; }"
                 : "+f"(d[0]), "+f"(d[1]), "+f"(d[2]), "+f"(d[3])
                 : "l"(da), "l"(db), "n"(TA), "r"(scale_d), "n"(TB));
}

__device__ __forceinline__ float bf_lo(uint32_t u) { return __uint_as_float(u << 16); }
__device__ __forceinline__ float bf_hi(uint32_t u) { return __uint_as_float(u & 0xFFFF0000u); }
__device__ __forceinline__ float rbf(float v) { return __bfloat162float(__float2bfloat16_rn(v)); }
__device__ __forceinline__ uint32_t pack_bf(float lo, float hi) {
    uint32_t r;
    asm("cvt.rn.bf16x2.f32 %0, %1, %2;" : "=r"(r) : "f"(hi), "f"(lo));
    return r;
}
__device__ __forceinline__ uint32_t mul_bf2(uint32_t a, uint32_t b) {
    __nv_bfloat162 r = __hmul2(*reinterpret_cast<__nv_bfloat162*>(&a), *reinterpret_cast<__nv_bfloat162*>(&b));
    return *reinterpret_cast<uint32_t*>(&r);
}
__device__ __forceinline__ uint32_t fma_bf2(uint32_t a, uint32_t b, uint32_t c) {
    uint32_t r;
    asm("fma.rn.bf16x2 %0, %1, %2, %3;" : "=r"(r) : "r"(a), "r"(b), "r"(c));
    return r;
}
__device__ __forceinline__ float2 cmul(float2 a, float2 b) { return make_float2(a.x * b.x - a.y * b.y, a.x * b.y + a.y * b.x); }
__device__ __forceinline__ float2 cfma(float2 a, float2 b, float2 c) {
    return make_float2(fmaf(a.x, b.x, fmaf(-a.y, b.y, c.x)), fmaf(a.x, b.y, fmaf(a.y, b.x, c.y)));
}
__device__ __forceinline__ float sigmoidf_(float v) { return __fdividef(1.0f, 1.0f + expf(-v)); }

__device__ __forceinline__ void bulk_prefetch(const void* src, uint32_t bytes) {
    asm volatile(ONE "cp.async.bulk.prefetch.L2.global [%0], %1; }" ::"l"(src), "r"(bytes) : "memory");
}
__device__ __forceinline__ void bulk_store(void* dst, uint32_t src, uint32_t bytes) {
    asm volatile(ONE "cp.async.bulk.global.shared::cta.bulk_group [%0], [%1], %2; }" ::"l"(dst), "r"(src), "r"(bytes) : "memory");
}
__device__ __forceinline__ void stsm4(uint32_t a, uint32_t x, uint32_t y, uint32_t z, uint32_t w) {
    asm volatile("stmatrix.sync.aligned.m8n8.x4.shared.b16 [%0], {%1,%2,%3,%4};" ::"r"(a), "r"(x), "r"(y), "r"(z), "r"(w) : "memory");
}
__device__ __forceinline__ uint4 ldsm4(uint32_t a) {
    uint4 v;
    asm volatile("ldmatrix.sync.aligned.m8n8.x4.shared.b16 {%0,%1,%2,%3}, [%4];" : "=r"(v.x), "=r"(v.y), "=r"(v.z), "=r"(v.w) : "r"(a) : "memory");
    return v;
}
__device__ __forceinline__ void stg4_unless(float* p, float a, float b, float c, float d, uint32_t skip) {
    asm volatile("{ .reg .pred p; setp.eq.u32 p, %5, 0; @p st.global.v4.f32 [%0], {%1,%2,%3,%4}; }" ::"l"(p), "f"(a), "f"(b), "f"(c), "f"(d), "r"(skip) : "memory");
}
__device__ __forceinline__ void red4(float* p, float a, float b, float c, float d) {
    asm volatile("red.global.add.v4.f32 [%0], {%1,%2,%3,%4};" ::"l"(p), "f"(a), "f"(b), "f"(c), "f"(d) : "memory");
}

#define TT0 2900
#define PER 510
#define PCUT 60
#define PFIN 360
#define PF0 1500
#define PFX_PACE 400
#define PF1 700
#define T2 300
#define P2 520
#define G0 450
#define R0 1900
#define R_PACE 250
#define W_SHIFT 250
#define PROMO CU_TENSOR_MAP_L2_PROMOTION_L2_256B
#define POLL_S 0
#define ST_TOL 100
#define ST_SHIFT 300
#define CLK_NS 420
#define MARGIN 60
#define BP1 12
#define DV 15
#define HOLD 450
#define RD 1500
#define FE 5
#define HP 4
#define AE 6
#define AG0 900
#define AB 17
#define HGE 39
constexpr uint32_t duration(int i) { return PER + (i >= RE0 && i < RE0 + 4 ? 72 : 0) + (i >= GU0 && i < GU0 + 32 ? 36 : 0); }
constexpr uint32_t cmax(uint32_t a, uint32_t b) { return a > b ? a : b; }
constexpr uint32_t issue_time(int i) {
    return i <= NST ? TT0 : i < XE ? issue_time(i - 1) + duration(i - NST) - (i >= XE - 3 && i > GU0 + 36 ? PCUT : 0) : issue_time(XE - 1) + cmax((i - XE + 1) * PFIN, (i - XE) * 512);
}
template <int I> struct Sched { static constexpr uint32_t t = issue_time(I); };
template <int LO, int HI, class F>
__device__ __forceinline__ void for_entries(uint32_t base, F body) {
    constexpr uint32_t per = Sched<LO + 1>::t - Sched<LO>::t;
    static_assert(Sched<HI - 1>::t - Sched<LO>::t == (HI - 1 - LO) * per, "period");
    uint32_t tt = base + Sched<LO>::t;
#pragma unroll 1
    for (int i = LO; i < HI; i++) {
        body(i, tt);
        tt += per;
    }
}

struct Ring { uint32_t prev; int slot; };
struct NoHook { __device__ void operator()() const {} };
template <int TA, int SM, class H = NoHook>
__device__ __forceinline__ void run_entries(Ring& r, int lo, int hi, float (&accA)[64], float (&accB)[64], float (&small)[4],
                                            bool fresh = false, bool sfresh = false, H released = H()) {
    const uint64_t d0 = make_desc(sb);
    const bool leader = (threadIdx.x & 31) == 0;
#pragma unroll 1
    for (int i = lo; i < hi; i++) {
        const uint32_t bar = sb + OFF_FULL + 8 * i;
        const uint64_t da = d0 + (uint64_t)(r.slot * (SLOT >> 4));
        const int n = i - (SM == 1 ? RE0 : GU0);
        const uint64_t dw = SM == 1 ? d0 + (uint64_t)((OFF_W >> 4) + n * 512)
                                    : (((uint64_t)2 << 62) | ((uint64_t)32 << 32) | (128u << 16) | ((sb + OFF_W) >> 4)) + (uint64_t)((n & 7) * 256);
        const uint64_t dt8 = d0 + (uint64_t)((OFF_XS >> 4) + (SM == 1 ? n * 64 : (n >> 1) * 64 + (n & 1) * 4));
        r.slot = r.slot == NST - 1 ? 0 : r.slot + 1;
        mbar_wait(bar);
        KSTAMP(i);
        wgmma_fence();
#pragma unroll
        for (int kk = 0; kk < 4; kk++) {
            wgmma_n128<TA>(accA, da + kk * (TA ? 128 : 2), da + 1024 + kk * 2, kk > 0 || !fresh);
            if (SM && kk == 3) {
#pragma unroll
                for (int u = 0; u < (SM == 1 ? 4 : 2); u++) wgmma_n8<SM - 1 + !SM>(small, dw + u * (SM == 1 ? 2 : 64), dt8 + u * 2, u > 0 || !sfresh);
            }
            wgmma_n128<TA>(accB, da + 512 + kk * (TA ? 128 : 2), da + 1024 + kk * 2, kk > 0 || !fresh);
            if (kk == 1) {
                wgmma_commit();
                wgmma_wait<1>();
                if (leader) mbar_arrive(r.prev);
                released();
            }
        }
        wgmma_commit();
        r.prev = bar + (OFF_EMPTY - OFF_FULL);
        fresh = sfresh = false;
    }
}
template <int HALF, int I>
__device__ __forceinline__ void run_small(float (&acc)[64]) {
    const uint64_t da = make_desc(sb) + (slot_off(I) >> 4);
    KSTAMP(I + HALF * (NENT - FIN));
    wgmma_fence();
#pragma unroll
    for (int kk = 0; kk < 4; kk++) wgmma_n128<1>(acc, da + HALF * 512 + kk * 128, da + 1024 + kk * 2, kk > 0 || !(HALF && I == FIN));
    wgmma_commit();
}
template <int V> struct Int { __host__ __device__ constexpr operator int() const { return V; } };
template <int N, class F> __device__ __forceinline__ void static_for(F f) {
    if constexpr (N > 0) { static_for<N - 1>(f); f(Int<N - 1>()); }
}

template <bool BY_SMID>
__global__ void __launch_bounds__(384, 1)
fused_kernel(const __grid_constant__ Params prm, const __grid_constant__ CUtensorMap mX, const __grid_constant__ CUtensorMap mB, const __grid_constant__ CUtensorMap mCre,
             const __grid_constant__ CUtensorMap mCim, const __grid_constant__ CUtensorMap mW,
             const __grid_constant__ CUtensorMap mWd, const __grid_constant__ CUtensorMap mXr, const __grid_constant__ CUtensorMap mXe) {
    extern __shared__ __align__(1024) uint8_t smem[];
    const uint32_t cstart = clk32();
    const int tid = threadIdx.x, lane = tid & 31;
    uint32_t id = blockIdx.x;
    if (BY_SMID) asm volatile("mov.u32 %0, %%smid;" : "=r"(id));
    const uint32_t po = tid * 2048, pbo = (id & 127) * 8192;
    const char *p0 = (const char*)prm.x + (pbo * 4 + po), *p1 = (const char*)prm.b_re + (pbo + po), *p2 = (const char*)prm.b_im + (pbo + po);
    asm volatile("{ .reg .pred p, q; setp.lt.u32 p, %3, 16; setp.lt.u32 q, %3, 4;\n"
                 "@q prefetch.global.L2 [%1]; @p prefetch.global.L2 [%0]; @q prefetch.global.L2 [%2]; }" ::"l"(p0), "l"(p1), "l"(p2), "r"(tid) : "memory");
    const int warp = __shfl_sync(0xffffffffu, tid >> 5, 0);
    gap();
    int cta;
    asm("{ .reg .pred p; .reg .u32 a, b, u, q;\n"
        "and.b32 a, %1, 14; shl.b32 a, a, 3; shr.u32 b, %1, 3; and.b32 b, b, 6; add.u32 a, a, b;\n"
        "and.b32 u, %1, 62; mul.lo.u32 q, u, 37; shr.u32 q, q, 9; shl.b32 u, u, 3; mad.lo.u32 u, q, -110, u; add.u32 u, u, 24;\n"
        "setp.lt.u32 p, %1, 64; selp.u32 a, a, u, p; lop3.b32 a, a, %1, 1, 0xF8;\n"
        "setp.lt.u32 p, %1, 124; selp.u32 b, 8, -116, p; add.u32 b, b, %1; setp.lt.u32 p, %1, 120; selp.u32 %0, a, b, p; }" : "=r"(cta) : "r"(id));
    const int chunk = (cta >> 5) * 4 + ((cta >> 2) & 3);
    const int dt = ((cta >> 4) & 1) * 4 + (cta & 3);
    if ((warp | (cta & NCTA)) == 5) {
        mbar_init_n<2>(sb + OFF_FULL, 1);
        tma5b(sb, &mB, 0, dt * 4, sb + OFF_FULL);
        gap();
        tma4(sb + 2 * ABYTES, &mX, 0, chunk * 64, sb + OFF_FULL);
        tma5b(sb + SLOT, &mB, 64, dt * 4, sb + OFF_FULL + 8);
        tma4(sb + SLOT + 2 * ABYTES, &mX, 64, chunk * 64, sb + OFF_FULL + 8);
    }
    else pace_until(cstart + HOLD);
    asm volatile("{ .reg .pred p, q; setp.lt.u32 p, %3, 16; setp.lt.u32 q, %3, 4;\n"
                 "@q prefetch.global.L2 [%1 + 128]; @p prefetch.global.L2 [%0 + 128]; @q prefetch.global.L2 [%2 + 128]; }" ::"l"(p0), "l"(p1), "l"(p2), "r"(tid) : "memory");
    if (cta >= NCTA) {
        if (smem_u32(smem) != sb) __trap();
        if (tid == 0) wait_count_slow(&prm.s->cnt[0], (atomicAdd(&prm.s->cnt[0], 1u) / NGRID + 1) * NGRID);
        return;
    }
    const bool has_gu = cta >= 16;
    constexpr uint32_t full = sb + OFF_FULL, empty = sb + OFF_EMPTY;
    constexpr uint32_t raw = full + 8 * 32;
    constexpr uint32_t bar_hraw = full + 8 * 97, bar_xs = full + 8 * 98, bar_xb = full + 8 * 100, bar_xa = full + 8 * 101,
        bar_retry = full + 8 * 102, bar_out = full + 8 * 104;
    constexpr uint32_t bar_base = empty - 64, bar_init3 = empty - 56, bar_rdone = empty - 48, bar_order0 = empty - 40, bar_init2 = empty - 32,
        bar_vec = empty - 24, bar_epoch = empty - 16, bar_dummy = empty - 8, bar_xs0 = empty + 8 * 69,
        bar_zero = empty + 8 * 70, bar_xafree = empty + 8 * 71, bar_order2 = empty + 8 * 72, bar_dn = empty + 8 * 73, bar_fp = empty + 8 * 74,
        bar_accb = empty + 8 * 76, bar_xbfree = empty + 8 * 78, bar_fold = empty + 8 * 79, bar_st = empty + 8 * 80,
        bar_order1 = empty + 8 * 67, bar_cand = empty + 8 * 68;

    if (warp == 5) {
        STAMP(31);
        if (lane < 2) mbar_expect_tx(full + 8 * lane, SLOT);
        __syncwarp();
        named_bar(0, 256);
#pragma unroll 1
        for (int i = 2; i < NST; i++) {
            pace_until(cstart + T2 + i * P2);
            tma5b(sb + i * SLOT, &mB, i * 64, dt * 4, full + 8 * i);
            tma4(sb + i * SLOT + 2 * ABYTES, &mX, i * 64, chunk * 64, full + 8 * i);
            STAMPIF(i == 4, 1);
        }
    } else if (warp == 4) {
        mbar_init_n<12>(bar_init2, 4);
        asm volatile("bar.arrive 0, 256;" ::: "memory");
        mbar_init_n<4>(bar_base, 4);
        mbar_init_n<8>(empty + 64, 4);
        *reinterpret_cast<uint2*>(smem + OFF_KEYS + 16) = make_uint2(0, 0);
        asm volatile("bar.arrive 1, 64;" ::: "memory");
        asm volatile("bar.arrive 5, 96;" ::: "memory");
        asm volatile("bar.arrive 6, 96;" ::: "memory");
        mbar_init_n<32>(full + 256, 3);
        if (lane < 2) mbar_arrive(bar_init2);
    } else if ((warp >> 1) == 3) {
        if (warp == 6) {
            mbar_init_n<8>(full + 16, 1);
            if (lane >= 2 && lane < 10) mbar_expect_tx(full + 8 * lane, lane >= RE0 && lane < RE0 + 4 ? SLOT + ABYTES : SLOT);
            __syncwarp();
            asm volatile("bar.arrive 0, 256;" ::: "memory");
        }
        const char* pf0 = (warp & 1) ? (const char*)((cta & 64) ? prm.b_im : prm.b_re) + (cta & 63) * 16384 : (const char*)prm.x + cta * 32768;
        pace_until(cstart + PF1);
        asm volatile("prefetch.global.L2 [%0];" ::"l"(pf0 + (lane & (30 >> (warp & 1) & 30)) * 1024 + (lane & 1) * 128 + 256));
        const int i0 = warp == 6 ? 10 : 21;
        mbar_init_n<11>(full + 8 * i0, 1);
        if (lane >= i0 && lane < i0 + 11) mbar_expect_tx(full + 8 * lane, lane >= GU0 && has_gu ? SLOT + WBYTES : SLOT);
        mbar_init_n<24>(full + 512 + 192 * (warp & 1), 1);
        named_bar(5, 96);
        if (lane == 0) mbar_arrive(bar_init2);
        STAMP(21);
    }
    __syncwarp();

    if (warp >= 8) {
        asm volatile("setmaxnreg.dec.sync.aligned.u32 72;");
        const uint32_t c0 = cstart;
        uint64_t stream;
        asm volatile("createpolicy.fractional.L2::evict_first.b64 %0, 1.0;" : "=l"(stream));
        const int dc = (cta & 15) * 64, dr = (cta >> 4) * 448;
        auto gutile = [&](int i) {
            const int n = i + 3 - GU0;
            if (has_gu) tma3s(sb + OFF_W + (n & 7) * WBYTES, &mW, cta * 32 - 512, n * 32, full + 8 * (i + 3), stream);
        };
        if (warp == 8) {
            named_bar(0, 256);
            sleep_until(c0 + RD);
            asm volatile("prefetch.tensormap [%0];" ::"l"(&mXr));
#pragma unroll 1
            for (int u = 0; u < 2; u++) {
                sleep_until(c0 + R0 + u * R_PACE);
                tma3(sb + OFF_W + u * ABYTES, &mXr, u * 256, cta * 16, full + 8 * (RE0 + u));
            }
            uint32_t dst = sb;
            auto gemm1 = [&](int i, uint32_t tt) {
                mbar_wait(empty + 8 * (i - NST));
                LATE(i, tt);
                pace_until(tt);
                tma5b(dst, &mB, (i & 15) * 64, (i >> 4) * 64 + dt * 4, full + 8 * i);
                tma4(dst + 2 * ABYTES, &mX, (i & 15) * 64, chunk * 64, full + 8 * i);
                dst = dst == sb + (NST - 1) * SLOT ? sb : dst + SLOT;
            };
            mbar_wait(bar_init2);
            uint32_t tt = c0 + TT0;
#pragma unroll 1
            for (int i = NST; i < AB; i++) {
                gemm1(i, tt);
                if (i < 7) tma3(sb + OFF_W + (i - 3) * ABYTES, &mXr, (i - 3) * 256, cta * 16, full + 8 * (i + 1));
                tt += (i & ~3) == RE0 + 4 ? PER + 72 : PER;
            }
            mbar_wait(bar_base);
            const uint32_t base = uni(lds32(sb + OFF_EPOCH + 8));
            tt = base + Sched<AB>::t;
#pragma unroll 1
            for (int i = AB; i < 32; i++) {
                gemm1(i, tt);
                tt += i >= GU0 + 4 ? PER + 36 : PER;
            }
            const char* hsrc = reinterpret_cast<const char*>(prm.s->h) + (size_t)chunk * 524288;
            auto gemm2 = [&](int i, uint32_t d, int freed, uint32_t tt) {
                mbar_wait(empty + 8 * freed);
                LATE(i, tt);
                pace_until(tt);
                bulk_load(d, hsrc, 2 * ABYTES, raw + 8 * i);
                tma5(d + 2 * ABYTES, (i & 4) ? &mCim : &mCre, ((i & 3) + ((i >> 1) & 12)) * 64, dt * 8, full + 8 * i);
                hsrc += 2 * ABYTES;
            };
            for_entries<32, GU0 + 29>(base, [&](int i, uint32_t tt) {
                gemm2(i, dst, i - NST, tt);
                gutile(i);
                dst = dst == sb + (NST - 1) * SLOT ? sb : dst + SLOT;
            });
            for_entries<GU0 + 29, GU0 + 37>(base, [&](int i, uint32_t tt) {
                gemm2(i, dst, i - NST, tt);
                const int n = i - GU0 - 29;
                if ((n & 5) == 1) tma5(sb + OFF_W + (n & 2) * (ABYTES / 2), &mXe, dt * 128 + (n & 2) * 32, chunk * 64, bar_xa);
                else if (n < 6) asm volatile(ONE "cp.async.bulk.prefetch.tensor.2d.L2.global [%0, {%1, %2}]; }" ::"l"(&mWd), "r"(dc), "r"(dr + 64 * (n < 4 ? 3 + n / 2 : n + 1)) : "memory");
                dst = dst == sb + (NST - 1) * SLOT ? sb : dst + SLOT;
            });
            static_for<NENT - GU0 - 37>([&](auto u) {
                constexpr int i = GU0 + 37 + u;
                if (i == 60) mbar_wait(bar_out + 56);
                gemm2(i, sb + slot_off(i), i < XE ? i - NST : i == XE ? 71   : i - NST - 1, base + Sched<i>::t);
            });
            STAMP(4);
        } else if (warp == 9) {
#pragma unroll
            for (int u = 0; u < 8; u++) {
                const int row = (u >> 2) * 4 + (lane >> 3);
                asm volatile("cp.async.cg.shared.global [%0], [%1], 16;" ::"r"(sb + OFF_XS + (u & 3) * 1024 + row * 128 + (((lane & 7) ^ row) << 4)),
                             "l"((const char*)(u < 4 ? prm.w_r : prm.gate_w) + (u & 3) * 512 + lane * 16) : "memory");
            }
            uint32_t ticket = 0;
            if (lane == 0) ticket = atomicAdd(&prm.s->cnt[0], 1u);
            named_bar(1, 64);
            if (lane == 0) *reinterpret_cast<volatile uint32_t*>(smem + OFF_EPOCH) = ticket / NGRID;
            __syncwarp();
            if (lane < 4) mbar_arrive(bar_epoch);
            asm volatile("cp.async.wait_all;" ::: "memory");
            asm volatile("fence.proxy.async.shared::cta;" ::: "memory");
            __syncwarp();
            if (lane < 4) mbar_arrive(bar_vec);
            STAMP(18);
#pragma unroll 1
            for (int i = 4; i < 22; i++) mbar_init_n<4>(empty + 32 * i, 4, i >= 6 && i < 13);
            if (lane < 2) mbar_arrive(bar_init3);
            STAMP(19);
            mbar_wait(bar_cand);
            {
                const uint32_t* list = reinterpret_cast<const uint32_t*>(smem + OFF_LIST);
                const int n = (int)lds32(sb + OFF_KEYS + 16);
#pragma unroll 1
                for (int i0 = 0; i0 < n; i0 += 32) {
                    const uint32_t k = list[i0 + lane];
                    int rank = 0;
#pragma unroll 2
                    for (int o = 0; o < n; o += 4) {
                        const uint4 l4 = *reinterpret_cast<const uint4*>(list + o);
                        rank += (l4.x > k) + (l4.y > k) + (l4.z > k) + (l4.w > k);
                    }
                    if (rank < 8) reinterpret_cast<uint32_t*>(smem + OFF_SEL)[rank] = k;
                }
                __syncwarp();
                STAMP(6);
                const uint32_t key = lds32(sb + OFF_SEL + 4 * (lane & 7)), tok = ~key & 2047u, tag = lds32(sb + OFF_EPOCH) + 1;
                const uint32_t ta = __shfl_sync(0xffffffffu, tok, lane >> 3), tb = __shfl_sync(0xffffffffu, tok, 4 + (lane >> 3));
                const uint32_t da = sb + OFF_XS + (lane >> 3) * 128 + (((lane & 7) ^ (lane >> 3)) << 4), db = (da ^ 64) + 512;
                const char *sa = (const char*)prm.x + ta * 2048 + (lane & 7) * 16, *sc = (const char*)prm.x + tb * 2048 + (lane & 7) * 16;
#pragma unroll
                for (int u = 0; u < 16; u++) {
                    asm volatile("cp.async.cg.shared.global [%0], [%1], 16;" ::"r"(da + u * 1024), "l"(sa + u * 128) : "memory");
                    asm volatile("cp.async.cg.shared.global [%0], [%1], 16;" ::"r"(db + u * 1024), "l"(sc + u * 128) : "memory");
                    if (u == 3) {
                        asm volatile("cp.async.wait_all;" ::: "memory");
                        asm volatile("fence.proxy.async.shared::cta;" ::: "memory");
                        __syncwarp();
                        if (lane < 4) mbar_arrive(bar_xs0);
                        STAMP(17);
                    }
                }
                if ((tok >> 7) == (uint32_t)chunk) {
                    float4* zp = reinterpret_cast<float4*>(prm.out + tok * D_ + dt * 128) + (lane >> 3) * 2;
#pragma unroll
                    for (int u = 0; u < 8; u++) zp[(u >> 1) * 8 + (u & 1)] = make_float4(0.f, 0.f, 0.f, 0.f);
                }
                uint32_t it = 0;
                unsigned long long u;
                do {
                    u = ld_relaxed1(&prm.s->gpack[tok >> 1]);
                    if (++it > SPIN_LIMIT) __trap();
                } while (!__all_sync(0xffffffffu, (uint32_t)(u >> 32) == tag));
                const uint32_t kb = key >> 16;
                const float r = bf_lo((kb & 0x8000u) ? (kb & 0x7FFFu) : (~kb & 0xFFFFu)), gv = (tok & 1) ? bf_hi((uint32_t)u) : bf_lo((uint32_t)u);
                reinterpret_cast<float*>(smem + OFF_FAC)[lane & 7] = rbf(1.0f - gv) * rbf(sigmoidf_(r));
                asm volatile("cp.async.wait_all;" ::: "memory");
                asm volatile("fence.proxy.async.shared::cta;" ::: "memory");
                __syncwarp();
                if (lane == 0) mbar_arrive(bar_xs);
                STAMP(7);
            }
            char* hd = reinterpret_cast<char*>(prm.s->h) + (size_t)chunk * 524288 + (dt >> 1) * 16384 + (dt & 1) * 4096;
            mbar_wait(bar_base);
            const uint32_t cb = uni(lds32(sb + OFF_EPOCH + 8)) + ST_SHIFT;
            uint32_t tt = cb + Sched<GU0 + 4>::t;
#pragma unroll 1
            for (int np = 0; np < 16; np++) {
                if (!(np & (np & 4 ? 1 : 2))) mbar_wait(bar_st + 4 * (np & 12) + ((np & 3) ? 8 : 0));
                const uint32_t now = clk32() - ST_TOL;
#pragma unroll 1
                while ((int)(tt - now) < 0) tt += PER + 36;
                const uint32_t src = sb + OFF_STG + (np & 3) * 4096;
                pace_until(tt);
                bulk_store(hd, src, 4096);
                asm volatile("cp.async.bulk.commit_group;" ::: "memory");
                if (np & 2) {
                    if (np & 1) asm volatile("cp.async.bulk.wait_group.read 0;" ::: "memory");
                    else asm volatile("cp.async.bulk.wait_group.read 1;" ::: "memory");
                    __syncwarp();
                    const uint32_t u8 = 4 * (np & 12) + 8 * (np & 1);
                    if (lane < 2) mbar_arrive(lane ? (np < 15 ? empty + 8 * 27 + 4 * u8 : bar_dummy) : bar_out + u8);
                }
                STAMPIF(np & 2, 8 + ((np >> 1) & 6) + (np & 1));
                hd += (np & 1) ? 65536 - 8192 : 8192;
                tt += PER + 36;
            }
#pragma unroll 1
            for (int u = 0; u < 2; u++) {
                pace_until(tt);
                tma5(sb + OFF_STG + u * ABYTES, &mXe, dt * 128 + u * 64, chunk * 64 + 8, bar_xb);
                tt += PER + 36;
            }
            wait_count(&prm.s->cnt[32], (lds32(sb + OFF_EPOCH) + 1) * NCTA);
            auto load_hid = [&]() {
                if (lane == 0) mbar_expect_tx(bar_hraw, 7168);
                bulk_load(sb + OFF_XS, prm.s->hid + dr, 7168, bar_hraw);
            };
            static_for<7>([&](auto u) {
                if (u != 2) mbar_wait(u == 1 ? bar_xbfree : empty + 8 * (u == 0 ? GU0 + 31 : FIN - 2 + u));
                if (u < 3) sleep_until(cb + Sched<GU0 + HGE - 2 + u>::t);
                if (u == 2) load_hid();
                tma2(sb + dn_off(u), &mWd, dc, dr + u * 64, bar_dn, stream);
                if (u == 2) {
                    const uint32_t t2 = lds32(sb + OFF_EPOCH) + 1, tagw = (t2 & 1) | ((t2 & 2) << 15);
#pragma unroll 1
                    for (uint32_t it = 0;; it++) {
                        mbar_wait(bar_hraw, it & 1);
                        uint32_t bad = 0;
#pragma unroll
                        for (int i = 0; i < 14; i++) bad |= lds32(sb + OFF_XS + i * 512 + lane * 16 + (lane >> 3) * 4) ^ tagw;
                        if (__all_sync(0xffffffffu, (bad & 0x00010001u) == 0)) break;
                        if (it > SPIN_LIMIT) __trap();
                        load_hid();
                    }
                    if (lane < 4) mbar_arrive(bar_zero);
                    STAMP(48);
                }
            });
            STAMP(27);
        } else {
            named_bar(6, 96);
            if (warp == 10) {
                const char* pb = (const char*)((cta & 64) ? prm.b_im : prm.b_re) + (cta & 63) * 16384;
                const char* pf = (lane < 16 ? (const char*)prm.x + cta * 32768 : pb) + (lane & 15) * 2048 + 512;
#pragma unroll 1
                for (int k = 0; k < 11; k++) {
                    sleep_until(c0 + PF0 + k * PFX_PACE);
                    if (lane < 16 ? k < 6 : lane < 24 && !(k & 1)) prefetch_l2(pf + k * (lane < 16 ? 256 : 128));
                }
#pragma unroll 1
                for (int k = 0; k < 12; k++) {
                    sleep_until(c0 + Sched<12>::t + ST_SHIFT + (k + BP1 - 12) * PER);
                    bulk_prefetch((k < 4 ? pb + 1048576 : (const char*)(k < 8 ? prm.c_re : prm.c_im) + cta * 16384) + (k & 3) * 4096, 4096);
                    if (k == 4) { mbar_wait(bar_init2); mbar_wait(bar_init3); }
                    if (k >= 4 && lane < 8) mbar_expect_tx(full + 8 * (8 * k + lane), 8 * k + lane < GU0 + 32 && has_gu ? 2 * ABYTES + WBYTES : 2 * ABYTES);
                }
                asm volatile("prefetch.tensormap [%0];" ::"l"(&mCre));
                asm volatile("prefetch.tensormap [%0];" ::"l"(&mCim));
                asm volatile("prefetch.tensormap [%0];" ::"l"(&mWd));
                asm volatile("prefetch.tensormap [%0];" ::"l"(&mXe));
                if (lane < 2) mbar_expect_tx(bar_xb + 8 * lane, 2 * ABYTES);
                mbar_wait(bar_xs);
                mbar_wait(bar_st);
                if (lane == 0) red_release(&prm.s->cnt[32]);
                __syncwarp();
                STAMP(22);
            } else {
                mbar_wait(bar_epoch);
                const uint32_t tag = lds32(sb + OFF_EPOCH) + 1;
                st_cell(prm.s->time + cta, 0, 0, 0, 0, lane == 0);
                asm volatile("prefetch.tensormap [%0];" ::"l"(&mW));
                mbar_wait(empty + 8 * AE);
                uint32_t gown, tm[4][4] = {}, it = 0;
                asm volatile("mov.u32 %0, %%globaltimer_lo;" : "=r"(gown));
                const uint32_t town = clk32();
                st_cell(prm.s->time + cta, tag, town, gown, 0, lane == 0);
                sleep_until(town + AG0);
                do {
#pragma unroll
                    for (int m = 0; m < 4; m++) ld_cell(tm[m], prm.s->time + ((cta & 96) ^ (32 * m)) + lane);
                    if (++it > SPIN_LIMIT) __trap();
                } while (!__all_sync(0xffffffffu, tm[0][0] == tag && tm[1][0] == tag && tm[2][0] == tag && tm[3][0] == tag));
                const int last = __reduce_max_sync(0xffffffffu, max(max((int)(tm[0][2] - gown), (int)(tm[1][2] - gown)), max((int)(tm[2][2] - gown), (int)(tm[3][2] - gown))));
                const uint32_t cand = tm[0][1] + ((min((int)(gown + last - tm[0][2]), 4000) * CLK_NS) >> 8);
                const uint32_t b0 = __shfl_sync(0xffffffffu, cand, cta & 16), b1 = __shfl_sync(0xffffffffu, cand, cta & 30);
                const uint32_t b2 = __shfl_sync(0xffffffffu, cand, cta & 31);
                const uint32_t base = (b0 - b2 + 400u < 800u ? b0 : b1 - b2 + 400u < 800u ? b1 : b2) + MARGIN - Sched<AE + NST>::t;
                *reinterpret_cast<volatile uint32_t*>(smem + OFF_EPOCH + 8) = base;
                mbar_wait(bar_init3);
                if (lane < 4) mbar_arrive(bar_base);
                STAMP(23);
                const uint32_t cb = base + W_SHIFT;
                auto early = [&](int i, uint32_t tt) {
                    mbar_wait(empty + 8 * (i - NST));
                    pace_until(tt);
                    gutile(i);
                };
                for_entries<GU0 - 3, GU0 + 4>(cb, early);
                for_entries<GU0 + 4, 32>(cb, early);
            }
            mbar_wait(bar_epoch);
            const uint32_t t2 = lds32(sb + OFF_EPOCH) + 1, tagw = (t2 & 1) | ((t2 & 2) << 15), half = (warp & 1) * ABYTES;
            const uint32_t lo = half + lane * 32 + (lane & 4) * 4 + (lane >> 3) * 4, retry = bar_retry + (warp & 1) * 8;
            const bool leader = lane == 0;
            uint32_t slot = sb + (32 % NST) * SLOT, rpar = 0;
#pragma unroll 1
            for (int i = 32; i < NENT; i++) {
                const uint32_t src = i == XE ? sb + OFF_W : slot;
                if (i != XE) slot = slot == sb + (NST - 1) * SLOT ? sb : slot + SLOT;
                auto current = [&]() {
                    uint32_t v[8];
#pragma unroll
                    for (int u = 0; u < 8; u++) v[u] = lds32(src + lo + u * 1024);
#pragma unroll
                    for (int u = 0; u < 8; u += 2) asm("lop3.b32 %0, %0, %1, %2, 0x7e;" : "+r"(v[u]) : "r"(v[u + 1]), "r"(tagw));
                    return __all_sync(0xffffffffu, ((v[0] | v[2] | v[4] | v[6]) & 0x00010001u) == 0);
                };
                mbar_wait(raw + 8 * i);
                if (!current()) {
#pragma unroll 1
                    for (uint32_t it = 0;; it++) {
                        if (it > SPIN_LIMIT) __trap();
                        STAMP(16);
                        if (leader) mbar_expect_tx(retry, ABYTES);
                        bulk_load(src + half, reinterpret_cast<const char*>(prm.s->h) + (size_t)chunk * 524288 + (i - 32) * 16384 + half, ABYTES, retry);
                        mbar_wait(retry, rpar);
                        rpar ^= 1;
                        if (current()) break;
                    }
                }
                if (leader) mbar_arrive(full + 8 * i);
            }
        }
    } else {
        asm volatile("setmaxnreg.inc.sync.aligned.u32 216;");
        const int wg = warp >> 2, w = warp & 3, g = lane >> 2, c = lane & 3, at = tid & 127;
        float facc[4];
        float2 a[2], m0[2], a32[2], a128[2];
        auto load_const = [&]() {
            const float2* cp = reinterpret_cast<const float2*>(smem + OFF_CONST) + wg * 64 + w * 8 + g;
#pragma unroll
            for (int h = 0; h < 2; h++) { a[h] = cp[32 * h]; m0[h] = cp[128 + 32 * h]; a32[h] = cp[256 + 32 * h]; a128[h] = cp[384 + 32 * h]; }
        };
        if (wg == 0) {
            named_bar(0, 256);
            STAMPIF(tid == 0, 20);
        } else {
            const int pc = (at >> 5) * 256 + dt * 32 + (at & 31);
            const float lr = __bfloat162float(prm.lam_re[pc]), li = __bfloat162float(prm.lam_im[pc]), ld = __bfloat162float(prm.log_dt[pc]);
            const uint32_t dk = __ldg(reinterpret_cast<const uint32_t*>(prm.dskip + dt * 128) + (at & 63));
#pragma unroll
            for (int i = 0; i < 4; i++) sts128(sb + OFF_LIST + i * 2048 + at * 16, 0u, 0u, 0u, 0u);

            {
                reinterpret_cast<uint32_t*>(smem + OFF_DK)[at & 63] = dk;
                const float dtv = rbf(expf(ld));
                const float er = expf(dtv * lr);
                float sn, cs;
                sincospif(dtv * li * 0.318309886183790672f, &sn, &cs);
                const float ar = er * cs, ai = er * sn;
                const float nr = ar - 1.0f, ni = ai;
                const bool big = fabsf(lr) >= fabsf(li);
                const float t = (big ? li : lr) / (big ? lr : li), dn = big ? lr + li * t : lr * t + li;
                const float cr = (big ? nr + ni * t : nr * t + ni) / dn, ci = (big ? ni - nr * t : ni * t - nr) / dn;
                float2* cp = reinterpret_cast<float2*>(smem + OFF_CONST) + at;
                float2 pw = make_float2(ar, prm.swapped ? ai : -ai);
                cp[0] = pw;
                cp[128] = make_float2(prm.swapped ? -2.f * cr : 2.f * cr, -2.f * ci);
#pragma unroll
                for (int i = 1; i <= 7; i++) {
                    pw = cmul(pw, pw);
                    if (i == 5) cp[256] = pw;
                    if (i == 7) cp[384] = pw;
                }
                __syncwarp();
            }
            named_bar(2, 128);
            load_const();
            mbar_wait(bar_epoch);
            const uint32_t tag = *reinterpret_cast<volatile uint32_t*>(smem + OFF_EPOCH) + 1;
            asm volatile("st.relaxed.gpu.global.b64 [%0], %1;" ::"l"(&prm.s->carry[(chunk >> 2) * 4096 + pc * 4 + (chunk & 3)]), "l"((unsigned long long)(tag + 2)) : "memory");
            if (w == 2) st_cell(lane < 4 ? (uint4*)prm.s->rpack + cta * 4 + lane : (uint4*)prm.s->gpack + cta * 4 + (lane & 3), 0, 0, 0, 0, lane < 8);
            {
                const uint32_t nt = ((tag & 1) | ((tag & 2) << 15)) ^ 0x00010001u;
                st_cell(prm.s->hid + cta * 32 - 512 + lane, nt, nt, nt, nt, has_gu && w == 3);
            }
            named_bar(2, 128);
            if (at < 2) mbar_arrive(bar_init3);
            unsigned long long* pub = (w ? prm.s->gpack : prm.s->rpack) + cta * 8 + lane;
            asm volatile("" : "+l"(pub));
            STAMPIF(lane == 0, 52);
            mbar_wait(bar_rdone);

            if (w < 2) {
                const float2* red = reinterpret_cast<const float2*>(smem + OFF_RED) + w * 8 + (lane & 7);
                const float2 r0 = red[0], r1 = red[16], r2 = red[32], r3 = red[48];
                const float v0 = (r0.x + r1.x) + (r2.x + r3.x), v1 = (r0.y + r1.y) + (r2.y + r3.y);
                uint32_t pk2;
                if (w == 0) {
                    pk2 = pack_bf(v0, v1);
                    pk2 ^= (((pk2 >> 15) & 0x00010001u) * 0x7FFFu) ^ 0x80008000u;
                } else pk2 = pack_bf(sigmoidf_(rbf(v0)), sigmoidf_(rbf(v1)));
                if (lane < 8) asm volatile("st.relaxed.gpu.global.b64 [%0], %1;" ::"l"(pub), "l"(((unsigned long long)tag << 32) | pk2) : "memory");
                __syncwarp();
            }
            STAMPIF(at == 0, 24);
            uint32_t it = 0, pr[8], g1;
            mbar_wait(bar_init3);
            sleep_until(clk32() + (w < 2 ? G0 : G0 + 250));
            while (true) {
                bool ok = true;
#pragma unroll
                for (int k = 0; k < 4; k++) {
                    const ulonglong2 u = ld_relaxed2(&prm.s->rpack[k * 256 + 2 * at]);
                    ok = ok && (uint32_t)(u.x >> 32) == tag && (uint32_t)(u.y >> 32) == tag;
                    pr[2 * k] = (uint32_t)u.x; pr[2 * k + 1] = (uint32_t)u.y;
                }
                const unsigned long long u1 = ld_relaxed1(&prm.s->gpack[chunk * 64 + (at & 63)]);
                ok = ok && (uint32_t)(u1 >> 32) == tag;
                g1 = (uint32_t)u1;
                if (__all_sync(0xffffffffu, ok)) break;
                if (++it > SPIN_LIMIT) __trap();
            }
            STAMPIF(lane == 0, 25);
            uint32_t m = __vmaxu2(__vimax3_u16x2(__vimax3_u16x2(pr[0], pr[1], pr[2]), pr[3], pr[4]), __vimax3_u16x2(pr[5], pr[6], pr[7]));
            m = (max(m, m << 16) & 0xFFFF0000u) | (uint32_t)lane;
            const uint32_t m1 = __reduce_max_sync(0xffffffffu, m), m2 = __reduce_max_sync(0xffffffffu, m == m1 ? 0u : m);
            uint32_t* keys = reinterpret_cast<uint32_t*>(smem + OFF_KEYS);
            if (lane == 0) keys[w] = m2;
            sts128(sb + OFF_XS + 4096 + at * 16, pr[0], pr[1], pr[2], pr[3]);
            sts128(sb + OFF_XS + 6144 + at * 16, pr[4], pr[5], pr[6], pr[7]);
            *reinterpret_cast<uint32_t*>(smem + OFF_G + 4 * (at & 63)) = g1;
            named_bar(2, 128);
            const uint4 th4 = *reinterpret_cast<const uint4*>(keys);
            const uint32_t th = (max(min(min(th4.x, th4.y), min(th4.z, th4.w)) >> 16, 1u) - 1u) * 0x00010001u;
            uint32_t mask = 0;
#pragma unroll
            for (int k = 7; k >= 0; k--) mask = mask * 2 + __vminu2(__vmaxu2(pr[k], th) ^ th, 0x00010001u);
            uint32_t pos = 0;
            asm volatile("{ .reg .pred p; setp.ne.u32 p, %2, 0; @p atom.shared.add.u32 %0, [%1], %2; }" : "+r"(pos) : "r"(sb + OFF_KEYS + 16), "r"(__popc(mask)) : "memory");
            while (mask) {
                const int bit = __ffs(mask) - 1, k = bit & 7, hi = bit >> 4;
                mask &= mask - 1;
                const uint32_t sc = *reinterpret_cast<const uint16_t*>(smem + OFF_XS + 4096 + (k >> 2) * 2048 + at * 16 + (k & 3) * 4 + hi * 2);
                *reinterpret_cast<uint32_t*>(smem + OFF_LIST + 4 * pos++) = (sc << 16) | (0x8000u + 2047u - (uint32_t)((k >> 1) * 512 + 4 * at + 2 * (k & 1) + hi));
            }
            __syncwarp();
            if (lane == 0) mbar_arrive(bar_cand);
            STAMPIF(lane == 0, 26);
            mbar_wait(bar_order0);
        }

        float accA[64], accB[64];
        Ring ring = {bar_dummy, wg};
        {
            run_entries<0, 0>(ring, wg * 16, wg ? GU0 : RE0, accA, accB, facc, true);
            if (wg == 0) {
                float racc[4];
                mbar_wait(bar_vec);
                run_entries<0, 1>(ring, RE0, RE0 + 4, accA, accB, racc, false, true);
                mbar_wait(bar_init2);
                const uint32_t red = sb + OFF_RED + 4 * (w * 32 + (c >> 1) * 16 + g);
                run_entries<0, 0>(ring, RE0 + 4, RE0 + 5, accA, accB, facc, false, false, [&]() {
                    pin4(racc);
                    asm volatile("{ .reg .pred p; setp.ne.u32 p, %3, 0; @p st.shared.f32 [%0], %1; @p st.shared.f32 [%0 + 32], %2; }" ::"r"(red),
                                 "f"((w & 1) ? racc[1] : racc[0]), "f"((w & 1) ? racc[3] : racc[2]), "r"((uint32_t)((c & 1) == (w >> 1))) : "memory");
                    __syncwarp();
                    if (lane == 0) mbar_arrive(bar_rdone);
                    STAMPIF(lane == 0, 5);
                });
                run_entries<0, 0>(ring, RE0 + 5, 16, accA, accB, facc);
                if (lane == 0) mbar_arrive(bar_order0);
                mbar_wait(bar_init3);
                load_const();
                named_bar(3, 128);
            } else {
#pragma unroll
                for (int u = 0; u < 2; u++) {
                    mbar_wait(u ? bar_xs : bar_xs0);
                    run_entries<0, 2>(ring, GU0 + 8 * u, u ? 32 : GU0 + 8, accA, accB, facc, false, u == 0);
                }
                if (lane == 0) mbar_arrive(bar_order1);
            }
        }
        const uint32_t tag = *reinterpret_cast<volatile uint32_t*>(smem + OFF_EPOCH) + 1;
        const float2 a64[2] = {cmul(a32[0], a32[0]), cmul(a32[1], a32[1])};
        wgmma_wait<0>();
        pin64(accA); pin64(accB); pin4(facc);
        if (lane == 0) mbar_arrive(ring.prev);
        STAMPIF(at == 0, 28 + wg);
        GSTAMP(tid == 0, 1);
        LP(1);

        const int tl = 32 * (g >> 1) + (g & 1) + 4 * w + 16 * wg, t0 = chunk * 128 + tl;
        float* op = prm.out + (size_t)t0 * D_ + dt * 128 + 4 * c;
        uint2 xv[8][2], dk[8];
        uint32_t gp[2], om[2], routed[2];
        auto row_setup = [&]() {
            const uint4 sa = *reinterpret_cast<const uint4*>(smem + OFF_SEL), sc = *reinterpret_cast<const uint4*>(smem + OFF_SEL + 16);
#pragma unroll
            for (int r = 0; r < 2; r++) {
                const uint32_t id = 0x8000u + 2047u - (uint32_t)(t0 + 2 * r);
                routed[r] = (uint16_t)sa.x == id || (uint16_t)sa.y == id || (uint16_t)sa.z == id || (uint16_t)sa.w == id ||
                            (uint16_t)sc.x == id || (uint16_t)sc.y == id || (uint16_t)sc.z == id || (uint16_t)sc.w == id;
                gp[r] = reinterpret_cast<const uint16_t*>(smem + OFF_G)[tl + 2 * r] * 0x00010001u;
                om[r] = pack_bf(1.0f - bf_hi(gp[r]), 1.0f - bf_hi(gp[r]));
            }
#pragma unroll
            for (int j = 0; j < 8; j++) dk[j] = lds64(sb + OFF_DK + 32 * j + 8 * c);
        };
        auto release = [&](uint32_t bar) {
            asm volatile("fence.proxy.async.shared::cta;" ::: "memory");
            __syncwarp();
            if (lane == 0) mbar_arrive(bar);
        };

        {
            const uint32_t t2 = tag & 3u;
            float2* cslot = &prm.s->carry[(wg * 512 + dt * 32 + w * 8 + g) * 4];
            const int j1 = chunk - 1 - c;
            unsigned long long v[2][4] = {{t2, t2, t2, t2}, {t2, t2, t2, t2}};
            auto poll = [&](int h) {
#pragma unroll
                for (int m = 0; m < 4; m++)
                    asm volatile("{ .reg .pred p; setp.ge.s32 p, %2, %3; @p ld.relaxed.gpu.global.b64 %0, [%1]; }"
                                 : "+l"(v[h][m]) : "l"(cslot + (j1 >> 2) * 4096 + c - m * 4096 + h * 1024), "r"(j1), "r"(4 * m) : "memory");
            };
            float2 e[2], w0[2];
            auto chain = [&](int h, int s0, int s1) {
                float (&acc)[64] = h ? accB : accA;
                if (s0 == 1) e[h] = make_float2(acc[0], acc[2]);
#pragma unroll
                for (int s = s0; s < s1; s++) {
                    const int i0 = 4 * (s >> 1) + (s & 1);
                    e[h] = cfma(make_float2(a[h].x, -a[h].y), e[h], make_float2(acc[i0], acc[i0 + 2]));
                }
                asm volatile("" : "+f"(e[h].x), "+f"(e[h].y), "+f"(accB[0]), "+f"(accB[2]));
                gap();
            };
            auto publish = [&](int h) {
                float2 f = make_float2(fmaf(m0[h].x, e[h].x, m0[h].y * e[h].y), fmaf(-m0[h].x, e[h].y, m0[h].y * e[h].x));
                float2 y = make_float2(__shfl_up_sync(0xffffffffu, f.x, 1, 4), __shfl_up_sync(0xffffffffu, f.y, 1, 4));
                if (c >= 1) f = cfma(a32[h], y, f);
                y = make_float2(__shfl_up_sync(0xffffffffu, f.x, 2, 4), __shfl_up_sync(0xffffffffu, f.y, 2, 4));
                if (c >= 2) f = cfma(a64[h], y, f);
                asm volatile("{ .reg .pred p; .reg .b64 t; setp.eq.u32 p, %3, 3; mov.b64 t, {%1, %2}; @p st.relaxed.gpu.global.b64 [%0], t; }"
                             ::"l"(cslot + (chunk >> 2) * 4096 + (chunk & 3) + h * 1024), "r"((__float_as_uint(f.x) & ~3u) | t2), "r"(__float_as_uint(f.y)), "r"(c) : "memory");
                w0[h] = make_float2(__shfl_up_sync(0xffffffffu, f.x, 1, 4), __shfl_up_sync(0xffffffffu, f.y, 1, 4));
                if (c == 0) w0[h] = make_float2(0.f, 0.f);
            };
            auto scale = [&](int h, int n0, int n1) {
                float (&acc)[64] = h ? accB : accA;
#pragma unroll
                for (int n = n0; n < n1; n++) {
                    asm volatile("{ .reg .f32 a, b, c, d, n; neg.f32 n, %4; mul.f32 a, %1, %5; mul.f32 b, %0, %5; mul.f32 c, %3, %5; mul.f32 d, %2, %5;\n"
                                 "fma.rn.f32 %0, %0, %4, a; fma.rn.f32 %1, %1, n, b; fma.rn.f32 %2, %2, %4, c; fma.rn.f32 %3, %3, n, d; }"
                                 : "+f"(acc[4 * n]), "+f"(acc[4 * n + 2]), "+f"(acc[4 * n + 1]), "+f"(acc[4 * n + 3]) : "f"(m0[h].x), "f"(m0[h].y));
                    gap();
                }
            };
            auto carry = [&](int h) {
                const float2 one = make_float2(1.f, 0.f), a256 = cmul(a128[h], a128[h]);
                float2 a512 = cmul(a256, a256), pw128 = cmul((j1 & 1) ? a128[h] : one, (j1 & 2) ? a256 : one);
                float2 pw32 = cmul((c & 1) ? a32[h] : one, (c & 2) ? a64[h] : one);
                asm volatile("" : "+f"(a512.x), "+f"(a512.y), "+f"(pw128.x), "+f"(pw128.y), "+f"(pw32.x), "+f"(pw32.y));
                STAMPIF(lane == 0 && !h, 34 + 2 * wg);
                uint32_t it = 0;
                while (!__all_sync(0xffffffffu, ((((uint32_t)v[h][0] ^ t2) | ((uint32_t)v[h][1] ^ t2) | ((uint32_t)v[h][2] ^ t2) | ((uint32_t)v[h][3] ^ t2)) & 3u) == 0)) {
                    poll(h);
                    if (++it > SPIN_LIMIT) __trap();
                }
                STAMPIF(lane == 0 && !h, 35 + 2 * wg);
                float2 hin = make_float2(__uint_as_float((uint32_t)v[h][3]), __uint_as_float((uint32_t)(v[h][3] >> 32)));
#pragma unroll
                for (int m = 2; m >= 0; m--) hin = cfma(a512, hin, make_float2(__uint_as_float((uint32_t)v[h][m]), __uint_as_float((uint32_t)(v[h][m] >> 32))));
                hin = cmul(pw128, hin);
                hin.x += __shfl_xor_sync(0xffffffffu, hin.x, 1); hin.y += __shfl_xor_sync(0xffffffffu, hin.y, 1);
                hin.x += __shfl_xor_sync(0xffffffffu, hin.x, 2); hin.y += __shfl_xor_sync(0xffffffffu, hin.y, 2);
                w0[h] = cfma(pw32, hin, w0[h]);
            };
            chain(0, 1, 32);
            publish(0);
            chain(1, 1, 8);
            STAMPIF(lane == 0, 30 + 2 * wg);
            chain(1, 8, 32);
            publish(1);
            gap();
            scale(0, 0, POLL_S);
            poll(0);
            scale(0, POLL_S, 16);
            carry(0);
            if (wg) mbar_wait(bar_out + 24);
            STAMPIF(lane == 0, 38 + 2 * wg);
            const uint32_t stg = sb + OFF_STG + prm.swapped * 8192 + w * 1024 + (lane & 7) * 128 + (((lane >> 3) ^ (lane & 7)) << 4);
            const uint32_t second = prm.swapped ? -8192 : 8192;
            uint32_t hold = prm.swapped >> 1, last[8];
            const uint32_t keep = c == (g >> 1) ? 0xFFFEFFFEu : 0xFFFFFFFFu, tagw = ((t2 & 1) | ((t2 & 2) << 15)) & ~keep;
#pragma unroll
            for (int h = 0; h < 2; h++) {
                float (&acc)[64] = h ? accB : accA;
                uint32_t ra[16], ia[16];
                if (h) {
                    scale(1, 0, 4);
#pragma unroll
                    for (int u = 0; u < 4; u++) asm volatile("lop3.b32 %0, %0, %1, %2, 0x80;" : "+r"(hold) : "r"(last[u]), "r"(last[4 + u]));
                    release(bar_st + 32 * wg + 8 + hold);
                    poll(1);
                    scale(1, 4, 16);
                    mbar_wait(bar_xs);
                    row_setup();
                    carry(1);
                }
                auto stage = [&](uint32_t (&r)[16], uint32_t base, int j) {
                    stsm4((base ^ ((j & 1) * 64)) + (j >> 1) * 4096, r[4 * j], r[4 * j + 1], r[4 * j + 2], r[4 * j + 3]);
                };
#pragma unroll
                for (int n = 0; n < 16; n++) {
                    const float2 y = cfma(a[h], w0[h], make_float2(acc[4 * n], acc[4 * n + 2]));
                    w0[h] = cfma(a[h], y, make_float2(acc[4 * n + 1], acc[4 * n + 3]));
                    ra[n] = pack_bf(y.x, w0[h].x);
                    ia[n] = pack_bf(y.y, w0[h].y);
                    if (!(n & 1)) { ra[n] = (ra[n] & keep) | tagw; ia[n] = (ia[n] & keep) | tagw; }
                    if (!h && (n & 3) == 3) {
                        if (n > 3) {
                            gap();
#pragma unroll
                            for (int u = n - 7; u < n - 3; u++) asm volatile("lop3.b32 %0, %0, %1, %2, 0x80;" : "+r"(hold) : "r"(ra[u]), "r"(ia[u]));
                        }
                        if (n == 15) {
#pragma unroll
                            for (int u = 0; u < 4; u++) { last[u] = ra[12 + u]; last[4 + u] = ia[12 + u]; }
                        }
                        if (n == 11) { asm volatile("" : "+r"(ra[n]), "+r"(ia[n])); gap(); release(bar_st + 32 * wg); }
                        stage(ra, stg, n >> 2); stage(ia, stg + second, n >> 2);
                        gap();
                    }
                }
                if (h) {
                    STAMPIF(lane == 0, 39 + 2 * wg);
                    mbar_wait(bar_out + 32 * wg);
                    if (prm.swapped) {
#pragma unroll
                        for (int n = 0; n < 16; n++) { const uint32_t t = ra[n]; ra[n] = ia[n]; ia[n] = t; }
                    }
                    const uint32_t st0 = stg - prm.swapped * 8192;
#pragma unroll
                    for (int j = 0; j < 4; j++) stage(ra, st0, j);
                    release(bar_st + 32 * wg + 16);
                    mbar_wait(bar_out + 32 * wg + 8);
#pragma unroll
                    for (int j = 0; j < 4; j++) stage(ia, st0 + 8192, j);
                    release(bar_st + 32 * wg + 24);
                }
                STAMPIF(lane == 0, 42 + 2 * wg + h);
            }
        }

        const uint32_t xr = 2 * (g & 3) + (g >> 2), xa = sb + (wg ? OFF_STG : OFF_W) + (16 * w + xr) * 128 + (((c >> 1) ^ xr) << 4) + (c & 1) * 8;
        auto handover = [&](uint32_t bar) {
            const uint4 z = ldsm4(sb + OFF_KEYS + 16);
            if (lane == 1) mbar_arrive(bar + z.x);
        };
        auto load_x = [&](int j0, int j1) {
#pragma unroll
            for (int j = j0; j < j1; j++)
#pragma unroll
                for (int r = 0; r < 2; r++) xv[j][r] = lds64((xa ^ (32 * (j & 3))) + (j >> 2) * ABYTES + r * 1024);
        };
        auto skip_term = [&](int j0, int j1) {
#pragma unroll
            for (int j = j0; j < j1; j++)
#pragma unroll
                for (int r = 0; r < 2; r++) {
                    xv[j][r].x = mul_bf2(xv[j][r].x, fma_bf2(gp[r], dk[j].x, om[r]));
                    xv[j][r].y = mul_bf2(xv[j][r].y, fma_bf2(gp[r], dk[j].y, om[r]));
                    asm volatile("" : "+r"(xv[j][r].x), "+r"(xv[j][r].y));
                }
        };
        auto finish = [&](float (&acc)[64], int j, bool gaps) {
#pragma unroll
            for (int r = 0; r < 2; r++) {
                const int o = 8 * j + 2 * r;
                const float gv = bf_hi(gp[r]);
                acc[o] = fmaf(gv, acc[o], bf_lo(xv[j][r].x)); acc[o + 1] = fmaf(gv, acc[o + 1], bf_hi(xv[j][r].x));
                acc[o + 4] = fmaf(gv, acc[o + 4], bf_lo(xv[j][r].y)); acc[o + 5] = fmaf(gv, acc[o + 5], bf_hi(xv[j][r].y));
                stg4_unless(op + r * 2 * D_ + 16 * j, acc[o], acc[o + 1], acc[o + 4], acc[o + 5], routed[r]);
                if (gaps) gap();
            }
        };
        auto finish_routed = [&](float (&acc)[64]) {
#pragma unroll
            for (int r = 0; r < 2; r++)
                if (routed[r]) {
#pragma unroll
                    for (int j = 0; j < 8; j++) red4(op + r * 2 * D_ + 16 * j, acc[8 * j + 2 * r], acc[8 * j + 2 * r + 1], acc[8 * j + 2 * r + 4], acc[8 * j + 2 * r + 5]);
                }
            __syncwarp();
        };
        const uint32_t xbuf = sb + w * 2048 + lane * 16;

        if (wg == 1) {
            float outB[64];
            {
                sts128(sb + OFF_XS + at * 16, __float_as_uint(facc[0]), __float_as_uint(facc[1]), __float_as_uint(facc[2]), __float_as_uint(facc[3]));
                named_bar(2, 128);
                const uint32_t pg = sb + OFF_XS + prm.up_first * 1024 + (at & 63) * 16 + (w >> 1) * 8, pu = pg + 1024 - prm.up_first * 2048;
                const uint2 g1 = lds64(pg), u1 = lds64(pu);
                uint4* hp = prm.s->hid + cta * 32 - 512 + 16 * (w & 1) + 8 * (w >> 1) + g;
                asm volatile("" : "+l"(hp));
                mbar_wait(bar_fp);
                const uint2 g2 = lds64(pg + 2048), u2 = lds64(pu + 2048);
                const float ga = rbf(__uint_as_float(g1.x) + __uint_as_float(g2.x)), gb = rbf(__uint_as_float(g1.y) + __uint_as_float(g2.y));
                uint32_t hw = mul_bf2(pack_bf(__fdividef(ga, 1.0f + __expf(-ga)), __fdividef(gb, 1.0f + __expf(-gb))),
                                      pack_bf(__uint_as_float(u1.x) + __uint_as_float(u2.x), __uint_as_float(u1.y) + __uint_as_float(u2.y)));
                if (c == 2 * (w & 1) + (w >> 1)) hw = (hw & 0xFFFEFFFEu) | (tag & 1) | ((tag & 2) << 15);
                st_cell(hp, hw, __shfl_down_sync(0xffffffffu, hw, 1), __shfl_down_sync(0xffffffffu, hw, 2), __shfl_down_sync(0xffffffffu, hw, 3), has_gu && c == 0);
            }
            STAMPIF(lane == 0, 47);
            mbar_wait(bar_xb);
            load_x(0, 8);
            release(bar_xbfree);
            skip_term(0, 8);
            STAMPIF(lane == 0, 46);
            mbar_wait(bar_order2);
            static_for<NENT - FIN>([&](auto u) {
                run_small<1, FIN + u>(outB);
                if (u == FE) { wgmma_wait<2>(); if (lane == 0) mbar_arrive(bar_fold); }
            });
            wgmma_wait<0>();
            pin64(outB);
            KSTAMP(2 * NENT - FIN);
            STAMPIF(at == 0, 50);
            LT(0);
#pragma unroll
            for (int q = 0; q < 2; q++) {
                uint4 pb[16];
                mbar_wait(bar_accb + 8 * q);
                if (q) LT(1);
#pragma unroll
                for (int v = q * HP; v < (q ? 16 : HP); v++) pb[v] = ldsm4(xbuf + sum_off(v));
#pragma unroll
                for (int v = q * HP; v < (q ? 16 : HP); v++) {
                    outB[4 * v] += __uint_as_float(pb[v].x); outB[4 * v + 1] += __uint_as_float(pb[v].y);
                    outB[4 * v + 2] += __uint_as_float(pb[v].z); outB[4 * v + 3] += __uint_as_float(pb[v].w);
                    if (v & 1) finish(outB, v >> 1, false);
                    if (v == DV) { gap(); if (lane == 0) mbar_expect_tx(bar_dn, w ? 0 : 7 * ABYTES); }
                }
            }
            finish_routed(outB);
            STAMPIF(lane == 0, 51);
            LT(2);
        } else {
            float outA[64], outB[64], gacc[4];
            ring.slot = 32 % NST;
            ring.prev = bar_dummy;
            mbar_wait(bar_order1);
            run_entries<1, 2>(ring, 32, GU0 + 32, outA, outB, gacc, true, true);
            run_entries<1, 0>(ring, GU0 + 32, GU0 + 33, outA, outB, gacc, false, false, [&]() {
                LP(2);
                pin4(gacc);
                sts128(sb + OFF_XS + 2048 + at * 16, __float_as_uint(gacc[0]), __float_as_uint(gacc[1]), __float_as_uint(gacc[2]), __float_as_uint(gacc[3]));
                __syncwarp();
                if (lane == 0) mbar_arrive(bar_fp);
            });
            mbar_wait(bar_xa);
            load_x(0, 2);
            run_entries<1, 0>(ring, GU0 + 33, GU0 + 34, outA, outB, gacc, false, false, [&]() { load_x(2, 3); });
            load_x(3, 5);
            run_entries<1, 0>(ring, GU0 + 34, GU0 + 35, outA, outB, gacc, false, false, [&]() { load_x(5, 6); });
            load_x(6, 8);
            run_entries<1, 0>(ring, GU0 + 35, GU0 + 36, outA, outB, gacc, false, false, [&]() { handover(bar_xafree); });
            skip_term(0, 3);
            run_entries<1, 0>(ring, GU0 + 36, GU0 + 37, outA, outB, gacc, false, false, [&]() { skip_term(3, 5); });
            skip_term(5, 8);
            run_entries<1, 0>(ring, GU0 + 37, FIN, outA, outB, gacc);
            auto dump = [&](int v) {
                stsm4(xbuf + sum_off(v), __float_as_uint(outB[4 * v]), __float_as_uint(outB[4 * v + 1]), __float_as_uint(outB[4 * v + 2]),
                      __float_as_uint(outB[4 * v + 3]));
            };
            static_for<NENT - FIN>([&](auto u) {
                mbar_wait(full + 8 * (FIN + u));
                run_small<0, FIN + u>(outA);
                if (u == 5 && lane == 0) mbar_arrive(bar_order2);
                wgmma_wait<1>();
                if (lane == 0) mbar_arrive(empty + 8 * (FIN + u - 1));
                if (u == 0) { pin64(outB); LP(3); }
                if (u == 2) mbar_wait(empty + 8 * FIN);
                if (u >= 2) dump(u - 2);
            });
            const uint2 sk = lds64(sb + OFF_SEL + 8 * c), fk = lds64(sb + OFF_FAC + 8 * c);
            float* y0 = prm.out + (~sk.x & 2047u) * D_ + (cta & 15) * 64 + w * 16 + g;
            float* y1 = prm.out + (~sk.y & 2047u) * D_ + (cta & 15) * 64 + w * 16 + g;
            asm volatile("" : "+l"(y0), "+l"(y1));
            handover(bar_accb);
            wgmma_wait<0>();
            pin64(outA);
            STAMPIF(at == 0, 53);
            GSTAMP(at == 0, 2);
#pragma unroll
            for (int j = 0; j < 8; j++) {
                finish(outA, j, true);
            }
            STAMPIF(lane == 0, 54);
            LT(0);
            mbar_wait(bar_fold);
#pragma unroll
            for (int v = 4; v < 16; v++) dump(v);
            handover(bar_accb + 8);
            STAMPIF(lane == 0, 55);
            finish_routed(outA);
            float yacc[4];
            const uint64_t dw = make_desc(sb), dh = (uint64_t)(((sb + OFF_XS) & 0x3FFFF) >> 4) | ((uint64_t)8 << 16) | ((uint64_t)8 << 32);
            mbar_wait(bar_zero);
            mbar_wait(bar_dn);
            STAMPIF(at == 0, 2);
            LT(1);
            wgmma_fence();
#pragma unroll
            for (int n = 0; n < 28; n++) wgmma_n8<1, 1>(yacc, dw + (dn_off(n >> 2) >> 4) + (n & 3) * 128, dh + n * 16, n > 0);
            wgmma_commit();
            wgmma_wait<0>();
            pin4(yacc);
            LT(2);
            asm volatile("red.global.add.f32 [%0], %2; red.global.add.f32 [%1], %3; red.global.add.f32 [%0 + 32], %4; red.global.add.f32 [%1 + 32], %5;"
                         ::"l"(y0), "l"(y1), "f"(yacc[0] * __uint_as_float(fk.x)), "f"(yacc[1] * __uint_as_float(fk.y)), "f"(yacc[2] * __uint_as_float(fk.x)),
                         "f"(yacc[3] * __uint_as_float(fk.y)) : "memory");
            STAMPIF(lane == 0, 3);
            LT(3);
        }
    }
}

typedef CUresult (*EncodeFn)(CUtensorMap*, CUtensorMapDataType, cuuint32_t, void*, const cuuint64_t*, const cuuint64_t*, const cuuint32_t*,
                             const cuuint32_t*, CUtensorMapInterleave, CUtensorMapSwizzle, CUtensorMapL2promotion, CUtensorMapFloatOOBfill);

bool encode(EncodeFn fn, CUtensorMap* m, const void* ptr, int rank, const cuuint64_t* dims, const cuuint64_t* strides, const cuuint32_t* box,
            CUtensorMapSwizzle sw = CU_TENSOR_MAP_SWIZZLE_128B, CUtensorMapL2promotion promo = CU_TENSOR_MAP_L2_PROMOTION_NONE) {
    const cuuint32_t es[5] = {1, 1, 1, 1, 1};
    return fn(m, CU_TENSOR_MAP_DATA_TYPE_BFLOAT16, rank, const_cast<void*>(ptr), dims, strides, box, es, CU_TENSOR_MAP_INTERLEAVE_NONE,
              sw, promo, CU_TENSOR_MAP_FLOAT_OOB_FILL_NONE) == CUDA_SUCCESS;
}

}

extern "C" void kernel_launch(void* const* d_in, const int* in_sizes, int n_in, void* d_out, int out_size) {
    (void)in_sizes; (void)n_in; (void)out_size;
    Params prm;
    prm.x = (const __nv_bfloat16*)d_in[0];
    prm.lam_re = (const __nv_bfloat16*)d_in[1];
    prm.lam_im = (const __nv_bfloat16*)d_in[2];
    prm.b_re = (const __nv_bfloat16*)d_in[3];
    prm.b_im = (const __nv_bfloat16*)d_in[4];
    prm.c_re = (const __nv_bfloat16*)d_in[5];
    prm.c_im = (const __nv_bfloat16*)d_in[6];
    prm.log_dt = (const __nv_bfloat16*)d_in[7];
    prm.dskip = (const __nv_bfloat16*)d_in[8];
    prm.w_r = (const __nv_bfloat16*)d_in[10];
    prm.gate_w = (const __nv_bfloat16*)d_in[14];
    prm.out = (float*)d_out;
    cudaGetSymbolAddress((void**)&prm.s, g_scratch);
    int dev = 0, sms = 0;
    cudaGetDevice(&dev);
    cudaDeviceGetAttribute(&sms, cudaDevAttrMultiProcessorCount, dev);
    auto kernel = sms == NGRID ? fused_kernel<true> : fused_kernel<false>;
    prm.swapped = prm.b_im < prm.b_re;

    void* fnp = nullptr;
    cudaDriverEntryPointQueryResult qr;
    cudaGetDriverEntryPoint("cuTensorMapEncodeTiled", &fnp, cudaEnableDefault, &qr);
    EncodeFn fn = (EncodeFn)fnp;
    cudaFuncSetAttribute(kernel, cudaFuncAttributeMaxDynamicSharedMemorySize, SMEM_BYTES);

    CUtensorMap mX, mB, mCre, mCim, mW, mWd, mXr, mXe;
    const cuuint64_t row = 2048;
    {
        const cuuint64_t dims[4] = {1024, 2, 4, 976}, st[3] = {row, 32 * row, 2 * row};
        const cuuint32_t box[4] = {64, 2, 4, 16};
        encode(fn, &mX, prm.x, 4, dims, st, box, CU_TENSOR_MAP_SWIZZLE_128B, PROMO);
    }
    {
        const char *lo = (const char*)(prm.swapped ? prm.b_im : prm.b_re), *hi = (const char*)(prm.swapped ? prm.b_re : prm.b_im);
        const cuuint64_t dims[5] = {1024, 8, 2, 96, 2}, st[4] = {row, (cuuint64_t)(hi - lo), 8 * row, 256 * row};
        const cuuint32_t box[5] = {64, 8, 2, 4, 2};
        encode(fn, &mB, lo, 5, dims, st, box, CU_TENSOR_MAP_SWIZZLE_128B, PROMO);
    }
    {
        const cuuint64_t dims[5] = {1024, 2, 4, 2, 64}, st[4] = {row, 4 * row, 2 * row, 16 * row};
        const cuuint32_t box[5] = {64, 2, 4, 2, 8};
        encode(fn, &mCre, prm.c_re, 5, dims, st, box);
        encode(fn, &mCim, prm.c_im, 5, dims, st, box);
    }
    {
        const char *pg = (const char*)d_in[11], *pu = (const char*)d_in[12];
        prm.up_first = pu < pg;
        const cuuint64_t dims[3] = {F_, D_, 2}, st[2] = {F_ * 2, (cuuint64_t)(pu < pg ? pg - pu : pu - pg)}, dimsd[2] = {D_, F_}, std_[1] = {row};
        const cuuint32_t box[3] = {32, 32, 2}, boxd[2] = {64, 64};
        encode(fn, &mW, pu < pg ? pu : pg, 3, dims, st, box, CU_TENSOR_MAP_SWIZZLE_64B, CU_TENSOR_MAP_L2_PROMOTION_NONE);
        encode(fn, &mWd, d_in[13], 2, dimsd, std_, boxd, CU_TENSOR_MAP_SWIZZLE_128B, CU_TENSOR_MAP_L2_PROMOTION_NONE);
    }
    {
        const cuuint64_t dims[3] = {D_ - 192, S_, 4}, st[2] = {row, 128};
        const cuuint32_t box[3] = {64, 16, 4};
        encode(fn, &mXr, prm.x, 3, dims, st, box, CU_TENSOR_MAP_SWIZZLE_128B, CU_TENSOR_MAP_L2_PROMOTION_NONE);
    }
    {
        const cuuint64_t dims[5] = {D_, 2, 2, 2, 976}, st[4] = {64 * row, row, 32 * row, 2 * row};
        const cuuint32_t box[5] = {64, 2, 2, 2, 8};
        encode(fn, &mXe, prm.x, 5, dims, st, box);
    }
    kernel<<<NGRID, 384, SMEM_BYTES, cudaStreamPerThread>>>(prm, mX, mB, mCre, mCim, mW, mWd, mXr, mXe);
}
```

```cpp
#include <cuda_runtime.h>
#include <cuda_bf16.h>
#include <cuda.h>
#include <stdint.h>

namespace {

constexpr int S_ = 2048, D_ = 1024, F_ = 3584;
constexpr int NCTA = 128, NGRID = 132;
constexpr int XE_ = 58;
constexpr int GU0_ = 18;
constexpr int NENT = 64, FIN = 58, XE = XE_;
constexpr int NST = 5;
constexpr int RE0 = 4;
constexpr int GU0 = GU0_;
constexpr uint32_t SLOT = 32768, ABYTES = 8192, WBYTES = 4096;
constexpr uint32_t OFF_XS = NST * SLOT;
constexpr uint32_t OFF_LIST = OFF_XS + 8192;
constexpr uint32_t OFF_W = OFF_XS + 16384;
constexpr uint32_t OFF_STG = OFF_W + 32768;
__host__ __device__ constexpr uint32_t slot_off(int i) { return i < XE ? (i % NST) * SLOT : i == XE ? OFF_W : ((i - 1) % NST) * SLOT; }
__host__ __device__ constexpr uint32_t dn_off(int u) { return u == 0 ? OFF_XS + ABYTES : u < 3 ? OFF_STG + (u - 1) * ABYTES : slot_off(FIN - 2 + u); }
__host__ __device__ constexpr uint32_t sum_off(int v) { return slot_off(FIN) + (v >> 2) * ABYTES + (v & 3) * 512; }
constexpr uint32_t OFF_CONST = OFF_STG;
constexpr uint32_t OFF_RED = OFF_STG + 4096;
constexpr uint32_t OFF_FULL = OFF_STG + 16384;
constexpr uint32_t OFF_EMPTY = OFF_FULL + 120 * 8;
constexpr uint32_t OFF_G = OFF_EMPTY + 88 * 8;
constexpr uint32_t OFF_DK = OFF_G + 256;
constexpr uint32_t OFF_KEYS = OFF_DK + 256;
constexpr uint32_t OFF_SEL = OFF_KEYS + 32;
constexpr uint32_t OFF_FAC = OFF_SEL + 32;
constexpr uint32_t OFF_EPOCH = OFF_FAC + 32;
constexpr uint32_t SMEM_BYTES = OFF_EPOCH + 16;
static_assert(SMEM_BYTES <= 232448, "smem");

constexpr uint32_t sb = 1024;
constexpr uint32_t SPIN_LIMIT = 1u << 18;

struct Scratch {
    unsigned int cnt[2 * 32];
    unsigned long long rpack[S_ / 2];
    unsigned long long gpack[S_ / 2];
    uint4 time[NCTA];
    float2 carry[16 * 1024];
    uint4 hid[F_];
    uint4 h[8 * 4 * 256 * 64];
};
__device__ __align__(128) Scratch g_scratch;

struct Params {
    const __nv_bfloat16 *x, *b_re, *b_im;
    Scratch* s;
    int up_first;
    int swapped;
    const __nv_bfloat16 *lam_re, *lam_im, *c_re, *c_im, *log_dt, *dskip, *w_r, *gate_w;
    float* out;
};

__device__ __forceinline__ uint32_t smem_u32(const void* p) { return (uint32_t)__cvta_generic_to_shared(p); }
__device__ __forceinline__ void mbar_init(uint32_t bar, uint32_t cnt) { asm volatile("mbarrier.init.shared::cta.b64 [%0], %1;" ::"r"(bar), "r"(cnt) : "memory"); }
__device__ __forceinline__ void mbar_expect_tx(uint32_t bar, uint32_t bytes) { asm volatile("mbarrier.arrive.expect_tx.shared::cta.b64 _, [%0], %1;" ::"r"(bar), "r"(bytes) : "memory"); }
__device__ __forceinline__ void mbar_arrive(uint32_t bar) { asm volatile("mbarrier.arrive.shared::cta.b64 _, [%0];" ::"r"(bar) : "memory"); }
__device__ __forceinline__ void mbar_wait(uint32_t bar, uint32_t parity = 0) {
    asm volatile("{ .reg .pred p; .reg .u32 n;\n"
                 "mov.u32 n, 0;\n"
                 "AGAIN: mbarrier.try_wait.parity.shared::cta.b64 p, [%0], %1;\n"
                 "@p bra.uni DONE;\n"
                 "add.u32 n, n, 1;\n"
                 "setp.lt.u32 p, n, %2;\n"
                 "@p bra.uni AGAIN;\n"
                 "trap;\n"
                 "DONE: }" ::"r"(bar), "r"(parity), "n"(SPIN_LIMIT) : "memory");
}
__device__ __forceinline__ bool elect_one() {
    uint32_t pred;
    asm volatile("{ .reg .pred P; elect.sync _|P, 0xffffffff; selp.b32 %0, 1, 0, P; }" : "=r"(pred));
    return pred;
}
__device__ __forceinline__ void named_bar(int id, int n) { asm volatile("bar.sync %0, %1;" ::"r"(id), "r"(n) : "memory"); }

#define ONE "{ .reg .pred e; elect.sync _|e, 0xffffffff;\n@e "
template <int N> __device__ __forceinline__ void mbar_init_n(uint32_t bar, uint32_t cnt, uint32_t extra = 0) {
    if (elect_one()) {
#pragma unroll
        for (int i = 0; i < N; i++) mbar_init(bar + 8 * i, i == N - 1 ? cnt + extra : cnt);
        asm volatile("fence.mbarrier_init.release.cluster;" ::: "memory");
    }
    __syncwarp();
}
__device__ __forceinline__ void bulk_load(uint32_t dst, const void* src, uint32_t bytes, uint32_t bar) {
    asm volatile(ONE "cp.async.bulk.shared::cluster.global.mbarrier::complete_tx::bytes [%0], [%1], %2, [%3]; }" ::"r"(dst), "l"(src), "r"(bytes), "r"(bar) : "memory");
}
__device__ __forceinline__ void sts128(uint32_t a, uint32_t x, uint32_t y, uint32_t z, uint32_t w) {
    asm volatile("st.shared.v4.u32 [%0], {%1,%2,%3,%4};" ::"r"(a), "r"(x), "r"(y), "r"(z), "r"(w) : "memory");
}
__device__ __forceinline__ uint2 lds64(uint32_t a) {
    uint2 v;
    asm volatile("ld.shared.v2.u32 {%0,%1}, [%2];" : "=r"(v.x), "=r"(v.y) : "r"(a) : "memory");
    return v;
}
__device__ __forceinline__ uint32_t clk32() { uint32_t c; asm volatile("mov.u32 %0, %%clock;" : "=r"(c)); return c; }
__device__ __forceinline__ void gap() { asm volatile("pmevent 1;" ::: "memory"); }
__device__ __forceinline__ void pace_until(uint32_t t) { while ((int)(clk32() - t) < 0) {} }
constexpr int SLEEP_MARGIN = 200;
__device__ __forceinline__ void sleep_until(uint32_t t) {
    while ((int)(clk32() + SLEEP_MARGIN - t) < 0) __nanosleep(40);
    pace_until(t);
}
__device__ __forceinline__ void tma2(uint32_t dst, const CUtensorMap* m, int c0, int c1, uint32_t bar, uint64_t pol) {
    asm volatile(ONE "cp.async.bulk.tensor.2d.shared::cluster.global.mbarrier::complete_tx::bytes.L2::cache_hint [%0], [%1, {%3, %4}], [%2], %5; }"
                 ::"r"(dst), "l"(m), "r"(bar), "r"(c0), "r"(c1), "l"(pol) : "memory");
}
__device__ __forceinline__ void tma3s(uint32_t dst, const CUtensorMap* m, int c0, int c1, uint32_t bar, uint64_t pol) {
    asm volatile(ONE "cp.async.bulk.tensor.3d.shared::cluster.global.mbarrier::complete_tx::bytes.L2::cache_hint [%0], [%1, {%3, %4, %5}], [%2], %6; }"
                 ::"r"(dst), "l"(m), "r"(bar), "r"(c0), "r"(c1), "r"(0), "l"(pol) : "memory");
}
__device__ __forceinline__ void tma3(uint32_t dst, const CUtensorMap* m, int c0, int c1, uint32_t bar) {
    asm volatile(ONE "cp.async.bulk.tensor.3d.shared::cluster.global.mbarrier::complete_tx::bytes [%0], [%1, {%3, %4, %5}], [%2]; }"
                 ::"r"(dst), "l"(m), "r"(bar), "r"(c0), "r"(c1), "r"(0) : "memory");
}
__device__ __forceinline__ void tma4(uint32_t dst, const CUtensorMap* m, int c0, int c3, uint32_t bar) {
    asm volatile(ONE "cp.async.bulk.tensor.4d.shared::cluster.global.mbarrier::complete_tx::bytes [%0], [%1, {%3, %5, %5, %4}], [%2]; }"
                 ::"r"(dst), "l"(m), "r"(bar), "r"(c0), "r"(c3), "r"(0) : "memory");
}
__device__ __forceinline__ void tma5(uint32_t dst, const CUtensorMap* m, int c0, int c4, uint32_t bar) {
    asm volatile(ONE "cp.async.bulk.tensor.5d.shared::cluster.global.mbarrier::complete_tx::bytes [%0], [%1, {%3, %5, %5, %5, %4}], [%2]; }"
                 ::"r"(dst), "l"(m), "r"(bar), "r"(c0), "r"(c4), "r"(0) : "memory");
}
__device__ __forceinline__ void tma5b(uint32_t dst, const CUtensorMap* m, int c0, int c3, uint32_t bar) {
    asm volatile(ONE "cp.async.bulk.tensor.5d.shared::cluster.global.mbarrier::complete_tx::bytes [%0], [%1, {%3, %5, %5, %4, %5}], [%2]; }"
                 ::"r"(dst), "l"(m), "r"(bar), "r"(c0), "r"(c3), "r"(0) : "memory");
}
__device__ __forceinline__ void prefetch_l2(const void* p) {
    asm volatile("cp.async.ca.shared.global.L2::256B [%0], [%1], 4;" ::"r"(sb + OFF_EPOCH + 12), "l"(p) : "memory");
}

__device__ __forceinline__ uint32_t lds32(uint32_t a) {
    uint32_t v;
    asm volatile("ld.volatile.shared.u32 %0, [%1];" : "=r"(v) : "r"(a) : "memory");
    return v;
}
__device__ __forceinline__ uint32_t uni(uint32_t v) { return __shfl_sync(0xffffffffu, v, 0); }   __device__ __forceinline__ uint32_t ld_acquire(const unsigned int* p) {
    uint32_t v;
    asm volatile("ld.acquire.gpu.global.u32 %0, [%1];" : "=r"(v) : "l"(p) : "memory");
    return v;
}
__device__ __forceinline__ void red_release(unsigned int* p) { asm volatile("red.release.gpu.global.add.u32 [%0], 1;" ::"l"(p) : "memory"); }
__device__ __forceinline__ void wait_count(const unsigned int* p, uint32_t target) {
#pragma unroll 1
    for (uint32_t it = 0; it < SPIN_LIMIT; ++it)
        if ((int)(ld_acquire(p) - target) >= 0) return;
    __trap();
}
__device__ __forceinline__ void wait_count_slow(const unsigned int* p, uint32_t target) {
#pragma unroll 1
    for (uint32_t it = 0; it < SPIN_LIMIT; ++it) {
        if ((int)(ld_acquire(p) - target) >= 0) return;
        __nanosleep(200);
    }
    __trap();
}
__device__ __forceinline__ unsigned long long ld_relaxed1(const void* p) {
    unsigned long long v;
    asm volatile("ld.relaxed.gpu.global.b64 %0, [%1];" : "=l"(v) : "l"(p) : "memory");
    return v;
}
__device__ __forceinline__ ulonglong2 ld_relaxed2(const void* p) {
    ulonglong2 v;
    asm volatile("ld.relaxed.gpu.global.v2.b64 {%0, %1}, [%2];" : "=l"(v.x), "=l"(v.y) : "l"(p) : "memory");
    return v;
}
__device__ __forceinline__ void ld_cell(uint32_t (&v)[4], const void* p, bool on = true) {
    asm volatile("{ .reg .pred p; .reg .b64 l, h; .reg .b128 t; setp.ne.u32 p, %5, 0; mov.b64 l, {%0, %1}; mov.b64 h, {%2, %3}; mov.b128 t, {l, h};\n"
                 "@p ld.relaxed.gpu.global.b128 t, [%4]; mov.b128 {l, h}, t; mov.b64 {%0, %1}, l; mov.b64 {%2, %3}, h; }"
                 : "+r"(v[0]), "+r"(v[1]), "+r"(v[2]), "+r"(v[3]) : "l"(p), "r"((uint32_t)on) : "memory");
}
__device__ __forceinline__ void st_cell(void* p, uint32_t a, uint32_t b, uint32_t c, uint32_t d, bool on) {
    asm volatile("{ .reg .pred p; .reg .b64 l, h; .reg .b128 t; setp.ne.u32 p, %5, 0; mov.b64 l, {%1, %2}; mov.b64 h, {%3, %4}; mov.b128 t, {l, h};\n"
                 "@p st.relaxed.gpu.global.b128 [%0], t; }" ::"l"(p), "r"(a), "r"(b), "r"(c), "r"(d), "r"((uint32_t)on) : "memory");
}

__device__ __forceinline__ uint64_t make_desc(uint32_t addr, uint32_t sbo = 1024) {
    return (uint64_t)((addr & 0x3FFFF) >> 4) | ((uint64_t)1 << 16) | ((uint64_t)(sbo >> 4) << 32) | ((uint64_t)1 << 62);
}
__device__ __forceinline__ void wgmma_fence() { asm volatile("wgmma.fence.sync.aligned;" ::: "memory"); }
__device__ __forceinline__ void wgmma_commit() { asm volatile("wgmma.commit_group.sync.aligned;" ::: "memory"); }
template <int N> __device__ __forceinline__ void wgmma_wait() { asm volatile("wgmma.wait_group.sync.aligned %0;" ::"n"(N) : "memory"); }

#define R8(d, i) "+f"(d[i]), "+f"(d[i + 1]), "+f"(d[i + 2]), "+f"(d[i + 3]), "+f"(d[i + 4]), "+f"(d[i + 5]), "+f"(d[i + 6]), "+f"(d[i + 7])
#define R64(d) R8(d, 0), R8(d, 8), R8(d, 16), R8(d, 24), R8(d, 32), R8(d, 40), R8(d, 48), R8(d, 56)
template <int TA>
__device__ __forceinline__ void wgmma_n128(float (&d)[64], uint64_t da, uint64_t db, int scale_d = 1) {
    asm volatile("{ .reg .pred p; setp.ne.b32 p, %66, 0;\n"
                 "wgmma.mma_async.sync.aligned.m64n128k16.f32.bf16.bf16 "
                 "{%0,%1,%2,%3,%4,%5,%6,%7,%8,%9,%10,%11,%12,%13,%14,%15,%16,%17,%18,%19,%20,%21,%22,%23,%24,%25,%26,%27,%28,%29,%30,%31,"
                 "%32,%33,%34,%35,%36,%37,%38,%39,%40,%41,%42,%43,%44,%45,%46,%47,%48,%49,%50,%51,%52,%53,%54,%55,%56,%57,%58,%59,%60,%61,%62,%63}, "
                 "%64, %65, p, 1, 1, %67, 0; }"
                 : R64(d)
                 : "l"(da), "l"(db), "r"(scale_d), "n"(TA));
}
__device__ __forceinline__ void pin4(float (&d)[4]) { asm volatile("" : "+f"(d[0]), "+f"(d[1]), "+f"(d[2]), "+f"(d[3])::"memory"); }
__device__ __forceinline__ void pin64(float (&d)[64]) { asm volatile("" : R64(d)::"memory"); }

template <int TA, int TB = 0>
__device__ __forceinline__ void wgmma_n8(float (&d)[4], uint64_t da, uint64_t db, int scale_d = 1) {
    asm volatile("{ .reg .pred p; setp.ne.b32 p, %7, 0;\n"
                 "wgmma.mma_async.sync.aligned.m64n8k16.f32.bf16.bf16 {%0,%1,%2,%3}, %4, %5, p, 1, 1, %6, %8; }"
                 : "+f"(d[0]), "+f"(d[1]), "+f"(d[2]), "+f"(d[3])
                 : "l"(da), "l"(db), "n"(TA), "r"(scale_d), "n"(TB));
}

__device__ __forceinline__ float bf_lo(uint32_t u) { return __uint_as_float(u << 16); }
__device__ __forceinline__ float bf_hi(uint32_t u) { return __uint_as_float(u & 0xFFFF0000u); }
__device__ __forceinline__ float rbf(float v) { return __bfloat162float(__float2bfloat16_rn(v)); }
__device__ __forceinline__ uint32_t pack_bf(float lo, float hi) {
    uint32_t r;
    asm("cvt.rn.bf16x2.f32 %0, %1, %2;" : "=r"(r) : "f"(hi), "f"(lo));
    return r;
}
__device__ __forceinline__ uint32_t mul_bf2(uint32_t a, uint32_t b) {
    __nv_bfloat162 r = __hmul2(*reinterpret_cast<__nv_bfloat162*>(&a), *reinterpret_cast<__nv_bfloat162*>(&b));
    return *reinterpret_cast<uint32_t*>(&r);
}
__device__ __forceinline__ uint32_t fma_bf2(uint32_t a, uint32_t b, uint32_t c) {
    uint32_t r;
    asm("fma.rn.bf16x2 %0, %1, %2, %3;" : "=r"(r) : "r"(a), "r"(b), "r"(c));
    return r;
}
__device__ __forceinline__ float2 cmul(float2 a, float2 b) { return make_float2(a.x * b.x - a.y * b.y, a.x * b.y + a.y * b.x); }
__device__ __forceinline__ float2 cfma(float2 a, float2 b, float2 c) {
    return make_float2(fmaf(a.x, b.x, fmaf(-a.y, b.y, c.x)), fmaf(a.x, b.y, fmaf(a.y, b.x, c.y)));
}
__device__ __forceinline__ float sigmoidf_(float v) { return __fdividef(1.0f, 1.0f + expf(-v)); }

__device__ __forceinline__ void bulk_prefetch(const void* src, uint32_t bytes) {
    asm volatile(ONE "cp.async.bulk.prefetch.L2.global [%0], %1; }" ::"l"(src), "r"(bytes) : "memory");
}
__device__ __forceinline__ void bulk_store(void* dst, uint32_t src, uint32_t bytes) {
    asm volatile(ONE "cp.async.bulk.global.shared::cta.bulk_group [%0], [%1], %2; }" ::"l"(dst), "r"(src), "r"(bytes) : "memory");
}
__device__ __forceinline__ void stsm4(uint32_t a, uint32_t x, uint32_t y, uint32_t z, uint32_t w) {
    asm volatile("stmatrix.sync.aligned.m8n8.x4.shared.b16 [%0], {%1,%2,%3,%4};" ::"r"(a), "r"(x), "r"(y), "r"(z), "r"(w) : "memory");
}
__device__ __forceinline__ uint4 ldsm4(uint32_t a) {
    uint4 v;
    asm volatile("ldmatrix.sync.aligned.m8n8.x4.shared.b16 {%0,%1,%2,%3}, [%4];" : "=r"(v.x), "=r"(v.y), "=r"(v.z), "=r"(v.w) : "r"(a) : "memory");
    return v;
}
__device__ __forceinline__ void stg4_unless(float* p, float a, float b, float c, float d, uint32_t skip) {
    asm volatile("{ .reg .pred p; setp.eq.u32 p, %5, 0; @p st.global.v4.f32 [%0], {%1,%2,%3,%4}; }" ::"l"(p), "f"(a), "f"(b), "f"(c), "f"(d), "r"(skip) : "memory");
}
__device__ __forceinline__ void red4(float* p, float a, float b, float c, float d) {
    asm volatile("red.global.add.v4.f32 [%0], {%1,%2,%3,%4};" ::"l"(p), "f"(a), "f"(b), "f"(c), "f"(d) : "memory");
}

constexpr int TT0 = 2900;
constexpr int PER = 510;
constexpr int PCUT = 60;
constexpr int PFIN = 360;
constexpr int PF0 = 1500;
constexpr int PFX_PACE = 400;
constexpr int PF1 = 700;
constexpr int T2 = 300;
constexpr int P2 = 520;
constexpr int G0 = 450;
constexpr int R0 = 1900;
constexpr int R_PACE = 250;
constexpr int W_SHIFT = 250;
#define PROMO CU_TENSOR_MAP_L2_PROMOTION_L2_256B
constexpr int POLL_S = 0;
constexpr int ST_TOL = 100;
constexpr int ST_SHIFT = 300;
constexpr int CLK_NS = 420;
constexpr int MARGIN = 60;
constexpr int BP1 = 12;
constexpr int DV = 15;
constexpr int HOLD = 450;
constexpr int RD = 1500;
constexpr int FE = 5;
#define HP 4
constexpr int AE = 6;
constexpr int AG0 = 900;
constexpr int AB = 17;
constexpr int HGE = 39;
constexpr uint32_t duration(int i) { return PER + (i >= RE0 && i < RE0 + 4 ? 72 : 0) + (i >= GU0 && i < GU0 + 32 ? 36 : 0); }
constexpr uint32_t cmax(uint32_t a, uint32_t b) { return a > b ? a : b; }
constexpr uint32_t issue_time(int i) {
    return i <= NST ? TT0 : i < XE ? issue_time(i - 1) + duration(i - NST) - (i >= XE - 3 && i > GU0 + 36 ? PCUT : 0) : issue_time(XE - 1) + cmax((i - XE + 1) * PFIN, (i - XE) * 512);
}
template <int I> struct Sched { static constexpr uint32_t t = issue_time(I); };
template <int LO, int HI, class F>
__device__ __forceinline__ void for_entries(uint32_t base, F body) {
    constexpr uint32_t per = Sched<LO + 1>::t - Sched<LO>::t;
    static_assert(Sched<HI - 1>::t - Sched<LO>::t == (HI - 1 - LO) * per, "period");
    uint32_t tt = base + Sched<LO>::t;
#pragma unroll 1
    for (int i = LO; i < HI; i++) {
        body(i, tt);
        tt += per;
    }
}

struct Ring { uint32_t prev; int slot; };
struct NoHook { __device__ void operator()() const {} };
template <int TA, int SM, class H = NoHook>
__device__ __forceinline__ void run_entries(Ring& r, int lo, int hi, float (&accA)[64], float (&accB)[64], float (&small)[4],
                                            bool fresh = false, bool sfresh = false, H released = H()) {
    const uint64_t d0 = make_desc(sb);
    const bool leader = (threadIdx.x & 31) == 0;
#pragma unroll 1
    for (int i = lo; i < hi; i++) {
        const uint32_t bar = sb + OFF_FULL + 8 * i;
        const uint64_t da = d0 + (uint64_t)(r.slot * (SLOT >> 4));
        const int n = i - (SM == 1 ? RE0 : GU0);
        const uint64_t dw = SM == 1 ? d0 + (uint64_t)((OFF_W >> 4) + n * 512)
                                    : (((uint64_t)2 << 62) | ((uint64_t)32 << 32) | (128u << 16) | ((sb + OFF_W) >> 4)) + (uint64_t)((n & 7) * 256);
        const uint64_t dt8 = d0 + (uint64_t)((OFF_XS >> 4) + (SM == 1 ? n * 64 : (n >> 1) * 64 + (n & 1) * 4));
        r.slot = r.slot == NST - 1 ? 0 : r.slot + 1;
        mbar_wait(bar);
        wgmma_fence();
#pragma unroll
        for (int kk = 0; kk < 4; kk++) {
            wgmma_n128<TA>(accA, da + kk * (TA ? 128 : 2), da + 1024 + kk * 2, kk > 0 || !fresh);
            if (SM && kk == 3) {
#pragma unroll
                for (int u = 0; u < (SM == 1 ? 4 : 2); u++) wgmma_n8<SM - 1 + !SM>(small, dw + u * (SM == 1 ? 2 : 64), dt8 + u * 2, u > 0 || !sfresh);
            }
            wgmma_n128<TA>(accB, da + 512 + kk * (TA ? 128 : 2), da + 1024 + kk * 2, kk > 0 || !fresh);
            if (kk == 1) {
                wgmma_commit();
                wgmma_wait<1>();
                if (leader) mbar_arrive(r.prev);
                released();
            }
        }
        wgmma_commit();
        r.prev = bar + (OFF_EMPTY - OFF_FULL);
        fresh = sfresh = false;
    }
}
template <int HALF, int I>
__device__ __forceinline__ void run_small(float (&acc)[64]) {
    const uint64_t da = make_desc(sb) + (slot_off(I) >> 4);
    wgmma_fence();
#pragma unroll
    for (int kk = 0; kk < 4; kk++) wgmma_n128<1>(acc, da + HALF * 512 + kk * 128, da + 1024 + kk * 2, kk > 0 || !(HALF && I == FIN));
    wgmma_commit();
}
template <int V> struct Int { __host__ __device__ constexpr operator int() const { return V; } };
template <int N, class F> __device__ __forceinline__ void static_for(F f) {
    if constexpr (N > 0) { static_for<N - 1>(f); f(Int<N - 1>()); }
}

template <bool BY_SMID>
__global__ void __launch_bounds__(384, 1)
fused_kernel(const __grid_constant__ Params prm, const __grid_constant__ CUtensorMap mX, const __grid_constant__ CUtensorMap mB, const __grid_constant__ CUtensorMap mCre,
             const __grid_constant__ CUtensorMap mCim, const __grid_constant__ CUtensorMap mW,
             const __grid_constant__ CUtensorMap mWd, const __grid_constant__ CUtensorMap mXr, const __grid_constant__ CUtensorMap mXe) {
    extern __shared__ __align__(1024) uint8_t smem[];
    const uint32_t cstart = clk32();
    const int tid = threadIdx.x, lane = tid & 31;
    uint32_t id = blockIdx.x;
    if (BY_SMID) asm volatile("mov.u32 %0, %%smid;" : "=r"(id));
    const uint32_t po = tid * 2048, pbo = (id & 127) * 8192;
    const char *p0 = (const char*)prm.x + (pbo * 4 + po), *p1 = (const char*)prm.b_re + (pbo + po), *p2 = (const char*)prm.b_im + (pbo + po);
    asm volatile("{ .reg .pred p, q; setp.lt.u32 p, %3, 16; setp.lt.u32 q, %3, 4;\n"
                 "@q prefetch.global.L2 [%1]; @p prefetch.global.L2 [%0]; @q prefetch.global.L2 [%2]; }" ::"l"(p0), "l"(p1), "l"(p2), "r"(tid) : "memory");
    const int warp = __shfl_sync(0xffffffffu, tid >> 5, 0);
    gap();
    int cta;
    asm("{ .reg .pred p; .reg .u32 a, b, u, q;\n"
        "and.b32 a, %1, 14; shl.b32 a, a, 3; shr.u32 b, %1, 3; and.b32 b, b, 6; add.u32 a, a, b;\n"
        "and.b32 u, %1, 62; mul.lo.u32 q, u, 37; shr.u32 q, q, 9; shl.b32 u, u, 3; mad.lo.u32 u, q, -110, u; add.u32 u, u, 24;\n"
        "setp.lt.u32 p, %1, 64; selp.u32 a, a, u, p; lop3.b32 a, a, %1, 1, 0xF8;\n"
        "setp.lt.u32 p, %1, 124; selp.u32 b, 8, -116, p; add.u32 b, b, %1; setp.lt.u32 p, %1, 120; selp.u32 %0, a, b, p; }" : "=r"(cta) : "r"(id));
    const int chunk = (cta >> 5) * 4 + ((cta >> 2) & 3);
    const int dt = ((cta >> 4) & 1) * 4 + (cta & 3);
    if ((warp | (cta & NCTA)) == 5) {
        mbar_init_n<2>(sb + OFF_FULL, 1);
        tma5b(sb, &mB, 0, dt * 4, sb + OFF_FULL);
        gap();
        tma4(sb + 2 * ABYTES, &mX, 0, chunk * 64, sb + OFF_FULL);
        tma5b(sb + SLOT, &mB, 64, dt * 4, sb + OFF_FULL + 8);
        tma4(sb + SLOT + 2 * ABYTES, &mX, 64, chunk * 64, sb + OFF_FULL + 8);
    }
    else pace_until(cstart + HOLD);
    asm volatile("{ .reg .pred p, q; setp.lt.u32 p, %3, 16; setp.lt.u32 q, %3, 4;\n"
                 "@q prefetch.global.L2 [%1 + 128]; @p prefetch.global.L2 [%0 + 128]; @q prefetch.global.L2 [%2 + 128]; }" ::"l"(p0), "l"(p1), "l"(p2), "r"(tid) : "memory");
    if (cta >= NCTA) {
        if (smem_u32(smem) != sb) __trap();
        if (tid == 0) wait_count_slow(&prm.s->cnt[0], (atomicAdd(&prm.s->cnt[0], 1u) / NGRID + 1) * NGRID);
        return;
    }
    const bool has_gu = cta >= 16;
    constexpr uint32_t full = sb + OFF_FULL, empty = sb + OFF_EMPTY;
    constexpr uint32_t raw = full + 8 * 32;
    constexpr uint32_t bar_hraw = full + 8 * 97, bar_xs = full + 8 * 98, bar_xb = full + 8 * 100, bar_xa = full + 8 * 101,
        bar_retry = full + 8 * 102, bar_out = full + 8 * 104;
    constexpr uint32_t bar_base = empty - 64, bar_init3 = empty - 56, bar_rdone = empty - 48, bar_order0 = empty - 40, bar_init2 = empty - 32,
        bar_vec = empty - 24, bar_epoch = empty - 16, bar_dummy = empty - 8, bar_xs0 = empty + 8 * 69,
        bar_zero = empty + 8 * 70, bar_xafree = empty + 8 * 71, bar_order2 = empty + 8 * 72, bar_dn = empty + 8 * 73, bar_fp = empty + 8 * 74,
        bar_accb = empty + 8 * 76, bar_xbfree = empty + 8 * 78, bar_fold = empty + 8 * 79, bar_st = empty + 8 * 80,
        bar_order1 = empty + 8 * 67, bar_cand = empty + 8 * 68;

    if (warp == 5) {
        if (lane < 2) mbar_expect_tx(full + 8 * lane, SLOT);
        __syncwarp();
        named_bar(0, 256);
#pragma unroll 1
        for (int i = 2; i < NST; i++) {
            pace_until(cstart + T2 + i * P2);
            tma5b(sb + i * SLOT, &mB, i * 64, dt * 4, full + 8 * i);
            tma4(sb + i * SLOT + 2 * ABYTES, &mX, i * 64, chunk * 64, full + 8 * i);
        }
    } else if (warp == 4) {
        mbar_init_n<12>(bar_init2, 4);
        asm volatile("bar.arrive 0, 256;" ::: "memory");
        mbar_init_n<4>(bar_base, 4);
        mbar_init_n<8>(empty + 64, 4);
        *reinterpret_cast<uint2*>(smem + OFF_KEYS + 16) = make_uint2(0, 0);
        asm volatile("bar.arrive 1, 64;" ::: "memory");
        asm volatile("bar.arrive 5, 96;" ::: "memory");
        asm volatile("bar.arrive 6, 96;" ::: "memory");
        mbar_init_n<32>(full + 256, 3);
        if (lane < 2) mbar_arrive(bar_init2);
    } else if ((warp >> 1) == 3) {
        if (warp == 6) {
            mbar_init_n<8>(full + 16, 1);
            if (lane >= 2 && lane < 10) mbar_expect_tx(full + 8 * lane, lane >= RE0 && lane < RE0 + 4 ? SLOT + ABYTES : SLOT);
            __syncwarp();
            asm volatile("bar.arrive 0, 256;" ::: "memory");
        }
        const char* pf0 = (warp & 1) ? (const char*)((cta & 64) ? prm.b_im : prm.b_re) + (cta & 63) * 16384 : (const char*)prm.x + cta * 32768;
        pace_until(cstart + PF1);
        asm volatile("prefetch.global.L2 [%0];" ::"l"(pf0 + (lane & (30 >> (warp & 1) & 30)) * 1024 + (lane & 1) * 128 + 256));
        const int i0 = warp == 6 ? 10 : 21;
        mbar_init_n<11>(full + 8 * i0, 1);
        if (lane >= i0 && lane < i0 + 11) mbar_expect_tx(full + 8 * lane, lane >= GU0 && has_gu ? SLOT + WBYTES : SLOT);
        mbar_init_n<24>(full + 512 + 192 * (warp & 1), 1);
        named_bar(5, 96);
        if (lane == 0) mbar_arrive(bar_init2);
    }
    __syncwarp();

    if (warp >= 8) {
        asm volatile("setmaxnreg.dec.sync.aligned.u32 72;");
        const uint32_t c0 = cstart;
        uint64_t stream;
        asm volatile("createpolicy.fractional.L2::evict_first.b64 %0, 1.0;" : "=l"(stream));
        const int dc = (cta & 15) * 64, dr = (cta >> 4) * 448;
        auto gutile = [&](int i) {
            const int n = i + 3 - GU0;
            if (has_gu) tma3s(sb + OFF_W + (n & 7) * WBYTES, &mW, cta * 32 - 512, n * 32, full + 8 * (i + 3), stream);
        };
        if (warp == 8) {
            named_bar(0, 256);
            sleep_until(c0 + RD);
            asm volatile("prefetch.tensormap [%0];" ::"l"(&mXr));
#pragma unroll 1
            for (int u = 0; u < 2; u++) {
                sleep_until(c0 + R0 + u * R_PACE);
                tma3(sb + OFF_W + u * ABYTES, &mXr, u * 256, cta * 16, full + 8 * (RE0 + u));
            }
            uint32_t dst = sb;
            auto gemm1 = [&](int i, uint32_t tt) {
                mbar_wait(empty + 8 * (i - NST));
                pace_until(tt);
                tma5b(dst, &mB, (i & 15) * 64, (i >> 4) * 64 + dt * 4, full + 8 * i);
                tma4(dst + 2 * ABYTES, &mX, (i & 15) * 64, chunk * 64, full + 8 * i);
                dst = dst == sb + (NST - 1) * SLOT ? sb : dst + SLOT;
            };
            mbar_wait(bar_init2);
            uint32_t tt = c0 + TT0;
#pragma unroll 1
            for (int i = NST; i < AB; i++) {
                gemm1(i, tt);
                if (i < 7) tma3(sb + OFF_W + (i - 3) * ABYTES, &mXr, (i - 3) * 256, cta * 16, full + 8 * (i + 1));
                tt += (i & ~3) == RE0 + 4 ? PER + 72 : PER;
            }
            mbar_wait(bar_base);
            const uint32_t base = uni(lds32(sb + OFF_EPOCH + 8));
            tt = base + Sched<AB>::t;
#pragma unroll 1
            for (int i = AB; i < 32; i++) {
                gemm1(i, tt);
                tt += i >= GU0 + 4 ? PER + 36 : PER;
            }
            const char* hsrc = reinterpret_cast<const char*>(prm.s->h) + (size_t)chunk * 524288;
            auto gemm2 = [&](int i, uint32_t d, int freed, uint32_t tt) {
                mbar_wait(empty + 8 * freed);
                pace_until(tt);
                bulk_load(d, hsrc, 2 * ABYTES, raw + 8 * i);
                tma5(d + 2 * ABYTES, (i & 4) ? &mCim : &mCre, ((i & 3) + ((i >> 1) & 12)) * 64, dt * 8, full + 8 * i);
                hsrc += 2 * ABYTES;
            };
            for_entries<32, GU0 + 29>(base, [&](int i, uint32_t tt) {
                gemm2(i, dst, i - NST, tt);
                gutile(i);
                dst = dst == sb + (NST - 1) * SLOT ? sb : dst + SLOT;
            });
            for_entries<GU0 + 29, GU0 + 37>(base, [&](int i, uint32_t tt) {
                gemm2(i, dst, i - NST, tt);
                const int n = i - GU0 - 29;
                if ((n & 5) == 1) tma5(sb + OFF_W + (n & 2) * (ABYTES / 2), &mXe, dt * 128 + (n & 2) * 32, chunk * 64, bar_xa);
                else if (n < 6) asm volatile(ONE "cp.async.bulk.prefetch.tensor.2d.L2.global [%0, {%1, %2}]; }" ::"l"(&mWd), "r"(dc), "r"(dr + 64 * (n < 4 ? 3 + n / 2 : n + 1)) : "memory");
                dst = dst == sb + (NST - 1) * SLOT ? sb : dst + SLOT;
            });
            static_for<NENT - GU0 - 37>([&](auto u) {
                constexpr int i = GU0 + 37 + u;
                if (i == 60) mbar_wait(bar_out + 56);
                gemm2(i, sb + slot_off(i), i < XE ? i - NST : i == XE ? 71   : i - NST - 1, base + Sched<i>::t);
            });
        } else if (warp == 9) {
#pragma unroll
            for (int u = 0; u < 8; u++) {
                const int row = (u >> 2) * 4 + (lane >> 3);
                asm volatile("cp.async.cg.shared.global [%0], [%1], 16;" ::"r"(sb + OFF_XS + (u & 3) * 1024 + row * 128 + (((lane & 7) ^ row) << 4)),
                             "l"((const char*)(u < 4 ? prm.w_r : prm.gate_w) + (u & 3) * 512 + lane * 16) : "memory");
            }
            uint32_t ticket = 0;
            if (lane == 0) ticket = atomicAdd(&prm.s->cnt[0], 1u);
            named_bar(1, 64);
            if (lane == 0) *reinterpret_cast<volatile uint32_t*>(smem + OFF_EPOCH) = ticket / NGRID;
            __syncwarp();
            if (lane < 4) mbar_arrive(bar_epoch);
            asm volatile("cp.async.wait_all;" ::: "memory");
            asm volatile("fence.proxy.async.shared::cta;" ::: "memory");
            __syncwarp();
            if (lane < 4) mbar_arrive(bar_vec);
#pragma unroll 1
            for (int i = 4; i < 22; i++) mbar_init_n<4>(empty + 32 * i, 4, i >= 6 && i < 13);
            if (lane < 2) mbar_arrive(bar_init3);
            mbar_wait(bar_cand);
            {
                const uint32_t* list = reinterpret_cast<const uint32_t*>(smem + OFF_LIST);
                const int n = (int)lds32(sb + OFF_KEYS + 16);
#pragma unroll 1
                for (int i0 = 0; i0 < n; i0 += 32) {
                    const uint32_t k = list[i0 + lane];
                    int rank = 0;
#pragma unroll 2
                    for (int o = 0; o < n; o += 4) {
                        const uint4 l4 = *reinterpret_cast<const uint4*>(list + o);
                        rank += (l4.x > k) + (l4.y > k) + (l4.z > k) + (l4.w > k);
                    }
                    if (rank < 8) reinterpret_cast<uint32_t*>(smem + OFF_SEL)[rank] = k;
                }
                __syncwarp();
                const uint32_t key = lds32(sb + OFF_SEL + 4 * (lane & 7)), tok = ~key & 2047u, tag = lds32(sb + OFF_EPOCH) + 1;
                const uint32_t ta = __shfl_sync(0xffffffffu, tok, lane >> 3), tb = __shfl_sync(0xffffffffu, tok, 4 + (lane >> 3));
                const uint32_t da = sb + OFF_XS + (lane >> 3) * 128 + (((lane & 7) ^ (lane >> 3)) << 4), db = (da ^ 64) + 512;
                const char *sa = (const char*)prm.x + ta * 2048 + (lane & 7) * 16, *sc = (const char*)prm.x + tb * 2048 + (lane & 7) * 16;
#pragma unroll
                for (int u = 0; u < 16; u++) {
                    asm volatile("cp.async.cg.shared.global [%0], [%1], 16;" ::"r"(da + u * 1024), "l"(sa + u * 128) : "memory");
                    asm volatile("cp.async.cg.shared.global [%0], [%1], 16;" ::"r"(db + u * 1024), "l"(sc + u * 128) : "memory");
                    if (u == 3) {
                        asm volatile("cp.async.wait_all;" ::: "memory");
                        asm volatile("fence.proxy.async.shared::cta;" ::: "memory");
                        __syncwarp();
                        if (lane < 4) mbar_arrive(bar_xs0);
                    }
                }
                if ((tok >> 7) == (uint32_t)chunk) {
                    float4* zp = reinterpret_cast<float4*>(prm.out + tok * D_ + dt * 128) + (lane >> 3) * 2;
#pragma unroll
                    for (int u = 0; u < 8; u++) zp[(u >> 1) * 8 + (u & 1)] = make_float4(0.f, 0.f, 0.f, 0.f);
                }
                uint32_t it = 0;
                unsigned long long u;
                do {
                    u = ld_relaxed1(&prm.s->gpack[tok >> 1]);
                    if (++it > SPIN_LIMIT) __trap();
                } while (!__all_sync(0xffffffffu, (uint32_t)(u >> 32) == tag));
                const uint32_t kb = key >> 16;
                const float r = bf_lo((kb & 0x8000u) ? (kb & 0x7FFFu) : (~kb & 0xFFFFu)), gv = (tok & 1) ? bf_hi((uint32_t)u) : bf_lo((uint32_t)u);
                reinterpret_cast<float*>(smem + OFF_FAC)[lane & 7] = rbf(1.0f - gv) * rbf(sigmoidf_(r));
                asm volatile("cp.async.wait_all;" ::: "memory");
                asm volatile("fence.proxy.async.shared::cta;" ::: "memory");
                __syncwarp();
                if (lane == 0) mbar_arrive(bar_xs);
            }
            char* hd = reinterpret_cast<char*>(prm.s->h) + (size_t)chunk * 524288 + (dt >> 1) * 16384 + (dt & 1) * 4096;
            mbar_wait(bar_base);
            const uint32_t cb = uni(lds32(sb + OFF_EPOCH + 8)) + ST_SHIFT;
            uint32_t tt = cb + Sched<GU0 + 4>::t;
#pragma unroll 1
            for (int np = 0; np < 16; np++) {
                if (!(np & (np & 4 ? 1 : 2))) mbar_wait(bar_st + 4 * (np & 12) + ((np & 3) ? 8 : 0));
                const uint32_t now = clk32() - ST_TOL;
#pragma unroll 1
                while ((int)(tt - now) < 0) tt += PER + 36;
                const uint32_t src = sb + OFF_STG + (np & 3) * 4096;
                pace_until(tt);
                bulk_store(hd, src, 4096);
                asm volatile("cp.async.bulk.commit_group;" ::: "memory");
                if (np & 2) {
                    if (np & 1) asm volatile("cp.async.bulk.wait_group.read 0;" ::: "memory");
                    else asm volatile("cp.async.bulk.wait_group.read 1;" ::: "memory");
                    __syncwarp();
                    const uint32_t u8 = 4 * (np & 12) + 8 * (np & 1);
                    if (lane < 2) mbar_arrive(lane ? (np < 15 ? empty + 8 * 27 + 4 * u8 : bar_dummy) : bar_out + u8);
                }
                hd += (np & 1) ? 65536 - 8192 : 8192;
                tt += PER + 36;
            }
#pragma unroll 1
            for (int u = 0; u < 2; u++) {
                pace_until(tt);
                tma5(sb + OFF_STG + u * ABYTES, &mXe, dt * 128 + u * 64, chunk * 64 + 8, bar_xb);
                tt += PER + 36;
            }
            wait_count(&prm.s->cnt[32], (lds32(sb + OFF_EPOCH) + 1) * NCTA);
            auto load_hid = [&]() {
                if (lane == 0) mbar_expect_tx(bar_hraw, 7168);
                bulk_load(sb + OFF_XS, prm.s->hid + dr, 7168, bar_hraw);
            };
            static_for<7>([&](auto u) {
                if (u != 2) mbar_wait(u == 1 ? bar_xbfree : empty + 8 * (u == 0 ? GU0 + 31 : FIN - 2 + u));
                if (u < 3) sleep_until(cb + Sched<GU0 + HGE - 2 + u>::t);
                if (u == 2) load_hid();
                tma2(sb + dn_off(u), &mWd, dc, dr + u * 64, bar_dn, stream);
                if (u == 2) {
                    const uint32_t t2 = lds32(sb + OFF_EPOCH) + 1, tagw = (t2 & 1) | ((t2 & 2) << 15);
#pragma unroll 1
                    for (uint32_t it = 0;; it++) {
                        mbar_wait(bar_hraw, it & 1);
                        uint32_t bad = 0;
#pragma unroll
                        for (int i = 0; i < 14; i++) bad |= lds32(sb + OFF_XS + i * 512 + lane * 16 + (lane >> 3) * 4) ^ tagw;
                        if (__all_sync(0xffffffffu, (bad & 0x00010001u) == 0)) break;
                        if (it > SPIN_LIMIT) __trap();
                        load_hid();
                    }
                    if (lane < 4) mbar_arrive(bar_zero);
                }
            });
        } else {
            named_bar(6, 96);
            if (warp == 10) {
                const char* pb = (const char*)((cta & 64) ? prm.b_im : prm.b_re) + (cta & 63) * 16384;
                const char* pf = (lane < 16 ? (const char*)prm.x + cta * 32768 : pb) + (lane & 15) * 2048 + 512;
#pragma unroll 1
                for (int k = 0; k < 11; k++) {
                    sleep_until(c0 + PF0 + k * PFX_PACE);
                    if (lane < 16 ? k < 6 : lane < 24 && !(k & 1)) prefetch_l2(pf + k * (lane < 16 ? 256 : 128));
                }
#pragma unroll 1
                for (int k = 0; k < 12; k++) {
                    sleep_until(c0 + Sched<12>::t + ST_SHIFT + (k + BP1 - 12) * PER);
                    bulk_prefetch((k < 4 ? pb + 1048576 : (const char*)(k < 8 ? prm.c_re : prm.c_im) + cta * 16384) + (k & 3) * 4096, 4096);
                    if (k == 4) { mbar_wait(bar_init2); mbar_wait(bar_init3); }
                    if (k >= 4 && lane < 8) mbar_expect_tx(full + 8 * (8 * k + lane), 8 * k + lane < GU0 + 32 && has_gu ? 2 * ABYTES + WBYTES : 2 * ABYTES);
                }
                asm volatile("prefetch.tensormap [%0];" ::"l"(&mCre));
                asm volatile("prefetch.tensormap [%0];" ::"l"(&mCim));
                asm volatile("prefetch.tensormap [%0];" ::"l"(&mWd));
                asm volatile("prefetch.tensormap [%0];" ::"l"(&mXe));
                if (lane < 2) mbar_expect_tx(bar_xb + 8 * lane, 2 * ABYTES);
                mbar_wait(bar_xs);
                mbar_wait(bar_st);
                if (lane == 0) red_release(&prm.s->cnt[32]);
                __syncwarp();
            } else {
                mbar_wait(bar_epoch);
                const uint32_t tag = lds32(sb + OFF_EPOCH) + 1;
                st_cell(prm.s->time + cta, 0, 0, 0, 0, lane == 0);
                asm volatile("prefetch.tensormap [%0];" ::"l"(&mW));
                mbar_wait(empty + 8 * AE);
                uint32_t gown, tm[4][4] = {}, it = 0;
                asm volatile("mov.u32 %0, %%globaltimer_lo;" : "=r"(gown));
                const uint32_t town = clk32();
                st_cell(prm.s->time + cta, tag, town, gown, 0, lane == 0);
                sleep_until(town + AG0);
                do {
#pragma unroll
                    for (int m = 0; m < 4; m++) ld_cell(tm[m], prm.s->time + ((cta & 96) ^ (32 * m)) + lane);
                    if (++it > SPIN_LIMIT) __trap();
                } while (!__all_sync(0xffffffffu, tm[0][0] == tag && tm[1][0] == tag && tm[2][0] == tag && tm[3][0] == tag));
                const int last = __reduce_max_sync(0xffffffffu, max(max((int)(tm[0][2] - gown), (int)(tm[1][2] - gown)), max((int)(tm[2][2] - gown), (int)(tm[3][2] - gown))));
                const uint32_t cand = tm[0][1] + ((min((int)(gown + last - tm[0][2]), 4000) * CLK_NS) >> 8);
                const uint32_t b0 = __shfl_sync(0xffffffffu, cand, cta & 16), b1 = __shfl_sync(0xffffffffu, cand, cta & 30);
                const uint32_t b2 = __shfl_sync(0xffffffffu, cand, cta & 31);
                const uint32_t base = (b0 - b2 + 400u < 800u ? b0 : b1 - b2 + 400u < 800u ? b1 : b2) + MARGIN - Sched<AE + NST>::t;
                *reinterpret_cast<volatile uint32_t*>(smem + OFF_EPOCH + 8) = base;
                mbar_wait(bar_init3);
                if (lane < 4) mbar_arrive(bar_base);
                const uint32_t cb = base + W_SHIFT;
                auto early = [&](int i, uint32_t tt) {
                    mbar_wait(empty + 8 * (i - NST));
                    pace_until(tt);
                    gutile(i);
                };
                for_entries<GU0 - 3, GU0 + 4>(cb, early);
                for_entries<GU0 + 4, 32>(cb, early);
            }
            mbar_wait(bar_epoch);
            const uint32_t t2 = lds32(sb + OFF_EPOCH) + 1, tagw = (t2 & 1) | ((t2 & 2) << 15), half = (warp & 1) * ABYTES;
            const uint32_t lo = half + lane * 32 + (lane & 4) * 4 + (lane >> 3) * 4, retry = bar_retry + (warp & 1) * 8;
            const bool leader = lane == 0;
            uint32_t slot = sb + (32 % NST) * SLOT, rpar = 0;
#pragma unroll 1
            for (int i = 32; i < NENT; i++) {
                const uint32_t src = i == XE ? sb + OFF_W : slot;
                if (i != XE) slot = slot == sb + (NST - 1) * SLOT ? sb : slot + SLOT;
                auto current = [&]() {
                    uint32_t v[8];
#pragma unroll
                    for (int u = 0; u < 8; u++) v[u] = lds32(src + lo + u * 1024);
#pragma unroll
                    for (int u = 0; u < 8; u += 2) asm("lop3.b32 %0, %0, %1, %2, 0x7e;" : "+r"(v[u]) : "r"(v[u + 1]), "r"(tagw));
                    return __all_sync(0xffffffffu, ((v[0] | v[2] | v[4] | v[6]) & 0x00010001u) == 0);
                };
                mbar_wait(raw + 8 * i);
                if (!current()) {
#pragma unroll 1
                    for (uint32_t it = 0;; it++) {
                        if (it > SPIN_LIMIT) __trap();
                        if (leader) mbar_expect_tx(retry, ABYTES);
                        bulk_load(src + half, reinterpret_cast<const char*>(prm.s->h) + (size_t)chunk * 524288 + (i - 32) * 16384 + half, ABYTES, retry);
                        mbar_wait(retry, rpar);
                        rpar ^= 1;
                        if (current()) break;
                    }
                }
                if (leader) mbar_arrive(full + 8 * i);
            }
        }
    } else {
        asm volatile("setmaxnreg.inc.sync.aligned.u32 216;");
        const int wg = warp >> 2, w = warp & 3, g = lane >> 2, c = lane & 3, at = tid & 127;
        float facc[4];
        float2 a[2], m0[2], a32[2], a128[2];
        auto load_const = [&]() {
            const float2* cp = reinterpret_cast<const float2*>(smem + OFF_CONST) + wg * 64 + w * 8 + g;
#pragma unroll
            for (int h = 0; h < 2; h++) { a[h] = cp[32 * h]; m0[h] = cp[128 + 32 * h]; a32[h] = cp[256 + 32 * h]; a128[h] = cp[384 + 32 * h]; }
        };
        if (wg == 0) {
            named_bar(0, 256);
        } else {
            const int pc = (at >> 5) * 256 + dt * 32 + (at & 31);
            const float lr = __bfloat162float(prm.lam_re[pc]), li = __bfloat162float(prm.lam_im[pc]), ld = __bfloat162float(prm.log_dt[pc]);
            const uint32_t dk = __ldg(reinterpret_cast<const uint32_t*>(prm.dskip + dt * 128) + (at & 63));
#pragma unroll
            for (int i = 0; i < 4; i++) sts128(sb + OFF_LIST + i * 2048 + at * 16, 0u, 0u, 0u, 0u);

            {
                reinterpret_cast<uint32_t*>(smem + OFF_DK)[at & 63] = dk;
                const float dtv = rbf(expf(ld));
                const float er = expf(dtv * lr);
                float sn, cs;
                sincospif(dtv * li * 0.318309886183790672f, &sn, &cs);
                const float ar = er * cs, ai = er * sn;
                const float nr = ar - 1.0f, ni = ai;
                const bool big = fabsf(lr) >= fabsf(li);
                const float t = (big ? li : lr) / (big ? lr : li), dn = big ? lr + li * t : lr * t + li;
                const float cr = (big ? nr + ni * t : nr * t + ni) / dn, ci = (big ? ni - nr * t : ni * t - nr) / dn;
                float2* cp = reinterpret_cast<float2*>(smem + OFF_CONST) + at;
                float2 pw = make_float2(ar, prm.swapped ? ai : -ai);
                cp[0] = pw;
                cp[128] = make_float2(prm.swapped ? -2.f * cr : 2.f * cr, -2.f * ci);
#pragma unroll
                for (int i = 1; i <= 7; i++) {
                    pw = cmul(pw, pw);
                    if (i == 5) cp[256] = pw;
                    if (i == 7) cp[384] = pw;
                }
                __syncwarp();
            }
            named_bar(2, 128);
            load_const();
            mbar_wait(bar_epoch);
            const uint32_t tag = *reinterpret_cast<volatile uint32_t*>(smem + OFF_EPOCH) + 1;
            asm volatile("st.relaxed.gpu.global.b64 [%0], %1;" ::"l"(&prm.s->carry[(chunk >> 2) * 4096 + pc * 4 + (chunk & 3)]), "l"((unsigned long long)(tag + 2)) : "memory");
            if (w == 2) st_cell(lane < 4 ? (uint4*)prm.s->rpack + cta * 4 + lane : (uint4*)prm.s->gpack + cta * 4 + (lane & 3), 0, 0, 0, 0, lane < 8);
            {
                const uint32_t nt = ((tag & 1) | ((tag & 2) << 15)) ^ 0x00010001u;
                st_cell(prm.s->hid + cta * 32 - 512 + lane, nt, nt, nt, nt, has_gu && w == 3);
            }
            named_bar(2, 128);
            if (at < 2) mbar_arrive(bar_init3);
            unsigned long long* pub = (w ? prm.s->gpack : prm.s->rpack) + cta * 8 + lane;
            asm volatile("" : "+l"(pub));
            mbar_wait(bar_rdone);

            if (w < 2) {
                const float2* red = reinterpret_cast<const float2*>(smem + OFF_RED) + w * 8 + (lane & 7);
                const float2 r0 = red[0], r1 = red[16], r2 = red[32], r3 = red[48];
                const float v0 = (r0.x + r1.x) + (r2.x + r3.x), v1 = (r0.y + r1.y) + (r2.y + r3.y);
                uint32_t pk2;
                if (w == 0) {
                    pk2 = pack_bf(v0, v1);
                    pk2 ^= (((pk2 >> 15) & 0x00010001u) * 0x7FFFu) ^ 0x80008000u;
                } else pk2 = pack_bf(sigmoidf_(rbf(v0)), sigmoidf_(rbf(v1)));
                if (lane < 8) asm volatile("st.relaxed.gpu.global.b64 [%0], %1;" ::"l"(pub), "l"(((unsigned long long)tag << 32) | pk2) : "memory");
                __syncwarp();
            }
            uint32_t it = 0, pr[8], g1;
            mbar_wait(bar_init3);
            sleep_until(clk32() + (w < 2 ? G0 : G0 + 250));
            while (true) {
                bool ok = true;
#pragma unroll
                for (int k = 0; k < 4; k++) {
                    const ulonglong2 u = ld_relaxed2(&prm.s->rpack[k * 256 + 2 * at]);
                    ok = ok && (uint32_t)(u.x >> 32) == tag && (uint32_t)(u.y >> 32) == tag;
                    pr[2 * k] = (uint32_t)u.x; pr[2 * k + 1] = (uint32_t)u.y;
                }
                const unsigned long long u1 = ld_relaxed1(&prm.s->gpack[chunk * 64 + (at & 63)]);
                ok = ok && (uint32_t)(u1 >> 32) == tag;
                g1 = (uint32_t)u1;
                if (__all_sync(0xffffffffu, ok)) break;
                if (++it > SPIN_LIMIT) __trap();
            }
            uint32_t m = __vmaxu2(__vimax3_u16x2(__vimax3_u16x2(pr[0], pr[1], pr[2]), pr[3], pr[4]), __vimax3_u16x2(pr[5], pr[6], pr[7]));
            m = (max(m, m << 16) & 0xFFFF0000u) | (uint32_t)lane;
            const uint32_t m1 = __reduce_max_sync(0xffffffffu, m), m2 = __reduce_max_sync(0xffffffffu, m == m1 ? 0u : m);
            uint32_t* keys = reinterpret_cast<uint32_t*>(smem + OFF_KEYS);
            if (lane == 0) keys[w] = m2;
            sts128(sb + OFF_XS + 4096 + at * 16, pr[0], pr[1], pr[2], pr[3]);
            sts128(sb + OFF_XS + 6144 + at * 16, pr[4], pr[5], pr[6], pr[7]);
            *reinterpret_cast<uint32_t*>(smem + OFF_G + 4 * (at & 63)) = g1;
            named_bar(2, 128);
            const uint4 th4 = *reinterpret_cast<const uint4*>(keys);
            const uint32_t th = (max(min(min(th4.x, th4.y), min(th4.z, th4.w)) >> 16, 1u) - 1u) * 0x00010001u;
            uint32_t mask = 0;
#pragma unroll
            for (int k = 7; k >= 0; k--) mask = mask * 2 + __vminu2(__vmaxu2(pr[k], th) ^ th, 0x00010001u);
            uint32_t pos = 0;
            asm volatile("{ .reg .pred p; setp.ne.u32 p, %2, 0; @p atom.shared.add.u32 %0, [%1], %2; }" : "+r"(pos) : "r"(sb + OFF_KEYS + 16), "r"(__popc(mask)) : "memory");
            while (mask) {
                const int bit = __ffs(mask) - 1, k = bit & 7, hi = bit >> 4;
                mask &= mask - 1;
                const uint32_t sc = *reinterpret_cast<const uint16_t*>(smem + OFF_XS + 4096 + (k >> 2) * 2048 + at * 16 + (k & 3) * 4 + hi * 2);
                *reinterpret_cast<uint32_t*>(smem + OFF_LIST + 4 * pos++) = (sc << 16) | (0x8000u + 2047u - (uint32_t)((k >> 1) * 512 + 4 * at + 2 * (k & 1) + hi));
            }
            __syncwarp();
            if (lane == 0) mbar_arrive(bar_cand);
            mbar_wait(bar_order0);
        }

        float accA[64], accB[64];
        Ring ring = {bar_dummy, wg};
        {
            run_entries<0, 0>(ring, wg * 16, wg ? GU0 : RE0, accA, accB, facc, true);
            if (wg == 0) {
                float racc[4];
                mbar_wait(bar_vec);
                run_entries<0, 1>(ring, RE0, RE0 + 4, accA, accB, racc, false, true);
                mbar_wait(bar_init2);
                const uint32_t red = sb + OFF_RED + 4 * (w * 32 + (c >> 1) * 16 + g);
                run_entries<0, 0>(ring, RE0 + 4, RE0 + 5, accA, accB, facc, false, false, [&]() {
                    pin4(racc);
                    asm volatile("{ .reg .pred p; setp.ne.u32 p, %3, 0; @p st.shared.f32 [%0], %1; @p st.shared.f32 [%0 + 32], %2; }" ::"r"(red),
                                 "f"((w & 1) ? racc[1] : racc[0]), "f"((w & 1) ? racc[3] : racc[2]), "r"((uint32_t)((c & 1) == (w >> 1))) : "memory");
                    __syncwarp();
                    if (lane == 0) mbar_arrive(bar_rdone);
                });
                run_entries<0, 0>(ring, RE0 + 5, 16, accA, accB, facc);
                if (lane == 0) mbar_arrive(bar_order0);
                mbar_wait(bar_init3);
                load_const();
                named_bar(3, 128);
            } else {
#pragma unroll
                for (int u = 0; u < 2; u++) {
                    mbar_wait(u ? bar_xs : bar_xs0);
                    run_entries<0, 2>(ring, GU0 + 8 * u, u ? 32 : GU0 + 8, accA, accB, facc, false, u == 0);
                }
                if (lane == 0) mbar_arrive(bar_order1);
            }
        }
        const uint32_t tag = *reinterpret_cast<volatile uint32_t*>(smem + OFF_EPOCH) + 1;
        const float2 a64[2] = {cmul(a32[0], a32[0]), cmul(a32[1], a32[1])};
        wgmma_wait<0>();
        pin64(accA); pin64(accB); pin4(facc);
        if (lane == 0) mbar_arrive(ring.prev);

        const int tl = 32 * (g >> 1) + (g & 1) + 4 * w + 16 * wg, t0 = chunk * 128 + tl;
        float* op = prm.out + (size_t)t0 * D_ + dt * 128 + 4 * c;
        uint2 xv[8][2], dk[8];
        uint32_t gp[2], om[2], routed[2];
        auto row_setup = [&]() {
            const uint4 sa = *reinterpret_cast<const uint4*>(smem + OFF_SEL), sc = *reinterpret_cast<const uint4*>(smem + OFF_SEL + 16);
#pragma unroll
            for (int r = 0; r < 2; r++) {
                const uint32_t id = 0x8000u + 2047u - (uint32_t)(t0 + 2 * r);
                routed[r] = (uint16_t)sa.x == id || (uint16_t)sa.y == id || (uint16_t)sa.z == id || (uint16_t)sa.w == id ||
                            (uint16_t)sc.x == id || (uint16_t)sc.y == id || (uint16_t)sc.z == id || (uint16_t)sc.w == id;
                gp[r] = reinterpret_cast<const uint16_t*>(smem + OFF_G)[tl + 2 * r] * 0x00010001u;
                om[r] = pack_bf(1.0f - bf_hi(gp[r]), 1.0f - bf_hi(gp[r]));
            }
#pragma unroll
            for (int j = 0; j < 8; j++) dk[j] = lds64(sb + OFF_DK + 32 * j + 8 * c);
        };
        auto release = [&](uint32_t bar) {
            asm volatile("fence.proxy.async.shared::cta;" ::: "memory");
            __syncwarp();
            if (lane == 0) mbar_arrive(bar);
        };

        {
            const uint32_t t2 = tag & 3u;
            float2* cslot = &prm.s->carry[(wg * 512 + dt * 32 + w * 8 + g) * 4];
            const int j1 = chunk - 1 - c;
            unsigned long long v[2][4] = {{t2, t2, t2, t2}, {t2, t2, t2, t2}};
            auto poll = [&](int h) {
#pragma unroll
                for (int m = 0; m < 4; m++)
                    asm volatile("{ .reg .pred p; setp.ge.s32 p, %2, %3; @p ld.relaxed.gpu.global.b64 %0, [%1]; }"
                                 : "+l"(v[h][m]) : "l"(cslot + (j1 >> 2) * 4096 + c - m * 4096 + h * 1024), "r"(j1), "r"(4 * m) : "memory");
            };
            float2 e[2], w0[2];
            auto chain = [&](int h, int s0, int s1) {
                float (&acc)[64] = h ? accB : accA;
                if (s0 == 1) e[h] = make_float2(acc[0], acc[2]);
#pragma unroll
                for (int s = s0; s < s1; s++) {
                    const int i0 = 4 * (s >> 1) + (s & 1);
                    e[h] = cfma(make_float2(a[h].x, -a[h].y), e[h], make_float2(acc[i0], acc[i0 + 2]));
                }
                asm volatile("" : "+f"(e[h].x), "+f"(e[h].y), "+f"(accB[0]), "+f"(accB[2]));
                gap();
            };
            auto publish = [&](int h) {
                float2 f = make_float2(fmaf(m0[h].x, e[h].x, m0[h].y * e[h].y), fmaf(-m0[h].x, e[h].y, m0[h].y * e[h].x));
                float2 y = make_float2(__shfl_up_sync(0xffffffffu, f.x, 1, 4), __shfl_up_sync(0xffffffffu, f.y, 1, 4));
                if (c >= 1) f = cfma(a32[h], y, f);
                y = make_float2(__shfl_up_sync(0xffffffffu, f.x, 2, 4), __shfl_up_sync(0xffffffffu, f.y, 2, 4));
                if (c >= 2) f = cfma(a64[h], y, f);
                asm volatile("{ .reg .pred p; .reg .b64 t; setp.eq.u32 p, %3, 3; mov.b64 t, {%1, %2}; @p st.relaxed.gpu.global.b64 [%0], t; }"
                             ::"l"(cslot + (chunk >> 2) * 4096 + (chunk & 3) + h * 1024), "r"((__float_as_uint(f.x) & ~3u) | t2), "r"(__float_as_uint(f.y)), "r"(c) : "memory");
                w0[h] = make_float2(__shfl_up_sync(0xffffffffu, f.x, 1, 4), __shfl_up_sync(0xffffffffu, f.y, 1, 4));
                if (c == 0) w0[h] = make_float2(0.f, 0.f);
            };
            auto scale = [&](int h, int n0, int n1) {
                float (&acc)[64] = h ? accB : accA;
#pragma unroll
                for (int n = n0; n < n1; n++) {
                    asm volatile("{ .reg .f32 a, b, c, d, n; neg.f32 n, %4; mul.f32 a, %1, %5; mul.f32 b, %0, %5; mul.f32 c, %3, %5; mul.f32 d, %2, %5;\n"
                                 "fma.rn.f32 %0, %0, %4, a; fma.rn.f32 %1, %1, n, b; fma.rn.f32 %2, %2, %4, c; fma.rn.f32 %3, %3, n, d; }"
                                 : "+f"(acc[4 * n]), "+f"(acc[4 * n + 2]), "+f"(acc[4 * n + 1]), "+f"(acc[4 * n + 3]) : "f"(m0[h].x), "f"(m0[h].y));
                    gap();
                }
            };
            auto carry = [&](int h) {
                const float2 one = make_float2(1.f, 0.f), a256 = cmul(a128[h], a128[h]);
                float2 a512 = cmul(a256, a256), pw128 = cmul((j1 & 1) ? a128[h] : one, (j1 & 2) ? a256 : one);
                float2 pw32 = cmul((c & 1) ? a32[h] : one, (c & 2) ? a64[h] : one);
                asm volatile("" : "+f"(a512.x), "+f"(a512.y), "+f"(pw128.x), "+f"(pw128.y), "+f"(pw32.x), "+f"(pw32.y));
                uint32_t it = 0;
                while (!__all_sync(0xffffffffu, ((((uint32_t)v[h][0] ^ t2) | ((uint32_t)v[h][1] ^ t2) | ((uint32_t)v[h][2] ^ t2) | ((uint32_t)v[h][3] ^ t2)) & 3u) == 0)) {
                    poll(h);
                    if (++it > SPIN_LIMIT) __trap();
                }
                float2 hin = make_float2(__uint_as_float((uint32_t)v[h][3]), __uint_as_float((uint32_t)(v[h][3] >> 32)));
#pragma unroll
                for (int m = 2; m >= 0; m--) hin = cfma(a512, hin, make_float2(__uint_as_float((uint32_t)v[h][m]), __uint_as_float((uint32_t)(v[h][m] >> 32))));
                hin = cmul(pw128, hin);
                hin.x += __shfl_xor_sync(0xffffffffu, hin.x, 1); hin.y += __shfl_xor_sync(0xffffffffu, hin.y, 1);
                hin.x += __shfl_xor_sync(0xffffffffu, hin.x, 2); hin.y += __shfl_xor_sync(0xffffffffu, hin.y, 2);
                w0[h] = cfma(pw32, hin, w0[h]);
            };
            chain(0, 1, 32);
            publish(0);
            chain(1, 1, 8);
            chain(1, 8, 32);
            publish(1);
            gap();
            scale(0, 0, POLL_S);
            poll(0);
            scale(0, POLL_S, 16);
            carry(0);
            if (wg) mbar_wait(bar_out + 24);
            const uint32_t stg = sb + OFF_STG + prm.swapped * 8192 + w * 1024 + (lane & 7) * 128 + (((lane >> 3) ^ (lane & 7)) << 4);
            const uint32_t second = prm.swapped ? -8192 : 8192;
            uint32_t hold = prm.swapped >> 1, last[8];
            const uint32_t keep = c == (g >> 1) ? 0xFFFEFFFEu : 0xFFFFFFFFu, tagw = ((t2 & 1) | ((t2 & 2) << 15)) & ~keep;
#pragma unroll
            for (int h = 0; h < 2; h++) {
                float (&acc)[64] = h ? accB : accA;
                uint32_t ra[16], ia[16];
                if (h) {
                    scale(1, 0, 4);
#pragma unroll
                    for (int u = 0; u < 4; u++) asm volatile("lop3.b32 %0, %0, %1, %2, 0x80;" : "+r"(hold) : "r"(last[u]), "r"(last[4 + u]));
                    release(bar_st + 32 * wg + 8 + hold);
                    poll(1);
                    scale(1, 4, 16);
                    mbar_wait(bar_xs);
                    row_setup();
                    carry(1);
                }
                auto stage = [&](uint32_t (&r)[16], uint32_t base, int j) {
                    stsm4((base ^ ((j & 1) * 64)) + (j >> 1) * 4096, r[4 * j], r[4 * j + 1], r[4 * j + 2], r[4 * j + 3]);
                };
#pragma unroll
                for (int n = 0; n < 16; n++) {
                    const float2 y = cfma(a[h], w0[h], make_float2(acc[4 * n], acc[4 * n + 2]));
                    w0[h] = cfma(a[h], y, make_float2(acc[4 * n + 1], acc[4 * n + 3]));
                    ra[n] = pack_bf(y.x, w0[h].x);
                    ia[n] = pack_bf(y.y, w0[h].y);
                    if (!(n & 1)) { ra[n] = (ra[n] & keep) | tagw; ia[n] = (ia[n] & keep) | tagw; }
                    if (!h && (n & 3) == 3) {
                        if (n > 3) {
                            gap();
#pragma unroll
                            for (int u = n - 7; u < n - 3; u++) asm volatile("lop3.b32 %0, %0, %1, %2, 0x80;" : "+r"(hold) : "r"(ra[u]), "r"(ia[u]));
                        }
                        if (n == 15) {
#pragma unroll
                            for (int u = 0; u < 4; u++) { last[u] = ra[12 + u]; last[4 + u] = ia[12 + u]; }
                        }
                        if (n == 11) { asm volatile("" : "+r"(ra[n]), "+r"(ia[n])); gap(); release(bar_st + 32 * wg); }
                        stage(ra, stg, n >> 2); stage(ia, stg + second, n >> 2);
                        gap();
                    }
                }
                if (h) {
                    mbar_wait(bar_out + 32 * wg);
                    if (prm.swapped) {
#pragma unroll
                        for (int n = 0; n < 16; n++) { const uint32_t t = ra[n]; ra[n] = ia[n]; ia[n] = t; }
                    }
                    const uint32_t st0 = stg - prm.swapped * 8192;
#pragma unroll
                    for (int j = 0; j < 4; j++) stage(ra, st0, j);
                    release(bar_st + 32 * wg + 16);
                    mbar_wait(bar_out + 32 * wg + 8);
#pragma unroll
                    for (int j = 0; j < 4; j++) stage(ia, st0 + 8192, j);
                    release(bar_st + 32 * wg + 24);
                }
            }
        }

        const uint32_t xr = 2 * (g & 3) + (g >> 2), xa = sb + (wg ? OFF_STG : OFF_W) + (16 * w + xr) * 128 + (((c >> 1) ^ xr) << 4) + (c & 1) * 8;
        auto handover = [&](uint32_t bar) {
            const uint4 z = ldsm4(sb + OFF_KEYS + 16);
            if (lane == 1) mbar_arrive(bar + z.x);
        };
        auto load_x = [&](int j0, int j1) {
#pragma unroll
            for (int j = j0; j < j1; j++)
#pragma unroll
                for (int r = 0; r < 2; r++) xv[j][r] = lds64((xa ^ (32 * (j & 3))) + (j >> 2) * ABYTES + r * 1024);
        };
        auto skip_term = [&](int j0, int j1) {
#pragma unroll
            for (int j = j0; j < j1; j++)
#pragma unroll
                for (int r = 0; r < 2; r++) {
                    xv[j][r].x = mul_bf2(xv[j][r].x, fma_bf2(gp[r], dk[j].x, om[r]));
                    xv[j][r].y = mul_bf2(xv[j][r].y, fma_bf2(gp[r], dk[j].y, om[r]));
                    asm volatile("" : "+r"(xv[j][r].x), "+r"(xv[j][r].y));
                }
        };
        auto finish = [&](float (&acc)[64], int j, bool gaps) {
#pragma unroll
            for (int r = 0; r < 2; r++) {
                const int o = 8 * j + 2 * r;
                const float gv = bf_hi(gp[r]);
                acc[o] = fmaf(gv, acc[o], bf_lo(xv[j][r].x)); acc[o + 1] = fmaf(gv, acc[o + 1], bf_hi(xv[j][r].x));
                acc[o + 4] = fmaf(gv, acc[o + 4], bf_lo(xv[j][r].y)); acc[o + 5] = fmaf(gv, acc[o + 5], bf_hi(xv[j][r].y));
                stg4_unless(op + r * 2 * D_ + 16 * j, acc[o], acc[o + 1], acc[o + 4], acc[o + 5], routed[r]);
                if (gaps) gap();
            }
        };
        auto finish_routed = [&](float (&acc)[64]) {
#pragma unroll
            for (int r = 0; r < 2; r++)
                if (routed[r]) {
#pragma unroll
                    for (int j = 0; j < 8; j++) red4(op + r * 2 * D_ + 16 * j, acc[8 * j + 2 * r], acc[8 * j + 2 * r + 1], acc[8 * j + 2 * r + 4], acc[8 * j + 2 * r + 5]);
                }
            __syncwarp();
        };
        const uint32_t xbuf = sb + w * 2048 + lane * 16;

        if (wg == 1) {
            float outB[64];
            {
                sts128(sb + OFF_XS + at * 16, __float_as_uint(facc[0]), __float_as_uint(facc[1]), __float_as_uint(facc[2]), __float_as_uint(facc[3]));
                named_bar(2, 128);
                const uint32_t pg = sb + OFF_XS + prm.up_first * 1024 + (at & 63) * 16 + (w >> 1) * 8, pu = pg + 1024 - prm.up_first * 2048;
                const uint2 g1 = lds64(pg), u1 = lds64(pu);
                uint4* hp = prm.s->hid + cta * 32 - 512 + 16 * (w & 1) + 8 * (w >> 1) + g;
                asm volatile("" : "+l"(hp));
                mbar_wait(bar_fp);
                const uint2 g2 = lds64(pg + 2048), u2 = lds64(pu + 2048);
                const float ga = rbf(__uint_as_float(g1.x) + __uint_as_float(g2.x)), gb = rbf(__uint_as_float(g1.y) + __uint_as_float(g2.y));
                uint32_t hw = mul_bf2(pack_bf(__fdividef(ga, 1.0f + __expf(-ga)), __fdividef(gb, 1.0f + __expf(-gb))),
                                      pack_bf(__uint_as_float(u1.x) + __uint_as_float(u2.x), __uint_as_float(u1.y) + __uint_as_float(u2.y)));
                if (c == 2 * (w & 1) + (w >> 1)) hw = (hw & 0xFFFEFFFEu) | (tag & 1) | ((tag & 2) << 15);
                st_cell(hp, hw, __shfl_down_sync(0xffffffffu, hw, 1), __shfl_down_sync(0xffffffffu, hw, 2), __shfl_down_sync(0xffffffffu, hw, 3), has_gu && c == 0);
            }
            mbar_wait(bar_xb);
            load_x(0, 8);
            release(bar_xbfree);
            skip_term(0, 8);
            mbar_wait(bar_order2);
            static_for<NENT - FIN>([&](auto u) {
                run_small<1, FIN + u>(outB);
                if (u == FE) { wgmma_wait<2>(); if (lane == 0) mbar_arrive(bar_fold); }
            });
            wgmma_wait<0>();
            pin64(outB);
#pragma unroll
            for (int q = 0; q < 2; q++) {
                uint4 pb[16];
                mbar_wait(bar_accb + 8 * q);
#pragma unroll
                for (int v = q * HP; v < (q ? 16 : HP); v++) pb[v] = ldsm4(xbuf + sum_off(v));
#pragma unroll
                for (int v = q * HP; v < (q ? 16 : HP); v++) {
                    outB[4 * v] += __uint_as_float(pb[v].x); outB[4 * v + 1] += __uint_as_float(pb[v].y);
                    outB[4 * v + 2] += __uint_as_float(pb[v].z); outB[4 * v + 3] += __uint_as_float(pb[v].w);
                    if (v & 1) finish(outB, v >> 1, false);
                    if (v == DV) { gap(); if (lane == 0) mbar_expect_tx(bar_dn, w ? 0 : 7 * ABYTES); }
                }
            }
            finish_routed(outB);
        } else {
            float outA[64], outB[64], gacc[4];
            ring.slot = 32 % NST;
            ring.prev = bar_dummy;
            mbar_wait(bar_order1);
            run_entries<1, 2>(ring, 32, GU0 + 32, outA, outB, gacc, true, true);
            run_entries<1, 0>(ring, GU0 + 32, GU0 + 33, outA, outB, gacc, false, false, [&]() {
                pin4(gacc);
                sts128(sb + OFF_XS + 2048 + at * 16, __float_as_uint(gacc[0]), __float_as_uint(gacc[1]), __float_as_uint(gacc[2]), __float_as_uint(gacc[3]));
                __syncwarp();
                if (lane == 0) mbar_arrive(bar_fp);
            });
            mbar_wait(bar_xa);
            load_x(0, 2);
            run_entries<1, 0>(ring, GU0 + 33, GU0 + 34, outA, outB, gacc, false, false, [&]() { load_x(2, 3); });
            load_x(3, 5);
            run_entries<1, 0>(ring, GU0 + 34, GU0 + 35, outA, outB, gacc, false, false, [&]() { load_x(5, 6); });
            load_x(6, 8);
            run_entries<1, 0>(ring, GU0 + 35, GU0 + 36, outA, outB, gacc, false, false, [&]() { handover(bar_xafree); });
            skip_term(0, 3);
            run_entries<1, 0>(ring, GU0 + 36, GU0 + 37, outA, outB, gacc, false, false, [&]() { skip_term(3, 5); });
            skip_term(5, 8);
            run_entries<1, 0>(ring, GU0 + 37, FIN, outA, outB, gacc);
            auto dump = [&](int v) {
                stsm4(xbuf + sum_off(v), __float_as_uint(outB[4 * v]), __float_as_uint(outB[4 * v + 1]), __float_as_uint(outB[4 * v + 2]),
                      __float_as_uint(outB[4 * v + 3]));
            };
            static_for<NENT - FIN>([&](auto u) {
                mbar_wait(full + 8 * (FIN + u));
                run_small<0, FIN + u>(outA);
                if (u == 5 && lane == 0) mbar_arrive(bar_order2);
                wgmma_wait<1>();
                if (lane == 0) mbar_arrive(empty + 8 * (FIN + u - 1));
                if (u == 0) pin64(outB);
                if (u == 2) mbar_wait(empty + 8 * FIN);
                if (u >= 2) dump(u - 2);
            });
            const uint2 sk = lds64(sb + OFF_SEL + 8 * c), fk = lds64(sb + OFF_FAC + 8 * c);
            float* y0 = prm.out + (~sk.x & 2047u) * D_ + (cta & 15) * 64 + w * 16 + g;
            float* y1 = prm.out + (~sk.y & 2047u) * D_ + (cta & 15) * 64 + w * 16 + g;
            asm volatile("" : "+l"(y0), "+l"(y1));
            handover(bar_accb);
            wgmma_wait<0>();
            pin64(outA);
#pragma unroll
            for (int j = 0; j < 8; j++) {
                finish(outA, j, true);
            }
            mbar_wait(bar_fold);
#pragma unroll
            for (int v = 4; v < 16; v++) dump(v);
            handover(bar_accb + 8);
            finish_routed(outA);
            float yacc[4];
            const uint64_t dw = make_desc(sb), dh = (uint64_t)(((sb + OFF_XS) & 0x3FFFF) >> 4) | ((uint64_t)8 << 16) | ((uint64_t)8 << 32);
            mbar_wait(bar_zero);
            mbar_wait(bar_dn);
            wgmma_fence();
#pragma unroll
            for (int n = 0; n < 28; n++) wgmma_n8<1, 1>(yacc, dw + (dn_off(n >> 2) >> 4) + (n & 3) * 128, dh + n * 16, n > 0);
            wgmma_commit();
            wgmma_wait<0>();
            pin4(yacc);
            asm volatile("red.global.add.f32 [%0], %2; red.global.add.f32 [%1], %3; red.global.add.f32 [%0 + 32], %4; red.global.add.f32 [%1 + 32], %5;"
                         ::"l"(y0), "l"(y1), "f"(yacc[0] * __uint_as_float(fk.x)), "f"(yacc[1] * __uint_as_float(fk.y)), "f"(yacc[2] * __uint_as_float(fk.x)),
                         "f"(yacc[3] * __uint_as_float(fk.y)) : "memory");
        }
    }
}

typedef CUresult (*EncodeFn)(CUtensorMap*, CUtensorMapDataType, cuuint32_t, void*, const cuuint64_t*, const cuuint64_t*, const cuuint32_t*,
                             const cuuint32_t*, CUtensorMapInterleave, CUtensorMapSwizzle, CUtensorMapL2promotion, CUtensorMapFloatOOBfill);

bool encode(EncodeFn fn, CUtensorMap* m, const void* ptr, int rank, const cuuint64_t* dims, const cuuint64_t* strides, const cuuint32_t* box,
            CUtensorMapSwizzle sw = CU_TENSOR_MAP_SWIZZLE_128B, CUtensorMapL2promotion promo = CU_TENSOR_MAP_L2_PROMOTION_NONE) {
    const cuuint32_t es[5] = {1, 1, 1, 1, 1};
    return fn(m, CU_TENSOR_MAP_DATA_TYPE_BFLOAT16, rank, const_cast<void*>(ptr), dims, strides, box, es, CU_TENSOR_MAP_INTERLEAVE_NONE,
              sw, promo, CU_TENSOR_MAP_FLOAT_OOB_FILL_NONE) == CUDA_SUCCESS;
}

}

extern "C" void kernel_launch(void* const* d_in, const int* in_sizes, int n_in, void* d_out, int out_size) {
    (void)in_sizes; (void)n_in; (void)out_size;
    Params prm;
    prm.x = (const __nv_bfloat16*)d_in[0];
    prm.lam_re = (const __nv_bfloat16*)d_in[1];
    prm.lam_im = (const __nv_bfloat16*)d_in[2];
    prm.b_re = (const __nv_bfloat16*)d_in[3];
    prm.b_im = (const __nv_bfloat16*)d_in[4];
    prm.c_re = (const __nv_bfloat16*)d_in[5];
    prm.c_im = (const __nv_bfloat16*)d_in[6];
    prm.log_dt = (const __nv_bfloat16*)d_in[7];
    prm.dskip = (const __nv_bfloat16*)d_in[8];
    prm.w_r = (const __nv_bfloat16*)d_in[10];
    prm.gate_w = (const __nv_bfloat16*)d_in[14];
    prm.out = (float*)d_out;
    cudaGetSymbolAddress((void**)&prm.s, g_scratch);
    int dev = 0, sms = 0;
    cudaGetDevice(&dev);
    cudaDeviceGetAttribute(&sms, cudaDevAttrMultiProcessorCount, dev);
    auto kernel = sms == NGRID ? fused_kernel<true> : fused_kernel<false>;
    prm.swapped = prm.b_im < prm.b_re;

    void* fnp = nullptr;
    cudaDriverEntryPointQueryResult qr;
    cudaGetDriverEntryPoint("cuTensorMapEncodeTiled", &fnp, cudaEnableDefault, &qr);
    EncodeFn fn = (EncodeFn)fnp;
    cudaFuncSetAttribute(kernel, cudaFuncAttributeMaxDynamicSharedMemorySize, SMEM_BYTES);

    CUtensorMap mX, mB, mCre, mCim, mW, mWd, mXr, mXe;
    const cuuint64_t row = 2048;
    {
        const cuuint64_t dims[4] = {1024, 2, 4, 976}, st[3] = {row, 32 * row, 2 * row};
        const cuuint32_t box[4] = {64, 2, 4, 16};
        encode(fn, &mX, prm.x, 4, dims, st, box, CU_TENSOR_MAP_SWIZZLE_128B, PROMO);
    }
    {
        const char *lo = (const char*)(prm.swapped ? prm.b_im : prm.b_re), *hi = (const char*)(prm.swapped ? prm.b_re : prm.b_im);
        const cuuint64_t dims[5] = {1024, 8, 2, 96, 2}, st[4] = {row, (cuuint64_t)(hi - lo), 8 * row, 256 * row};
        const cuuint32_t box[5] = {64, 8, 2, 4, 2};
        encode(fn, &mB, lo, 5, dims, st, box, CU_TENSOR_MAP_SWIZZLE_128B, PROMO);
    }
    {
        const cuuint64_t dims[5] = {1024, 2, 4, 2, 64}, st[4] = {row, 4 * row, 2 * row, 16 * row};
        const cuuint32_t box[5] = {64, 2, 4, 2, 8};
        encode(fn, &mCre, prm.c_re, 5, dims, st, box);
        encode(fn, &mCim, prm.c_im, 5, dims, st, box);
    }
    {
        const char *pg = (const char*)d_in[11], *pu = (const char*)d_in[12];
        prm.up_first = pu < pg;
        const cuuint64_t dims[3] = {F_, D_, 2}, st[2] = {F_ * 2, (cuuint64_t)(pu < pg ? pg - pu : pu - pg)}, dimsd[2] = {D_, F_}, std_[1] = {row};
        const cuuint32_t box[3] = {32, 32, 2}, boxd[2] = {64, 64};
        encode(fn, &mW, pu < pg ? pu : pg, 3, dims, st, box, CU_TENSOR_MAP_SWIZZLE_64B, CU_TENSOR_MAP_L2_PROMOTION_NONE);
        encode(fn, &mWd, d_in[13], 2, dimsd, std_, boxd, CU_TENSOR_MAP_SWIZZLE_128B, CU_TENSOR_MAP_L2_PROMOTION_NONE);
    }
    {
        const cuuint64_t dims[3] = {D_ - 192, S_, 4}, st[2] = {row, 128};
        const cuuint32_t box[3] = {64, 16, 4};
        encode(fn, &mXr, prm.x, 3, dims, st, box, CU_TENSOR_MAP_SWIZZLE_128B, CU_TENSOR_MAP_L2_PROMOTION_NONE);
    }
    {
        const cuuint64_t dims[5] = {D_, 2, 2, 2, 976}, st[4] = {64 * row, row, 32 * row, 2 * row};
        const cuuint32_t box[5] = {64, 2, 2, 2, 8};
        encode(fn, &mXe, prm.x, 5, dims, st, box);
    }
    kernel<<<NGRID, 384, SMEM_BYTES, cudaStreamPerThread>>>(prm, mX, mB, mCre, mCim, mW, mWd, mXr, mXe);
}
```
